```python
import torch

def _softmax(x, axis=-1):
    return torch.softmax(x, dim=axis)

def _gelu(x):
    return torch.nn.functional.gelu(x, approximate='tanh')

def _silu(x):
    return torch.nn.functional.silu(x)

def _sigmoid(x):
    return torch.sigmoid(x)

def _layernorm(x, axis=-1, eps=1e-05):
    m = x.mean(dim=axis, keepdim=True)
    v = x.var(dim=axis, keepdim=True, unbiased=False)
    return (x - m) / torch.sqrt(v + eps)

def _scatter_add(tgt, idx, src, axis=0):
    return tgt.clone().index_add_(axis, idx, src)

def _segment_sum(src, seg, n):
    out = torch.zeros((n,) + src.shape[1:], dtype=src.dtype)
    return out.index_add_(0, seg, src)

def _pad(x, pw):
    flat = tuple((v for pair in reversed(pw) for v in pair))
    return torch.nn.functional.pad(x, flat)
kernel_name = 'gated_mix__memory_aug_recurrent_mem_tr__moe_arch_mod__prompt'

def setup_inputs():

    _w = lambda a: (lambda t: t.to(torch.bfloat16) if t.is_floating_point() else t)(torch.as_tensor(a))

    def _A_setup():
        B, S, Dm = (1, 2048, 1024)
        H, Dh = (32, 128)
        M, seg = (8, 32)
        seg = min(seg, S)
        S = S // seg * seg
        return {'x': _w((lambda *s: torch.randn(*s, dtype=torch.bfloat16) * 0.05)(B, S, Dm)), 'mem0': _w((lambda *s: torch.randn(*s, dtype=torch.bfloat16) * 0.8)(B, M, Dm)), 'Wq': _w((lambda *s: torch.randn(*s, dtype=torch.bfloat16) * 3.2)(Dm, H, Dh) * Dm ** (-0.5)), 'Wk': _w((lambda *s: torch.randn(*s, dtype=torch.bfloat16) * 3.2)(Dm, H, Dh) * Dm ** (-0.5)), 'Wv': _w((lambda *s: torch.randn(*s, dtype=torch.bfloat16) * 0.8)(Dm, H, Dh) * Dm ** (-0.5)), 'Wo': _w((lambda *s: torch.randn(*s, dtype=torch.bfloat16) * 0.8)(H, Dh, Dm) * (H * Dh) ** (-0.5)), 'seg_len': seg}
    _A_in = _A_setup()

    def _B_setup():
        B, S, D, F, C = (1, 2048, 1024, 3584, 8)
        return {'x': _w((lambda *s: torch.randn(*s, dtype=torch.bfloat16) * 0.05)(B, S, D)), 'w_r': _w((lambda *s: torch.randn(*s, dtype=torch.bfloat16) * 1.6)(D)), 'w_gate': _w((lambda *s: torch.randn(*s, dtype=torch.bfloat16) * 0.1)(D, F)), 'w_up': _w((lambda *s: torch.randn(*s, dtype=torch.bfloat16) * 0.1)(D, F)), 'w_down': _w((lambda *s: torch.randn(*s, dtype=torch.bfloat16) * 0.1)(F, D))}
    _B_in = _B_setup()
    return {'A_x': _A_in['x'], 'A_mem0': _A_in['mem0'], 'A_Wq': _A_in['Wq'], 'A_Wk': _A_in['Wk'], 'A_Wv': _A_in['Wv'], 'A_Wo': _A_in['Wo'], 'A_seg_len': _A_in['seg_len'], 'B_x': _B_in['x'], 'B_w_r': _B_in['w_r'], 'B_w_gate': _B_in['w_gate'], 'B_w_up': _B_in['w_up'], 'B_w_down': _B_in['w_down'], 'gate_w': _w((lambda *s: torch.randn(*s, dtype=torch.bfloat16) * 0.05)(1024) * 16.0)}

def reference(A_x, A_mem0, A_Wq, A_Wk, A_Wv, A_Wo, A_seg_len, B_x, B_w_r, B_w_gate, B_w_up, B_w_down, gate_w):

    def _A_ref(x, mem0, Wq, Wk, Wv, Wo, seg_len):
        B, S, Dm = x.shape
        H, Dh = (Wq.shape[1], Wq.shape[2])
        M = mem0.shape[1]
        scale = Dh ** (-0.5)
        n_seg = S // seg_len
        L = M + seg_len
        idx = torch.arange(L)
        mask = (idx[:, None] < M) | (idx[:, None] >= idx[None, :])
        mem = mem0
        outs = []
        for s in range(n_seg):
            xs = x[:, s * seg_len:(s + 1) * seg_len, :].clone()
            h = torch.concatenate([mem, xs], axis=1)
            q = torch.einsum('btd,dhe->bhte', h, Wq)
            k = torch.einsum('btd,dhe->bhte', h, Wk)
            v = torch.einsum('btd,dhe->bhte', h, Wv)
            scores = torch.einsum('bhqe,bhke->bhqk', q, k) * scale
            scores = torch.where(mask[None, None], scores, -1000000000.0)
            p = _softmax(scores, axis=-1)
            o = torch.einsum('bhqk,bhke->bhqe', p, v)
            o = torch.einsum('bhte,hed->btd', o, Wo)
            mem = o[:, :M, :].clone()
            outs.append(o[:, M:, :])
        return torch.concatenate(outs, axis=1)

    def _B_ref(x, w_r, w_gate, w_up, w_down):
        B, S, D = x.shape
        C = 8
        r = x @ w_r
        idx = torch.argsort(-r, axis=-1)[:, :C]
        idx_e = (lambda x, n, axis: torch.repeat_interleave(x, n, dim=axis))(idx.reshape(B, C, 1), D, axis=2)
        x_sel = (lambda x, i, axis: torch.take_along_dim(x, i, dim=axis))(x, idx_e, axis=1)
        g = _silu(x_sel @ w_gate)
        u = x_sel @ w_up
        y = g * u @ w_down
        r_sel = _sigmoid((lambda x, i, axis: torch.take_along_dim(x, i, dim=axis))(r, idx, axis=1))
        y = y * r_sel.reshape(B, C, 1)
        b_off = (torch.arange(B) * S).reshape(B, 1)
        flat_idx = (idx + b_off).reshape(B * C)
        zero = (x * 0.0).reshape(B * S, D)
        upd = _scatter_add(zero, flat_idx, y.reshape(B * C, D), axis=0)
        return x + upd.reshape(B, S, D)
    x = A_x
    g = _sigmoid((x * gate_w).sum(-1, keepdims=True))
    a = _A_ref(x, A_mem0, A_Wq, A_Wk, A_Wv, A_Wo, A_seg_len)
    b = _B_ref(x, B_w_r, B_w_gate, B_w_up, B_w_down)
    return g * a + (1 - g) * b
```

```cpp
#include <cuda_runtime.h>
#include <cuda_bf16.h>
#include <cuda_fp16.h>
#include <cuda.h>
#include <stdint.h>

typedef __nv_bfloat16 bf16;

#define S_TOK 2048
#define DM 1024
#define NH 32
#define DH 128
#define MM 8
#define SEG 32
#define NSEG 64
#define LL 40
#define FF 3584
#define NCTA 128

static __device__ bf16 g_ox[(size_t)S_TOK * NH * DH];
static __device__ float g_gate[S_TOK];
static __device__ float g_r[S_TOK];
static __device__ int g_idx[8];
static __device__ bf16 g_upd[8 * DM];

static __device__ __forceinline__ float rbf(float v) { return __bfloat162float(__float2bfloat16(v)); }
static __device__ __forceinline__ uint32_t smem_u32(const void* p) { return (uint32_t)__cvta_generic_to_shared(p); }
static __device__ __forceinline__ uint32_t pack_bf16(float lo, float hi) {
  __nv_bfloat162 v = __floats2bfloat162_rn(lo, hi);
  return *reinterpret_cast<uint32_t*>(&v);
}

static __device__ __forceinline__ void wg_fence() { asm volatile("wgmma.fence.sync.aligned;" ::: "memory"); }
static __device__ __forceinline__ void wg_commit() { asm volatile("wgmma.commit_group.sync.aligned;" ::: "memory"); }
static __device__ __forceinline__ void wg_wait0() { asm volatile("wgmma.wait_group.sync.aligned 0;" ::: "memory"); }
static __device__ __forceinline__ void fence_async_smem() { asm volatile("fence.proxy.async.shared::cta;" ::: "memory"); }

static __device__ __forceinline__ uint64_t make_desc(uint32_t addr, uint32_t lbo, uint32_t sbo) {
  uint64_t d = 0;
  d |= (uint64_t)((addr & 0x3FFFF) >> 4);
  d |= (uint64_t)((lbo >> 4) & 0x3FFF) << 16;
  d |= (uint64_t)((sbo >> 4) & 0x3FFF) << 32;
  d |= (uint64_t)1 << 62;
  return d;
}

#define DESC_HI(sbo) (((sbo) >> 4) | (1u << 30))
template <int OFF, int SCALE>
static __device__ __forceinline__ void wgmma_n32_ra(float (&d)[16], const uint32_t (&a)[4], uint32_t base16) {
  asm volatile(
      "{\n.reg .b32 t;\n.reg .b64 dd;\nadd.u32 t, %20, %21;\nmov.b64 dd, {t, %22};\n"
      "wgmma.mma_async.sync.aligned.m64n32k16.f32.bf16.bf16 "
      "{%0,%1,%2,%3,%4,%5,%6,%7,%8,%9,%10,%11,%12,%13,%14,%15}, {%16,%17,%18,%19}, dd, %23, 1, 1, 0;\n}"
      : "+f"(d[0]), "+f"(d[1]), "+f"(d[2]), "+f"(d[3]), "+f"(d[4]), "+f"(d[5]), "+f"(d[6]), "+f"(d[7]),
        "+f"(d[8]), "+f"(d[9]), "+f"(d[10]), "+f"(d[11]), "+f"(d[12]), "+f"(d[13]), "+f"(d[14]), "+f"(d[15])
      : "r"(a[0]), "r"(a[1]), "r"(a[2]), "r"(a[3]), "r"(base16), "n"(OFF >> 4), "n"(DESC_HI(1024)), "n"(SCALE));
}
template <int AOFF, int BOFF, int SCALE>
static __device__ __forceinline__ void wgmma_n32_ss_ta(float (&d)[16], uint32_t abase16, uint32_t bbase16) {
  asm volatile(
      "{\n.reg .b32 t, u;\n.reg .b64 da, db;\nadd.u32 t, %16, %18;\nmov.b64 da, {t, %20};\nadd.u32 u, %17, %19;\nmov.b64 db, {u, %20};\n"
      "wgmma.mma_async.sync.aligned.m64n32k16.f32.bf16.bf16 "
      "{%0,%1,%2,%3,%4,%5,%6,%7,%8,%9,%10,%11,%12,%13,%14,%15}, da, db, %21, 1, 1, 1, 0;\n}"
      : "+f"(d[0]), "+f"(d[1]), "+f"(d[2]), "+f"(d[3]), "+f"(d[4]), "+f"(d[5]), "+f"(d[6]), "+f"(d[7]),
        "+f"(d[8]), "+f"(d[9]), "+f"(d[10]), "+f"(d[11]), "+f"(d[12]), "+f"(d[13]), "+f"(d[14]), "+f"(d[15])
      : "r"(abase16), "r"(bbase16), "n"(AOFF >> 4), "n"(BOFF >> 4), "n"(DESC_HI(1024)), "n"(SCALE));
}
static __device__ __forceinline__ void ldmatrix_x4_trans(uint32_t (&r)[4], uint32_t addr) {
  asm volatile("ldmatrix.sync.aligned.m8n8.x4.trans.shared.b16 {%0,%1,%2,%3}, [%4];"
               : "=r"(r[0]), "=r"(r[1]), "=r"(r[2]), "=r"(r[3]) : "r"(addr) : "memory");
}
static __device__ __forceinline__ void mma_16816(float (&d)[4], const uint32_t (&a)[4], uint32_t b0, uint32_t b1) {
  asm volatile("mma.sync.aligned.m16n8k16.row.col.f32.bf16.bf16.f32 {%0,%1,%2,%3}, {%4,%5,%6,%7}, {%8,%9}, {%0,%1,%2,%3};"
               : "+f"(d[0]), "+f"(d[1]), "+f"(d[2]), "+f"(d[3])
               : "r"(a[0]), "r"(a[1]), "r"(a[2]), "r"(a[3]), "r"(b0), "r"(b1));
}

static __device__ __forceinline__ uint32_t mapa(uint32_t addr, uint32_t rank) {
  uint32_t r; asm volatile("mapa.shared::cluster.u32 %0, %1, %2;" : "=r"(r) : "r"(addr), "r"(rank)); return r;
}

static __device__ __forceinline__ void mbar_init(uint32_t bar, int cnt) {
  asm volatile("mbarrier.init.shared::cta.b64 [%0], %1;" :: "r"(bar), "r"(cnt) : "memory");
}
static __device__ __forceinline__ void mbar_expect_tx(uint32_t bar, uint32_t bytes) {
  asm volatile("mbarrier.arrive.expect_tx.shared::cta.b64 _, [%0], %1;" :: "r"(bar), "r"(bytes) : "memory");
}
static __device__ __forceinline__ void tma_load_2d(uint32_t dst, const CUtensorMap* tm, int c0, int c1, uint32_t bar) {
  asm volatile("cp.async.bulk.tensor.2d.shared::cluster.global.mbarrier::complete_tx::bytes [%0], [%1, {%3, %4}], [%2];"
               :: "r"(dst), "l"(tm), "r"(bar), "r"(c0), "r"(c1) : "memory");
}

static __device__ unsigned char g_win[6 << 20];
static __device__ unsigned int g_side[67 * 32];
static __device__ unsigned int g_err;
#define W_UP (1u << 20)
#define W_2 (2u << 20)
static __device__ __forceinline__ uint32_t w_blk(uint32_t off, uint32_t side) { return off | (((__popc((off >> 12) & 0xb3u) ^ side) & 1u) << 12); }
static __device__ __forceinline__ uint32_t w_h1(int c) { return W_UP | (1u << 13) | ((c >> 1) << 14) | ((c & 1) << 11); }
static __device__ __forceinline__ uint32_t w_ar(int s) { return ((s & 1) << 15) | ((s & 2) << 17); }
static __device__ __forceinline__ uint32_t w_mvx(int c, int s) { return W_2 | ((s & 1) << 20) | ((c >> 1) << 14) | ((c & 1) << 11); }
static __device__ __forceinline__ uint32_t w_mxa(int c, int s) { return W_2 | ((s & 1) << 20) | (1u << 13) | ((c >> 1) << 14) | ((c & 1) << 11); }
#define H1_V (1u << 13)

#define SPIN_LIMIT (1 << 18)

#define SM_X 0
#define SM_WOS 65536
#define SM_WVS 131072
#define SM_MEM 163840
#define SM_QKP 180224
#define SM_VP 184320
#define SM_CW 188416
#define SM_VST 196608
#define SM_VR 196608
#define SM_CQ 200704
#define SM_CV 208896
#define SM_XF 217088
#define SM_VL 221184
#define SM_OF 225280
#define SM_OX 227328
#define SM_PF 229376
#define SM_PX 230016
#define SM_RD 223232
#define SM_XS 231168
#define SM_BAR 231808
#define SM_TAB 231936
#define SM_TS 232064
#define NTS 40
#define SM_TOTAL SM_TS
#define MB_F 0
#define MB_XE0 16
#define MB_XE1 112
#define MB_INIT 24
#define MB_MEM 32
#define MB_W 48
#define MB_XF 64
#define MB_VR 72
#define MB_X0 80
#define MB_WO 88
#define SM_SIDE (SM_BAR + 96)
#define MB_PX 120
#define B_QK 1
#define B_V 2
#define B_P 3
#define B_O 4
#define B_M2 5
#define B_PUB 6
#define B_CQ 7
#define B_QK1 8
#define B_ALL 9
#define B_PXF 10
#define B_CV 15
#define B_X2 11
#define B_PX 12
#define B_GO 14
#define B_RD 13

#define TST(a, b, c, d)
#define TSF(i, w)
#define TSP(i, w)
#define TVF(i, v)
#define TS(i)
#define TV(i, v)

static __device__ __forceinline__ void bar_sync(int id, int n) { asm volatile("bar.sync %0, %1;" :: "r"(id), "r"(n) : "memory"); }
static __device__ __forceinline__ void bar_arrive(int id, int n) { asm volatile("bar.arrive %0, %1;" :: "r"(id), "r"(n) : "memory"); }
static __device__ __forceinline__ uint4 ldg_r4(const void* p) { uint4 v;
  asm volatile("ld.relaxed.gpu.global.v4.u32 {%0,%1,%2,%3}, [%4];" : "=r"(v.x), "=r"(v.y), "=r"(v.z), "=r"(v.w) : "l"(p) : "memory"); return v; }
static __device__ __forceinline__ uint32_t ldg_r1(const void* p) { uint32_t v;
  asm volatile("ld.relaxed.gpu.global.u32 %0, [%1];" : "=r"(v) : "l"(p) : "memory"); return v; }
template <int OFF> static __device__ __forceinline__ uint32_t ldg_r1o(const void* p) { uint32_t v;
  asm volatile("ld.relaxed.gpu.global.u32 %0, [%1+%2];" : "=r"(v) : "l"(p), "n"(OFF) : "memory"); return v; }
static __device__ __forceinline__ void stg_r4(void* p, uint32_t a, uint32_t b, uint32_t c, uint32_t d) {
  asm volatile("st.relaxed.gpu.global.v4.u32 [%0], {%1,%2,%3,%4};" :: "l"(p), "r"(a), "r"(b), "r"(c), "r"(d) : "memory"); }
static __device__ __forceinline__ void stg_r2(void* p, uint32_t a, uint32_t b) {
  asm volatile("st.relaxed.gpu.global.v2.u32 [%0], {%1,%2};" :: "l"(p), "r"(a), "r"(b) : "memory"); }
static __device__ __forceinline__ uint2 ldg_r2(const void* p) { uint2 v;
  asm volatile("ld.relaxed.gpu.global.v2.u32 {%0,%1}, [%2];" : "=r"(v.x), "=r"(v.y) : "l"(p) : "memory"); return v; }
static __device__ __forceinline__ void stg_4(void* p, const uint4& v) {
  asm volatile("st.global.v4.u32 [%0], {%1,%2,%3,%4};" :: "l"(p), "r"(v.x), "r"(v.y), "r"(v.z), "r"(v.w) : "memory"); }
static __device__ __forceinline__ uint32_t f2u(float v) { return __float_as_uint(v); }
static __device__ __forceinline__ void stg_2(void* p, uint32_t a, uint32_t b) {
  asm volatile("st.global.v2.u32 [%0], {%1,%2};" :: "l"(p), "r"(a), "r"(b) : "memory"); }
static __device__ __forceinline__ void stg_r1(void* p, uint32_t a) {
  asm volatile("st.relaxed.gpu.global.u32 [%0], %1;" :: "l"(p), "r"(a) : "memory"); }
static __device__ __forceinline__ void sts128(uint32_t a, uint32_t x, uint32_t y, uint32_t z, uint32_t w) {
  asm volatile("st.shared.v4.u32 [%0], {%1,%2,%3,%4};" :: "r"(a), "r"(x), "r"(y), "r"(z), "r"(w) : "memory"); }
static __device__ __forceinline__ void sts128f(uint32_t a, float x, float y, float z, float w) {
  asm volatile("st.shared.v4.f32 [%0], {%1,%2,%3,%4};" :: "r"(a), "f"(x), "f"(y), "f"(z), "f"(w) : "memory"); }
static __device__ __forceinline__ uint4 lds128(uint32_t a) { uint4 v;
  asm volatile("ld.shared.v4.u32 {%0,%1,%2,%3}, [%4];" : "=r"(v.x), "=r"(v.y), "=r"(v.z), "=r"(v.w) : "r"(a) : "memory"); return v; }
static __device__ __forceinline__ float4 lds128f(uint32_t a) { float4 v;
  asm volatile("ld.shared.v4.f32 {%0,%1,%2,%3}, [%4];" : "=f"(v.x), "=f"(v.y), "=f"(v.z), "=f"(v.w) : "r"(a) : "memory"); return v; }
static __device__ __forceinline__ void sts32(uint32_t a, uint32_t x) { asm volatile("st.shared.u32 [%0], %1;" :: "r"(a), "r"(x) : "memory"); }
static __device__ __forceinline__ void sts64f(uint32_t a, float x, float y) { asm volatile("st.shared.v2.f32 [%0], {%1,%2};" :: "r"(a), "f"(x), "f"(y) : "memory"); }
static __device__ __forceinline__ uint2 lds64(uint32_t a) { uint2 v;
  asm volatile("ld.shared.v2.u32 {%0,%1}, [%2];" : "=r"(v.x), "=r"(v.y) : "r"(a) : "memory"); return v; }
static __device__ __forceinline__ void st_async4(uint32_t ra, float x, float y, float z, float w, uint32_t rbar) {
  asm volatile("st.async.weak.shared::cluster.mbarrier::complete_tx::bytes.v4.f32 [%0], {%1,%2,%3,%4}, [%5];"
               :: "r"(ra), "f"(x), "f"(y), "f"(z), "f"(w), "r"(rbar) : "memory"); }
static __device__ __forceinline__ void stsm4t(uint32_t a, uint32_t x, uint32_t y, uint32_t z, uint32_t w) {
  asm volatile("stmatrix.sync.aligned.m8n8.x4.trans.shared.b16 [%0], {%1,%2,%3,%4};" :: "r"(a), "r"(x), "r"(y), "r"(z), "r"(w) : "memory"); }
static __device__ __forceinline__ uint4 ldsm4(uint32_t a) { uint4 v;
  asm volatile("ldmatrix.sync.aligned.m8n8.x4.shared.b16 {%0,%1,%2,%3}, [%4];" : "=r"(v.x), "=r"(v.y), "=r"(v.z), "=r"(v.w) : "r"(a) : "memory"); return v; }
static __device__ __forceinline__ uint4 ldsm4t(uint32_t a) { uint4 v;
  asm volatile("ldmatrix.sync.aligned.m8n8.x4.trans.shared.b16 {%0,%1,%2,%3}, [%4];" : "=r"(v.x), "=r"(v.y), "=r"(v.z), "=r"(v.w) : "r"(a) : "memory"); return v; }
static __device__ __forceinline__ uint32_t movm(uint32_t a) { uint32_t d;
  asm volatile("movmatrix.sync.aligned.m8n8.trans.b16 %0, %1;" : "=r"(d) : "r"(a)); return d; }
static __device__ __forceinline__ float u2f(uint32_t v) { return __uint_as_float(v); }
static __device__ __forceinline__ uint32_t nz(uint32_t w) { return w == 0u ? 0x8000u : w; }
static __device__ __forceinline__ uint32_t tagw(uint32_t w, uint32_t t) { uint32_t d;
  asm("lop3.b32 %0, %1, %2, 1, 0xd8;" : "=r"(d) : "r"(w), "r"(t)); return d; }
static __device__ __forceinline__ uint32_t pack_m2(float lo, float hi, uint32_t t) { return tagw(pack_bf16(lo, hi), t); }
static __device__ __forceinline__ uint32_t pack_f16(float lo, float hi) { uint32_t d;
  asm("cvt.rn.satfinite.f16x2.f32 %0, %1, %2;" : "=r"(d) : "f"(hi), "f"(lo)); return d; }
static __device__ __forceinline__ void sum_h4(float& lo, float& hi, uint32_t a, uint32_t b, uint32_t c, uint32_t d) {
  const float2 x = __half22float2(*reinterpret_cast<__half2*>(&a)), y = __half22float2(*reinterpret_cast<__half2*>(&b));
  const float2 z = __half22float2(*reinterpret_cast<__half2*>(&c)), w = __half22float2(*reinterpret_cast<__half2*>(&d));
  lo = (x.x + y.x) + (z.x + w.x); hi = (x.y + y.y) + (z.y + w.y);
}
static __device__ __forceinline__ uint32_t lds32(uint32_t a) { uint32_t v; asm volatile("ld.shared.u32 %0, [%1];" : "=r"(v) : "r"(a) : "memory"); return v; }
static __device__ __forceinline__ uint32_t addb2(uint32_t a, uint32_t b) { uint32_t d;
  asm("add.rn.bf16x2 %0, %1, %2;" : "=r"(d) : "r"(a), "r"(b)); return d; }
static __device__ __forceinline__ uint32_t x3(uint32_t a, uint32_t b, uint32_t t) { uint32_t d;
  asm("lop3.b32 %0, %1, %2, %3, 0x7e;" : "=r"(d) : "r"(a), "r"(b), "r"(t)); return d; }
static __device__ __forceinline__ uint32_t or3(uint32_t a, uint32_t b, uint32_t c) { uint32_t d;
  asm("lop3.b32 %0, %1, %2, %3, 0xfe;" : "=r"(d) : "r"(a), "r"(b), "r"(c)); return d; }
static __device__ __forceinline__ uint32_t bad4(const uint4& u, uint32_t t) { return x3(u.x, u.y, t) | x3(u.z, u.w, t); }
static __device__ __forceinline__ uint32_t bad8(const uint4& u, const uint4& v, uint32_t t) {
  return or3(x3(u.x, u.y, t), x3(u.z, u.w, t), x3(v.x, v.y, t)) | x3(v.z, v.w, t); }
static __device__ __forceinline__ float ex2(float x) { float y; asm("ex2.approx.ftz.f32 %0, %1;" : "=f"(y) : "f"(x)); return y; }
static __device__ __forceinline__ float rcpf(float x) { float y; asm("rcp.approx.ftz.f32 %0, %1;" : "=f"(y) : "f"(x)); return y; }
static __device__ __forceinline__ void mbar_wait(uint32_t bar, int parity) {
  asm volatile("{\n.reg .pred p, q;\n.reg .u32 n;\nmbarrier.try_wait.parity.shared::cta.b64 p, [%0], %1;\n@p bra W_DONE;\nmov.u32 n, 0;\n"
               "W_LOOP:\nmbarrier.try_wait.parity.shared::cta.b64 p, [%0], %1;\nadd.u32 n, n, 1;\nsetp.lt.and.u32 q, n, %2, !p;\n@q bra W_LOOP;\nW_DONE:\n}"
               :: "r"(bar), "r"(parity), "n"(SPIN_LIMIT) : "memory");
}
static __device__ __forceinline__ uint32_t mbar_test(uint32_t bar, int parity) { uint32_t ok;
  asm volatile("{\n.reg .pred p;\nmbarrier.test_wait.parity.shared::cta.b64 p, [%1], %2;\nselp.u32 %0, 1, 0, p;\n}" : "=r"(ok) : "r"(bar), "r"(parity) : "memory"); return ok; }
static __device__ __forceinline__ void mbar_arrive(uint32_t bar) {
  asm volatile("mbarrier.arrive.shared::cta.b64 _, [%0];" :: "r"(bar) : "memory"); }
static __device__ __forceinline__ void mbar_arrive_cluster_rlx(uint32_t raddr) {
  asm volatile("mbarrier.arrive.relaxed.cluster.shared::cluster.b64 _, [%0];" :: "r"(raddr) : "memory"); }
static __device__ __forceinline__ void tma_load_mc(uint32_t dst, const CUtensorMap* tm, int c1, int c2, uint32_t bar) {
  asm volatile("cp.async.bulk.tensor.3d.shared::cluster.global.mbarrier::complete_tx::bytes.multicast::cluster [%0], [%1, {%3, %4, %5}], [%2], %6;"
               :: "r"(dst), "l"(tm), "r"(bar), "r"(0), "r"(c1), "r"(c2), "h"((uint16_t)3) : "memory"); }
static __device__ __forceinline__ void cp16(uint32_t dst, const void* src) {
  asm volatile("cp.async.cg.shared.global [%0], [%1], 16;" :: "r"(dst), "l"(src) : "memory"); }
static __device__ __forceinline__ void mma_1688(float (&d)[4], uint32_t a0, uint32_t a1, uint32_t b0) {
  asm volatile("mma.sync.aligned.m16n8k8.row.col.f32.bf16.bf16.f32 {%0,%1,%2,%3}, {%4,%5}, {%6}, {%0,%1,%2,%3};"
               : "+f"(d[0]), "+f"(d[1]), "+f"(d[2]), "+f"(d[3]) : "r"(a0), "r"(a1), "r"(b0)); }
static __device__ __forceinline__ void mma4(float (&d)[4], uint32_t a0, uint32_t a1, uint32_t a2, uint32_t a3, uint32_t b0, uint32_t b1) {
  asm volatile("mma.sync.aligned.m16n8k16.row.col.f32.bf16.bf16.f32 {%0,%1,%2,%3}, {%4,%5,%6,%7}, {%8,%9}, {%0,%1,%2,%3};"
               : "+f"(d[0]), "+f"(d[1]), "+f"(d[2]), "+f"(d[3]) : "r"(a0), "r"(a1), "r"(a2), "r"(a3), "r"(b0), "r"(b1)); }
static __device__ __forceinline__ void mma4z(float (&d)[4], uint32_t a0, uint32_t a1, uint32_t a2, uint32_t a3, uint32_t b0, uint32_t b1) {
  asm volatile("mma.sync.aligned.m16n8k16.row.col.f32.bf16.bf16.f32 {%0,%1,%2,%3}, {%4,%5,%6,%7}, {%8,%9}, {%10,%10,%10,%10};"
               : "=f"(d[0]), "=f"(d[1]), "=f"(d[2]), "=f"(d[3]) : "r"(a0), "r"(a1), "r"(a2), "r"(a3), "r"(b0), "r"(b1), "f"(0.f)); }
static __device__ __forceinline__ void mma4h(float (&d)[4], uint32_t a0, uint32_t a1, uint32_t a2, uint32_t a3, uint32_t b) {
  asm volatile("mma.sync.aligned.m16n8k16.row.col.f32.f16.f16.f32 {%0,%1,%2,%3}, {%4,%5,%6,%7}, {%8,%8}, {%0,%1,%2,%3};"
               : "+f"(d[0]), "+f"(d[1]), "+f"(d[2]), "+f"(d[3]) : "r"(a0), "r"(a1), "r"(a2), "r"(a3), "r"(b)); }
static __device__ __forceinline__ void mma2h(float (&d)[4], uint32_t a0, uint32_t a1, uint32_t b) {
  asm volatile("mma.sync.aligned.m16n8k8.row.col.f32.f16.f16.f32 {%0,%1,%2,%3}, {%4,%5}, {%6}, {%0,%1,%2,%3};"
               : "+f"(d[0]), "+f"(d[1]), "+f"(d[2]), "+f"(d[3]) : "r"(a0), "r"(a1), "r"(b)); }
static __device__ __forceinline__ uint32_t clk32() { uint32_t t; asm volatile("mov.u32 %0, %%clock;" : "=r"(t)); return t; }
static __device__ __forceinline__ uint32_t gt32() { uint32_t t; asm volatile("mov.u32 %0, %%globaltimer_lo;" : "=r"(t)); return t; }
static __device__ __forceinline__ void spin(int clk) { if (clk > 0) { uint32_t t = clk32(); while (clk32() - t < (uint32_t)clk) {} } }
#define FENCE() asm volatile("griddepcontrol.launch_dependents;" ::: "memory")
#define OPAQUE_L(p) asm volatile("" : "+l"(p))
#define OPAQUE_R(p) asm volatile("" : "+r"(p))

template <int KK, int K1, int W0, int NW, int FIRST> struct XR {
  static __device__ __forceinline__ void run(float (&d)[16], const uint32_t (&w)[NW][4], uint32_t b16) {
    wgmma_n32_ra<(KK >> 2) * 4096 + (KK & 3) * 32, !FIRST>(d, w[W0 + KK], b16);
    XR<KK + 1, K1, W0, NW, 0>::run(d, w, b16);
  }
};
template <int K1, int W0, int NW, int FIRST> struct XR<K1, K1, W0, NW, FIRST> { static __device__ __forceinline__ void run(float (&)[16], const uint32_t (&)[NW][4], uint32_t) {} };
template <int KK, int K0, int K1, int FIRST> struct XS {
  static __device__ __forceinline__ void run(float (&d)[16], uint32_t a16, uint32_t b16) {
    wgmma_n32_ss_ta<(KK - K0) * 2048, (KK >> 2) * 4096 + (KK & 3) * 32, !FIRST>(d, a16, b16);
    XS<KK + 1, K0, K1, 0>::run(d, a16, b16);
  }
};
template <int K0, int K1, int FIRST> struct XS<K1, K0, K1, FIRST> { static __device__ __forceinline__ void run(float (&)[16], uint32_t, uint32_t) {} };

static __device__ bf16 g_h[8 * FF];
static __device__ unsigned int g_sbar;
struct SideParams { const bf16* x; const bf16* w_r; const bf16* w_gate; const bf16* w_up; const bf16* w_down; const bf16* gate_w; const bf16* Wo; };

static __device__ __forceinline__ void side_barrier(unsigned int target) {
  __syncthreads();
  if (threadIdx.x == 0) {
    __threadfence();
    atomicAdd(&g_sbar, 1u);
    int n = 0;
    while (*(volatile unsigned int*)&g_sbar < target) { if (++n > (1 << 22)) { g_err = 50; break; } }
    __threadfence();
  }
  __syncthreads();
}
static __device__ __forceinline__ uint4 ldg_nc(const void* p) { uint4 v;
  asm volatile("ld.global.nc.L1::no_allocate.v4.u32 {%0,%1,%2,%3}, [%4];" : "=r"(v.x), "=r"(v.y), "=r"(v.z), "=r"(v.w) : "l"(p)); return v; }
static __device__ __forceinline__ uint4 ldg_st(const void* p) { uint4 v;
  asm volatile("ld.global.nc.L1::no_allocate.v4.u32 {%0,%1,%2,%3}, [%4];" : "=r"(v.x), "=r"(v.y), "=r"(v.z), "=r"(v.w) : "l"(p));
  return v; }
static __device__ __forceinline__ void mm8(float (&acc)[8][4], const bf16* W, int ldw, int nk16, uint32_t abase, int lane) {
  const int g = lane >> 2, t = lane & 3;
  const bf16* wp = W + (size_t)(2 * t) * ldw + g * 8;
#pragma unroll 1
  for (int k = 0; k < nk16; k += 4) {
    uint4 r[4][4];
#pragma unroll
    for (int u = 0; u < 4; u++) {
      const bf16* q = wp + (size_t)(k + u) * 16 * ldw;
      r[u][0] = ldg_st(q); r[u][1] = ldg_st(q + ldw); r[u][2] = ldg_st(q + 8 * ldw); r[u][3] = ldg_st(q + 9 * ldw);
    }
#pragma unroll
    for (int u = 0; u < 4; u++) {
      uint32_t a0, a2;
      asm volatile("ld.shared.u32 %0, [%1];" : "=r"(a0) : "r"(abase + (k + u) * 32));
      asm volatile("ld.shared.u32 %0, [%1];" : "=r"(a2) : "r"(abase + (k + u) * 32 + 16));
      const uint32_t* p0 = reinterpret_cast<const uint32_t*>(&r[u][0]); const uint32_t* p1 = reinterpret_cast<const uint32_t*>(&r[u][1]);
      const uint32_t* p2 = reinterpret_cast<const uint32_t*>(&r[u][2]); const uint32_t* p3 = reinterpret_cast<const uint32_t*>(&r[u][3]);
#pragma unroll
      for (int i = 0; i < 8; i++) {
        const uint32_t sel = (i & 1) ? 0x7632u : 0x5410u;
        mma4(acc[i], a0, 0u, a2, 0u, __byte_perm(p0[i >> 1], p1[i >> 1], sel), __byte_perm(p2[i >> 1], p3[i >> 1], sel));
      }
    }
  }
}
static __device__ __noinline__ void side_work(const SideParams& P, unsigned char* smem, int q) {
  const int tid = threadIdx.x, lane = tid & 31, warp = tid >> 5, g = lane >> 2, t = lane & 3;
  const uint32_t sb = smem_u32(smem);
  unsigned int* cand = reinterpret_cast<unsigned int*>(smem);
  bf16* xs = reinterpret_cast<bf16*>(smem + 1024);
  float* part = reinterpret_cast<float*>(smem + 65536);
  {
    uint4 gw[4], wr[4];
#pragma unroll
    for (int i = 0; i < 4; i++) { gw[i] = ldg_nc(P.gate_w + i * 256 + lane * 8); wr[i] = ldg_nc(P.w_r + i * 256 + lane * 8); }
#pragma unroll 1
    for (int it = warp * 4; it < 512; it += 48) {
      uint4 xv[4][4];
#pragma unroll
      for (int u = 0; u < 4; u++)
#pragma unroll
        for (int i = 0; i < 4; i++) xv[u][i] = ldg_nc(P.x + (size_t)(q * 512 + it + u) * DM + i * 256 + lane * 8);
#pragma unroll
      for (int u = 0; u < 4; u++) {
        float sg = 0.f, sr = 0.f;
#pragma unroll
        for (int i = 0; i < 4; i++) {
          const uint32_t* a = reinterpret_cast<const uint32_t*>(&xv[u][i]); const uint32_t* b = reinterpret_cast<const uint32_t*>(&gw[i]);
          const uint32_t* c = reinterpret_cast<const uint32_t*>(&wr[i]);
#pragma unroll
          for (int e = 0; e < 4; e++) {
            const float x0 = u2f(a[e] << 16), x1 = u2f(a[e] & 0xffff0000u);
            sg += rbf(x0 * u2f(b[e] << 16)) + rbf(x1 * u2f(b[e] & 0xffff0000u));
            sr = fmaf(x0, u2f(c[e] << 16), fmaf(x1, u2f(c[e] & 0xffff0000u), sr));
          }
        }
        for (int o = 16; o; o >>= 1) { sg += __shfl_xor_sync(~0u, sg, o); sr += __shfl_xor_sync(~0u, sr, o); }
        if (lane == 0) {
          const int tok = q * 512 + it + u;
          g_gate[tok] = rbf(1.f / (1.f + expf(-rbf(sg))));
          g_r[tok] = rbf(sr);
        }
      }
    }
  }
  side_barrier(4);
  {
    unsigned int key[8];
#pragma unroll
    for (int i = 0; i < 8; i++) {
      const int tok = (warp & 7) * 256 + i * 32 + lane;
      const uint32_t b = __float_as_uint(__ldcg(&g_r[tok]) + 0.f) >> 16;
      key[i] = (((b & 0x8000u) ? (~b & 0xffffu) : (b | 0x8000u)) << 16) | (uint32_t)(2047 - tok);
    }
    for (int pass = 0; pass < 2; pass++) {
      if (pass == 0 ? warp < 8 : warp == 0) {
        for (int c = 0; c < 8; c++) {
          const unsigned int m = __reduce_max_sync(~0u, max(max(max(key[0], key[1]), max(key[2], key[3])), max(max(key[4], key[5]), max(key[6], key[7]))));
#pragma unroll
          for (int i = 0; i < 8; i++) if (key[i] == m) key[i] = 0u;
          if (lane == 0) cand[pass ? 128 + c : warp * 8 + c] = m;
        }
      }
      __syncthreads();
      if (pass == 0 && warp == 0) {
#pragma unroll
        for (int i = 0; i < 8; i++) key[i] = i < 2 ? cand[i * 32 + lane] : 0u;
      }
    }
    if (q == 0 && tid < 8) g_idx[tid] = 2047 - (int)(cand[128 + tid] & 0xffffu);
    for (int i = tid; i < 1024; i += 384) {
      const int c = i >> 7, tok = 2047 - (int)(cand[128 + c] & 0xffffu);
      *reinterpret_cast<uint4*>(xs + c * (FF + 8) + (i & 127) * 8) = ldg_nc(P.x + (size_t)tok * DM + (i & 127) * 8);
    }
    __syncthreads();
  }
  const uint32_t abase = sb + 1024 + g * (FF + 8) * 2 + t * 4;
  for (int u = warp; u < 56; u += 12) {
    const int kh = u / 28, mat = (u % 28) / 14, cb = u % 14;
    float acc[8][4];
#pragma unroll
    for (int i = 0; i < 8; i++) acc[i][0] = acc[i][1] = acc[i][2] = acc[i][3] = 0.f;
    mm8(acc, (mat ? P.w_up : P.w_gate) + (size_t)kh * 512 * FF + q * 896 + cb * 64, FF, DM / 32, abase + kh * 1024, lane);
    float* pp = part + ((kh * 2 + mat) * 8 + g) * 896 + cb * 64 + 16 * t;
#pragma unroll
    for (int i = 0; i < 8; i++) { pp[i] = acc[i][0]; pp[8 + i] = acc[i][1]; }
  }
  __syncthreads();
  for (int i = tid; i < 8 * 896; i += 384) {
    const float ag = rbf(part[i] + part[16 * 896 + i]), au = rbf(part[8 * 896 + i] + part[24 * 896 + i]);
    g_h[(i / 896) * FF + q * 896 + i % 896] = __float2bfloat16(rbf(ag / (1.f + expf(-ag))) * au);
  }
  side_barrier(8);
  for (int i = tid; i < 8 * FF / 8; i += 384) {
    const int c = i / (FF / 8), o = i % (FF / 8);
    *reinterpret_cast<uint4*>(xs + c * (FF + 8) + o * 8) = __ldcg(reinterpret_cast<const uint4*>(g_h + c * FF + o * 8));
  }
  __syncthreads();
  {
    const int cb = warp & 3, kq = warp >> 2;
    float acc[8][4];
#pragma unroll
    for (int i = 0; i < 8; i++) acc[i][0] = acc[i][1] = acc[i][2] = acc[i][3] = 0.f;
    mm8(acc, P.w_down + (size_t)kq * 1216 * DM + q * 256 + cb * 64, DM, kq == 2 ? 72 : 76, abase + kq * 1216 * 2, lane);
#pragma unroll
    for (int i = 0; i < 8; i++) { part[(kq * 8 + g) * 256 + cb * 64 + 16 * t + i] = acc[i][0]; part[(kq * 8 + g) * 256 + cb * 64 + 16 * t + 8 + i] = acc[i][1]; }
    __syncthreads();
    for (int i = tid; i < 2048; i += 384) {
      const int c = i >> 8, tok = 2047 - (int)(cand[128 + c] & 0xffffu);
      const float y = (part[i] + part[2048 + i]) + part[4096 + i];
      const float rs = rbf(1.f / (1.f + expf(-__ldcg(&g_r[tok]))));
      g_upd[c * DM + q * 256 + (i & 255)] = __float2bfloat16(rbf(y) * rs);
    }
  }
}
struct RecParams { const bf16* mem0; unsigned char* win; };
struct WMaps { CUtensorMap q, k, v; };
#define RLX 1
#define DLY_SIDE 16000
#define WSPL 1

#define DLY_S 80
#define DLY_V 200
#define DLY_M3 150
#define RF_FAT 208
#define RF_CTL 88
#define NCH 2
#define WPF 7
#define WRF 7
#define VPF 2
#define DLY_WO 820
#define XPF 4
#define DLY_FA 520
#define DLY_XL 30
#define NPROBE 3
#define BORD 2
#define BG 1
#define VI 1
#define DLY_VI 0
#define WORD 0
#define ETW 1
#define MIRROR 1
#define DLY_N 30
#define F1C 1
#define KA 0
#define KEEP() do { float kd[4]; mma4z(kd, 0u, 0u, 0u, 0u, 0u, 0u); } while (0)
#define WKA 8
#define WPA 4
#define F0T 1
#define DLY_K 1520
#define DLY_KS 992
#define DLY_E 60
#define DLY_PF 300
#define DLY_F0 300
#define XXORD 1
#define DLY_PX 150
#define DLY_TB 700
#define ADD3(a, b, c) addb2(addb2(a, c), b)
#define STR2(x) #x
#define STR(x) STR2(x)

static __device__ __forceinline__ void cp16p(uint32_t dst, const void* src, uint32_t v) {
  asm volatile("{\n.reg .pred q;\nsetp.ne.u32 q, %2, 0;\n@q cp.async.cg.shared.global [%0], [%1], 16;\n}" :: "r"(dst), "l"(src), "r"(v) : "memory"); }
static __device__ __forceinline__ void red_bf2(void* p, uint32_t v) {
  asm volatile("red.relaxed.gpu.global.add.noftz.bf16x2 [%0], %1;" :: "l"(p), "r"(v) : "memory"); }
static __device__ __forceinline__ void red_bf2p(void* p, uint32_t v, uint32_t e) {
  asm volatile("{\n.reg .pred q;\nsetp.lt.u32 q, %2, 2;\n@q red.relaxed.gpu.global.add.noftz.bf16x2 [%0], %1;\n}" :: "l"(p), "r"(v), "r"(e) : "memory"); }
static __device__ __forceinline__ void red_bf2p4(void* p, uint32_t v, uint32_t e) {
  asm volatile("{\n.reg .pred q;\nsetp.lt.u32 q, %2, 4;\n@q red.relaxed.gpu.global.add.noftz.bf16x2 [%0], %1;\n}" :: "l"(p), "r"(v), "r"(e) : "memory"); }
static __device__ __forceinline__ void sts16(uint32_t a, uint32_t x) { asm volatile("{\n.reg .b16 h;\ncvt.u16.u32 h, %1;\nst.shared.u16 [%0], h;\n}" :: "r"(a), "r"(x) : "memory"); }
static __device__ __forceinline__ uint32_t cnt_word(uint32_t L) { return (L & 17u) | ((L & 6u) << 1) | ((L & 8u) >> 2); }
static __device__ __forceinline__ uint32_t cnt_line(uint32_t l) { return (l & 17u) | ((l & 12u) >> 1) | ((l & 2u) << 2); }
static __device__ __forceinline__ int m3_gather(uint32_t sb, const unsigned char* p3, const unsigned char* pd, int dq, uint32_t l16, uint32_t mc, int hf, int tf, int go) {
  const uint32_t md = l16 + (sb + SM_MEM + hf * 8192), dd = l16 + (sb + SM_RD + hf * 512), dc = (l16 >> 2) + ((l16 & 32u) << 3) + (sb + SM_RD + hf * 512);
  {
    const unsigned char* p0f = p3 + tf * 4096; const unsigned char* p0n = p3 + (tf ^ 1) * 4096; const unsigned char* p1f = p0n + dq; const unsigned char* p1n = p0f + dq;
    uint32_t mf = md + tf * 1024, mn = md + (tf ^ 1) * 1024, far = ((l16 >> 8) ^ (l16 >> 7) ^ tf ^ 1u) & 1u;
    OPAQUE_L(p0f); OPAQUE_L(p0n); OPAQUE_L(p1f); OPAQUE_L(p1n); OPAQUE_R(mf); OPAQUE_R(mn); OPAQUE_R(far); FENCE();
    if (go) bar_sync(B_GO, 96);
#pragma unroll
    for (int i = 0; i < 4; i++) { cp16(mn + 4096 + (i >> 1) * 2048 + (i & 1) * 512, p1f + i * 1024); cp16(mf + (i >> 1) * 2048 + (i & 1) * 512, p0f + i * 1024); }
    cp16p(dd, pd, far);
    spin(DLY_N);
#pragma unroll
    for (int i = 0; i < 4; i++) { cp16(mf + 4096 + (i >> 1) * 2048 + (i & 1) * 512, p1n + i * 1024); cp16(mn + (i >> 1) * 2048 + (i & 1) * 512, p0n + i * 1024); }
    cp16p(dd, pd, far ^ 1u);
  }
  int n = 0;
  uint32_t d0, d1;
#pragma unroll 1
  for (;;) {
    asm volatile("cp.async.commit_group;\ncp.async.wait_group 0;" ::: "memory");
    __syncwarp();
    const uint32_t c0 = lds32(mc), c1 = lds32(mc + 4096);
    d0 = lds32(dc); d1 = lds32(dc + 128);
    if (!__any_sync(~0u, (x3(c0, c1, 0x42000000u) | x3(d0, d1, 0x42000000u)) >= 0x10000u) || ++n > SPIN_LIMIT) break;
    const int src = cnt_word(l16 >> 4);
    const uint32_t m0 = __ballot_sync(~0u, (__shfl_sync(~0u, c0, src) >> 16) != 0x4200u) >> (l16 >> 7), m1 = __ballot_sync(~0u, (__shfl_sync(~0u, c1, src) >> 16) != 0x4200u) >> (l16 >> 7);
    const uint32_t m2 = __ballot_sync(~0u, (d0 >> 16) != 0x4200u), m3 = __ballot_sync(~0u, (d1 >> 16) != 0x4200u);
#pragma unroll
    for (int i = 0; i < 8; i++) {
      const int o = ((i >> 1) & 1) * 4096 + (i >> 2) * 2048 + (i & 1) * 1024;
      cp16p(md + i * 512, p3 + o, m0 & (1u << (4 * i))); cp16p(md + 4096 + i * 512, p3 + dq + o, m1 & (1u << (4 * i)));
    }
    cp16p(dd, pd, (((l16 & 128u) ? m3 : m2) >> (((l16 >> 2) & 28u) + ((l16 >> 7) & 2u))) & 3u);
  }
  sts16(mc + 2, d0); sts16(mc + 4098, d1);
  __syncwarp();
  if (l16 == 0) mbar_arrive(sb + SM_BAR + MB_MEM + hf * 8);
  return n;
}

__global__ void __cluster_dims__(2, 1, 1) __launch_bounds__(384, 1)
rec_kernel(const __grid_constant__ CUtensorMap tmx, const __grid_constant__ CUtensorMap tmw, const __grid_constant__ WMaps W, RecParams P, const __grid_constant__ SideParams SP) {
  extern __shared__ __align__(1024) unsigned char smem[];
  asm volatile("griddepcontrol.launch_dependents;");
  const uint32_t sb = smem_u32(smem);
  const int tid = threadIdx.x, lane = tid & 31, t128 = tid & 127;
  const int wg = __shfl_sync(~0u, tid >> 7, 0), wq = __shfl_sync(~0u, (tid >> 5) & 3, 0);
  const int r = blockIdx.x & 1, pp = blockIdx.x >> 1;
  const int mi = lane >> 3, r8 = lane & 7;

  if (tid == 0) {
    mbar_init(sb + SM_BAR + MB_F, 1); mbar_init(sb + SM_BAR + MB_F + 8, 1); mbar_init(sb + SM_BAR + MB_XE0, 2); mbar_init(sb + SM_BAR + MB_XE1, 2); mbar_init(sb + SM_BAR + MB_INIT, 2);
    mbar_init(sb + SM_BAR + MB_MEM, 1); mbar_init(sb + SM_BAR + MB_MEM + 8, 1); mbar_init(sb + SM_BAR + MB_W, 1); mbar_init(sb + SM_BAR + MB_W + 8, 1);
    mbar_init(sb + SM_BAR + MB_XF, MIRROR ? 8 : 4); mbar_init(sb + SM_BAR + MB_X0, 1); mbar_init(sb + SM_BAR + MB_WO, 1); mbar_init(sb + SM_BAR + MB_VR, 5);
    asm volatile("fence.mbarrier_init.release.cluster;" ::: "memory");
  }
  if (tid == 32) {
    asm volatile("prefetch.tensormap [%0];" :: "l"(&W.q) : "memory"); asm volatile("prefetch.tensormap [%0];" :: "l"(&W.k) : "memory");
    asm volatile("prefetch.tensormap [%0];" :: "l"(&W.v) : "memory"); asm volatile("prefetch.tensormap [%0];" :: "l"(&tmx) : "memory");
  }
  if (tid >= 256 && tid < 320) {
    unsigned char* pl = P.win + r * W_2 + (W_UP | (1u << 19) | ((pp >> 5) << 14)) + (pp & 31) * 128 + wq * 4096;
    stg_r1(pl + lane * 4, 0u);
    uint32_t best = 1u << 30, acc = 0;
#pragma unroll 1
    for (int rep = 0; rep < NPROBE; rep++) {
      uint32_t v = 0, t1; const uint32_t t0 = clk32();
      if (lane == 0) asm volatile("atom.relaxed.gpu.global.add.u32 %0, [%1], 2;" : "=r"(v) : "l"(pl + acc) : "memory");
      acc = v >> 31;
      asm volatile("{\n.reg .u32 x;\nadd.u32 x, %1, 0;\nmov.u32 %0, %%clock;\n}" : "=r"(t1) : "r"(acc));
      best = min(best, t1 - t0 + acc);
    }
    if (lane == 0) sts32(sb + SM_SIDE + wq * 4, best);
    bar_sync(B_P, 64);
    if (wq == 0) {
      const uint2 bt = lds64(sb + SM_SIDE);
      if (lane < 8 && (r == 0 || pp == 0)) stg_r1(&g_side[(r ? 66 : pp) * 32 + lane], 2u | (bt.x < bt.y ? 1u : 0u));
      spin(DLY_TB);
      uint32_t a, b, c; int n = 0;
#pragma unroll 1
      do {
        a = ldg_r1(&g_side[lane * 32]); b = ldg_r1(&g_side[(32 + lane) * 32]); c = ldg_r1(&g_side[(64 + min(lane, 2)) * 32]);
      } while (!__all_sync(~0u, a & b & c & 2u) && ++n < SPIN_LIMIT);
      a = __ballot_sync(~0u, a & 1u); b = __ballot_sync(~0u, b & 1u); c = __ballot_sync(~0u, c & 1u);
      const uint32_t pol2 = (a ^ (c >> 2)) & 1u;
      c &= 3u;
      const unsigned long long ab = ((unsigned long long)b << 32) | a;
      const int sd = pp < 64 ? (int)(ab >> pp) & 1 : (int)(c >> (pp - 64)) & 1;
      const int n1 = __popcll(ab) + __popc(c), n0 = 66 - n1;
      const int below1 = pp < 64 ? __popcll(ab & ((1ull << pp) - 1)) : __popcll(ab) + (pp == 65 ? (int)(c & 1u) : 0);
      const int rk = sd ? below1 : pp - below1;
      const int k0 = (n0 & 1) ? n0 - 1 : n0 >= n1 ? n0 - 2 : n0, k1 = 64 - k0;
      const int role = rk >= (sd ? k1 : k0) ? 64 + ((n0 & 1) ? sd : rk - (sd ? k1 : k0)) : sd ? k0 + rk : rk;
      __syncwarp();
      if (lane == 0) sts128(sb + SM_SIDE, 2 * k0, 0u, pol2, role * 2 + r);
    }
  }
  __syncthreads();
  const int cta = __shfl_sync(~0u, (int)lds32(sb + SM_SIDE + 12), 0), h = cta >> 2, j = cta & 3, p = j >> 1;
  if (cta >= NCTA) {
    spin(DLY_SIDE);
    side_work(SP, smem, cta - NCTA);
    return;
  }
  asm volatile("barrier.cluster.arrive.relaxed.aligned;" ::: "memory");
#define WLOAD(i0, i1) _Pragma("unroll 1") for (int u = i0; u < i1; u++) {        \
    const int g2 = u >> 2, i = u & 3, k = g2 * 512 + ((i * 128 + r * 256) & 511); \
    const uint32_t mb = sb + SM_BAR + MB_W + g2 * 8; \
    tma_load_2d(sb + g2 * 65536 + i * 8192, &W.q, h * DH + j * 32, k, mb); \
    tma_load_2d(sb + g2 * 65536 + 32768 + i * 8192, &W.k, h * DH + j * 32, k, mb); \
    if (i < 2) tma_load_2d(sb + (i ? SM_WVS : SM_VST) + g2 * 16384, &W.v, h * DH + p * 64, k, mb); }
  if (tid == 288) {
    mbar_expect_tx(sb + SM_BAR + MB_X0, 32768);
#pragma unroll 1
    for (int i = 0; i < 4; i++)
      asm volatile("cp.async.bulk.tensor.3d.shared::cluster.global.mbarrier::complete_tx::bytes [%0], [%1, {%3, %3, %4}], [%2];"
                   :: "r"(sb + SM_MEM + i * 8192), "l"(&tmx), "r"(sb + SM_BAR + MB_X0), "r"(0), "r"(i * 2) : "memory");
    mbar_expect_tx(sb + SM_BAR + MB_W, 98304); mbar_expect_tx(sb + SM_BAR + MB_W + 8, 98304);
    WLOAD(0, 4 + WSPL);
  }
  __syncwarp();
  asm volatile("barrier.cluster.wait.acquire.aligned;" ::: "memory");
#define SIDES() const uint4 sm2 = lds128(sb + SM_SIDE); const int nlo = sm2.x; const uint32_t me = cta >= nlo

#define XLOAD(t, sg) do { tma_load_mc(sb + SM_X + ((t) * 8 + r * 4) * 4096, &tmx, (sg) * SEG, (t) * 8 + r * 4, sb + SM_BAR + MB_F + (t) * 8); \
                          tma_load_mc(sb + SM_X + ((t) * 8 + r * 4 + 2) * 4096, &tmx, (sg) * SEG, (t) * 8 + r * 4 + 2, sb + SM_BAR + MB_F + (t) * 8); } while (0)
  if (wg < 2) {
    asm volatile("setmaxnreg.inc.sync.aligned.u32 " STR(RF_FAT) ";");
    uint32_t w[32][4], wv[8][4];
    uint32_t lm = ((mi >> 1) * 8 + r8) * 128 + (((wq * 2 + (mi & 1)) ^ r8) << 4), l16 = lane * 16;
    lm = __shfl_sync(~0u, lm, lane); l16 = __shfl_sync(~0u, l16, lane);
    mbar_wait(sb + SM_BAR + MB_W + wg * 8, 0);
    {
      const uint32_t lq0 = sb + wg * 65536 + (wq >> 1) * 32768 + ((mi >> 1) * 8 + r8) * 64 + ((((wq & 1) * 2 + (mi & 1)) ^ (r8 >> 1)) << 4);
#pragma unroll
      for (int kk = 0; kk < 32; kk++) ldmatrix_x4_trans(w[kk], lq0 + kk * 1024);
    }
#pragma unroll
    for (int kk = 0; kk < 8; kk++) ldmatrix_x4_trans(wv[kk], sb + SM_VST + wg * 16384 + kk * 2048 + lm);
    if (wg == 0) bar_sync(B_V, 160);
    else bar_arrive(B_P, 224);
    const int w8 = wg * 4 + wq;
    const int tf = __shfl_sync(~0u, (cta >= (int)lds32(sb + SM_SIDE) ? 0 : 1) ^ r, 0);
    const uint32_t xb16 = (((sb + SM_X + wg * 32768 + r * 16384) & 0x3FFFF) >> 4) | (1u << 16), xh16 = xb16 ^ 1024u;
    const uint32_t rsb = mapa(sb, r ^ 1);
    const uint32_t va16 = (((sb + SM_WVS + wg * 16384) & 0x3FFFF) >> 4) | (64u << 16);
#define MT (l16 + (sb + SM_MEM + wg * 8192))
#define WA (lm + (sb + SM_WVS + wg * 16384))
#define WOF(f) (lm + (sb + SM_WOS + wg * 32768 + (((f) & 1) ^ tf) * 16384 + ((f) >> 1) * 2048))
#define TH(base) (l16 + (sb + (base) + w8 * 512))
#define TQ(base) (l16 + (sb + (base) + wq * 512))
#define DUMP(base) _Pragma("unroll") for (int n = 0; n < 4; n++) sts128f(TQ((base) + n * 2048), d[4 * n], d[4 * n + 1], d[4 * n + 2], d[4 * n + 3])
#define INIT(base) _Pragma("unroll") for (int n = 0; n < 4; n++) { const float4 t = lds128f(TQ((base) + n * 2048)); d[4 * n] = t.x; d[4 * n + 1] = t.y; d[4 * n + 2] = t.z; d[4 * n + 3] = t.w; }
#define XQK(first, b0, b1) do { wg_fence(); XR<0, 16, 0, 32, first>::run(d, w, b0); XR<0, 16, 16, 32, 0>::run(d, w, b1); wg_commit(); wg_wait0(); } while (0)
#define XVS(first, b0) do { wg_fence(); XS<8, 8, 16, first>::run(d, va16, b0); XR<0, 8, 0, 8, 0>::run(d, wv, b0); wg_commit(); wg_wait0(); } while (0)
#define XVR(first, b0) do { wg_fence(); XR<0, 8, 0, 8, first>::run(d, wv, b0); XS<8, 8, 16, 0>::run(d, va16, b0); wg_commit(); wg_wait0(); } while (0)
#define XREL(mb) do { if (wq == 0 && l16 == 0) { mbar_arrive_cluster_rlx(rsb + SM_BAR + (mb)); mbar_arrive(sb + SM_BAR + (mb)); } } while (0)
#define XFOUT() do { \
          _Pragma("unroll") for (int hf = 0; hf < 2; hf++) \
            stsm4t(l16 + (sb + SM_XF + (wq * 2 + hf) * 512), pack_bf16(d[8 * hf], d[8 * hf + 1]), pack_bf16(d[8 * hf + 2], d[8 * hf + 3]), \
                   pack_bf16(d[8 * hf + 4], d[8 * hf + 5]), pack_bf16(d[8 * hf + 6], d[8 * hf + 7])); \
          __syncwarp(); \
          if (l16 < (MIRROR ? 32 : 16)) mbar_arrive(sb + SM_BAR + MB_XF); } while (0)
#define ADDIN(base) _Pragma("unroll") for (int n = 0; n < 4; n++) { const float4 t = lds128f(TQ((base) + n * 2048)); d[4 * n] += t.x; d[4 * n + 1] += t.y; d[4 * n + 2] += t.z; d[4 * n + 3] += t.w; }
    if (wg == 0) {
      float d[16];
      const uint32_t x0 = (((sb + SM_MEM + r * 16384) & 0x3FFFF) >> 4) | (1u << 16), x1 = (((sb + SM_MEM + (r ^ 1) * 16384) & 0x3FFFF) >> 4) | (1u << 16);
      mbar_wait(sb + SM_BAR + MB_X0, 0);
      XQK(1, x0, x1);
      DUMP(SM_CQ);
      XVS(1, x0);
      bar_sync(B_CQ, 256);
      DUMP(SM_CV);
      bar_sync(B_X2, 384);
    } else {
      float d[16];
      bar_sync(B_CQ, 256);
      INIT(SM_CQ);
      bar_sync(B_X2, 384);
      mbar_wait(sb + SM_BAR + MB_F + 8, 0);
      XQK(0, xb16, xh16);
      XFOUT();
    }
    uint32_t f0ok = 0;
    for (int s = 0;; s++) {
      OPAQUE_R(lm); OPAQUE_R(l16);
      if (wg || s < NSEG - 1) {
        float d[16];
        const uint32_t cv = ((s ^ wg) & 1) ? SM_CV : SM_CW;
        if (!wg && !f0ok) mbar_wait(sb + SM_BAR + MB_F, s & 1);
        TSP(9, 1);
        if (BORD == 2) XVR(1, xb16); else XVS(1, xb16);
        OPAQUE_R(l16);
        if (wg == 0) {
          DUMP(cv);
          TSP(5, 1);
        } else {
          XREL(MB_XE1);
          ADDIN(cv);
          uint32_t q[4], o[4];
#pragma unroll
          for (int i = 0; i < 4; i++) { const uint32_t a = pack_bf16(d[2 * i], d[2 * i + 1]), b = pack_bf16(d[8 + 2 * i], d[9 + 2 * i]); q[i] = r ? b : a; o[i] = r ? a : b; }
          st_async4(l16 + (rsb + SM_VR + wq * 512), u2f(o[0]), u2f(o[1]), u2f(o[2]), u2f(o[3]), rsb + SM_BAR + MB_VR);
          sts128(TQ(SM_VL), q[0], q[1], q[2], q[3]);
          __syncwarp();
          if (l16 == 0) mbar_arrive(sb + SM_BAR + MB_VR);
          TSP(28, 5);
        }
      }
      OPAQUE_R(lm); OPAQUE_R(l16);
      {
        uint32_t sa[4][4];
#pragma unroll
        for (int i = 0; i < VPF; i++) ldmatrix_x4_trans(sa[i], WA + i * 2048);
        float a[NCH][4], v[2][4]; uint4 c[4];
        FENCE();
        mbar_wait(sb + SM_BAR + MB_MEM + wg * 8, s & 1);
        TSF(0, 1);
        TSF(21, 5);
#define QP(i) ((i) >= 12 ? (i) - 8 : (i) % 3 == 1 ? (i) / 3 : 8 + (i) - ((i) + 2) / 3)
#pragma unroll
        for (int i = 0; i < 3; i++) c[i] = ldsm4t(MT + QP(i) * 512);
#pragma unroll
        for (int i = 0; i < 16; i++) {
          if (i + 3 < 16) c[(i + 3) & 3] = ldsm4t(MT + QP(i + 3) * 512);
          if (2 * i < NCH) mma4z(a[2 * i], w[2 * QP(i)][0], w[2 * QP(i)][1], w[2 * QP(i)][2], w[2 * QP(i)][3], c[i & 3].x, c[i & 3].y);
          else mma_16816(a[(2 * i) % NCH], w[2 * QP(i)], c[i & 3].x, c[i & 3].y);
          if (2 * i + 1 < NCH) mma4z(a[2 * i + 1], w[2 * QP(i) + 1][0], w[2 * QP(i) + 1][1], w[2 * QP(i) + 1][2], w[2 * QP(i) + 1][3], c[i & 3].z, c[i & 3].w);
          else mma_16816(a[(2 * i + 1) % NCH], w[2 * QP(i) + 1], c[i & 3].z, c[i & 3].w);
          if (VI && QP(i) == 0) {
            mma4z(v[0], wv[0][0], wv[0][1], wv[0][2], wv[0][3], c[i & 3].x, c[i & 3].y);
            mma4z(v[1], wv[1][0], wv[1][1], wv[1][2], wv[1][3], c[i & 3].z, c[i & 3].w);
          } else if (VI && QP(i) < 4) {
            mma_16816(v[0], wv[2 * (QP(i) & 3)], c[i & 3].x, c[i & 3].y);
            mma_16816(v[1], wv[2 * (QP(i) & 3) + 1], c[i & 3].z, c[i & 3].w);
          }
          FENCE();
        }
        {
          const uint32_t qa = (((l16 & 0x30u) << 3) | ((l16 & 0x10u) << 2) | ((l16 >> 3) & 0x30u) | ((l16 >> 4) & 4u)) + (sb + SM_QKP + w8 * 512);
#pragma unroll
          for (int i = 0; i < 4; i++) {
            const float t = NCH == 4 ? (a[0][i] + a[1][i]) + (a[2 % NCH][i] + a[3 % NCH][i]) : NCH == 3 ? (a[0][i] + a[1][i]) + a[2 % NCH][i] : a[0][i] + a[1][i];
            sts32((qa ^ ((i & 1) << 6)) + (i >> 1) * 8, __float_as_uint(t));
          }
        }
        bar_arrive(B_QK, 288);
        bar_arrive(B_QK1, 288);
        FENCE();
        spin(DLY_VI);
#pragma unroll
        for (int i = VPF; i < 4; i++) ldmatrix_x4_trans(sa[i], WA + i * 2048);
        FENCE();
#pragma unroll
        for (int i = 0; i < 4; i++) {
          mma_16816(v[0], sa[(2 * i) & 3], c[i].x, c[i].y);
          mma_16816(v[1], sa[(2 * i + 1) & 3], c[i].z, c[i].w);
          if (i < 2) { ldmatrix_x4_trans(sa[2 * i], WA + (4 + 2 * i) * 2048); ldmatrix_x4_trans(sa[2 * i + 1], WA + (5 + 2 * i) * 2048); }
          FENCE();
        }
        sts128f(TH(SM_VP), v[0][0] + v[1][0], v[0][1] + v[1][1], v[0][2] + v[1][2], v[0][3] + v[1][3]);
        bar_arrive(B_V, 320);
        TSF(24, 5);
      }
      if (s == NSEG - 1) break;
      if (s == 0) mbar_wait(sb + SM_BAR + MB_WO, 0);
      OPAQUE_R(lm); OPAQUE_R(l16);
      {
        uint32_t wo[WPF][4];
        {
          float d[16];
          if (wg) mbar_wait(sb + SM_BAR + MB_F + 8, (s + 1) & 1);
          bar_sync(B_PUB, 320);
          wg_fence();
          XR<0, WKA, 0, 32, 1>::run(d, w, xb16);
#pragma unroll
          for (int f = 0; f < WPA; f++) ldmatrix_x4_trans(wo[f], WOF(f));
          XR<WKA, 16, 0, 32, 0>::run(d, w, xb16); XR<0, 16, 16, 32, 0>::run(d, w, xh16);
          wg_commit(); wg_wait0();
          TSF(31, 5); TSF(13, 1);
          OPAQUE_R(l16);
#define XHALF(g) do { \
            _Pragma("unroll") for (int n = 0; n < 2; n++) sts128f(TQ(SM_CQ + ((g) * 2 + n) * 2048), d[8 - 8 * (g) + 4 * n], d[9 - 8 * (g) + 4 * n], d[10 - 8 * (g) + 4 * n], d[11 - 8 * (g) + 4 * n]); \
            bar_sync(B_CQ, 256); \
            const float4 t0 = lds128f(TQ(SM_CQ + (2 - 2 * (g)) * 2048)), t1 = lds128f(TQ(SM_CQ + (3 - 2 * (g)) * 2048)); \
            stsm4t(l16 + (sb + SM_XF + (wq * 2 + (g)) * 512), pack_bf16(d[8 * (g)] + t0.x, d[8 * (g) + 1] + t0.y), pack_bf16(d[8 * (g) + 2] + t0.z, d[8 * (g) + 3] + t0.w), \
                   pack_bf16(d[8 * (g) + 4] + t1.x, d[8 * (g) + 5] + t1.y), pack_bf16(d[8 * (g) + 6] + t1.z, d[8 * (g) + 7] + t1.w)); } while (0)
          if (wg == 0) { XREL(MB_XE0); XHALF(0); } else XHALF(1);
          __syncwarp();
          if (l16 == 0) mbar_arrive(sb + SM_BAR + MB_XF);
          TSF(3, 5);
        }
#pragma unroll
        for (int f = WPA; f < WPF; f++) ldmatrix_x4_trans(wo[f], WOF(f));
        unsigned char* pa = P.win + (w_ar(s) + j * 8192 + tf * 4096 + w8 * 512 + (l16 >> 2));
        uint32_t ce = ((l16 >> 4) - 4 * w8) ^ (2 * tf);
        OPAQUE_L(pa); OPAQUE_R(ce);
        FENCE();
        bar_sync(B_O, 320);
        uint4 ob[2];
        ob[0] = ldsm4(l16 + (sb + SM_OF)); ob[1] = ldsm4(l16 + (sb + SM_OF + 512));
        float acc[2][4];
#pragma unroll
        for (int f = 0; f < 16; f++) {
          const int ks = f >> 1;
          const uint32_t b0 = (ks & 1) ? ob[(ks >> 1) & 1].z : ob[(ks >> 1) & 1].x, b1 = (ks & 1) ? ob[(ks >> 1) & 1].w : ob[(ks >> 1) & 1].y;
          if (f < 2) mma4z(acc[f], wo[f][0], wo[f][1], wo[f][2], wo[f][3], b0, b1);
          else mma_16816(acc[f % 2], wo[f < WPF ? f : 2 + (f - WPF) % (WPF - 2)], b0, b1);
          if (f - 1 >= 2 && f - 1 + (WPF - 2) < 16) {
            const int nf = f - 1 + (WPF - 2);
            ldmatrix_x4_trans(wo[2 + (nf - WPF) % (WPF - 2)], WOF(nf));
          }
          if (f == 4 || f == 8) ob[((f >> 2) - 1) & 1] = ldsm4(l16 + (sb + SM_OF + (1 + (f >> 2)) * 512));
          FENCE();
        }
        if (F0T) f0ok = mbar_test(sb + SM_BAR + MB_F, (s + 1) & 1);
        if (BG) bar_sync(B_CV, 256);
        FENCE();
        red_bf2(pa, pack_bf16(acc[0][0], ce == 0 ? 1.f : acc[0][1])); red_bf2(pa + 256, pack_bf16(acc[0][2], ce == 1 ? 1.f : acc[0][3]));
        {
          unsigned char* pb = reinterpret_cast<unsigned char*>(reinterpret_cast<uintptr_t>(pa) ^ 4096u);
          red_bf2p4(((ce & 2) ? pb : pa) + 128, pack_bf16(ce == 0 ? acc[0][1] : ce == 1 ? acc[0][3] : ce == 2 ? acc[1][1] : acc[1][3], 1.f), ce);
          red_bf2(pb, pack_bf16(acc[1][0], ce == 2 ? 1.f : acc[1][1])); red_bf2(pb + 256, pack_bf16(acc[1][2], ce == 3 ? 1.f : acc[1][3]));
        }
        TSF(4, 1);
        TSF(2, 6);
        bar_arrive(B_M2, 288);
      }
    }
  } else {
    asm volatile("setmaxnreg.dec.sync.aligned.u32 " STR(RF_CTL) ";");
    const int g = lane >> 2, tq = lane & 3;
    if (wq == 0) {
      if (lane < 12) asm volatile("prefetch.global.L2 [%0];" :: "l"(SP.x + (size_t)(cta * 12 + lane) * 64));
      __syncwarp();
      {
        SIDES();
        const uint32_t o[6] = {w_blk(w_h1(cta), me), w_blk(w_h1(cta) ^ H1_V, me), w_blk(w_mvx(cta, 0), me ^ sm2.z), w_blk(w_mvx(cta, 1), me ^ sm2.z),
                               w_blk(w_mxa(cta, 0), me ^ sm2.z), w_blk(w_mxa(cta, 1), me ^ sm2.z)};
#pragma unroll
        for (int i = 0; i < 24; i++) stg_r4(P.win + (o[i >> 2] + (i & 3) * 512 + lane * 16), 0u, 0u, 0u, 0u);
#pragma unroll
        for (int i = 0; i < 6; i++) stg_r1(P.win + (w_ar(i >> 1) + cta * 256 + (i & 1) * 128 + lane * 4), 0u);
        __threadfence();
        __syncwarp();
      }
      {
        const uint32_t wv = movm(*reinterpret_cast<const uint32_t*>(P.mem0 + g * DM + cta * 8 + tq * 2));
        const bool sp = lane == cnt_word(cta & 31);
        const uint32_t la = w_ar(-1) + ((cta & ~24) | ((cta & 8) << 1) | ((cta & 16) >> 1)) * 256 + lane * 4;
        stg_r1(P.win + la, sp ? (wv & 0xffffu) | 0x42000000u : wv);
        if (sp) stg_r1(P.win + ((la & ~256u) + 128), (wv >> 16) | 0x42000000u);
      }
      bar_sync(B_V, 160);
      if (lane == 0) {
        fence_async_smem(); mbar_arrive_cluster_rlx(mapa(sb + SM_BAR + MB_INIT, 0)); mbar_arrive_cluster_rlx(mapa(sb + SM_BAR + MB_INIT, 1));
        mbar_wait(sb + SM_BAR + MB_INIT, 0);
        mbar_expect_tx(sb + SM_BAR + MB_F, 32768);
        mbar_expect_tx(sb + SM_BAR + MB_F + 8, 32768);
        XLOAD(1, 0); XLOAD(0, 1);
        WLOAD(4 + WSPL, 8);
      }
      __syncwarp();
      bar_sync(B_X2, 384);
    } else {
      bar_sync(B_P, 224);
      if (t128 == 96) {
        fence_async_smem();
        mbar_expect_tx(sb + SM_BAR + MB_WO, 65536);
        for (int i = 0; i < 8; i++) tma_load_2d(sb + SM_WOS + i * 8192, &tmw, j * 256 + (i >> 1) * 64, h * DH + (i & 1) * 64, sb + SM_BAR + MB_WO);
      }
      __syncwarp();
      bar_sync(B_X2, 384);
    }
    SIDES();
    uint32_t l16 = __shfl_sync(~0u, lane * 16, lane);
    const uint32_t me2 = me ^ sm2.z;
    const float sc = 0.08838834764831845f * 1.4426950408889634f;
    uint32_t ls = l16 + sb;
#define PV4(va, vm, dst) do { \
        float o[4][4], z[4]; \
        FENCE(); \
        mma4z(z, 0x3F803F80u, 0x3F803F80u, 0x3F803F80u, 0x3F803F80u, p0.x, p0.y); \
        _Pragma("unroll") for (int t = 0; t < 4; t++) mma4z(o[t], va[2 * t].x, va[2 * t].y, va[2 * t].z, va[2 * t].w, p0.x, p0.y); \
        FENCE(); \
        mma4(z, 0x3F803F80u, 0x3F803F80u, 0x3F803F80u, 0x3F803F80u, p0.z, p0.w); \
        _Pragma("unroll") for (int t = 0; t < 2; t++) mma4(o[t], va[2 * t + 1].x, va[2 * t + 1].y, va[2 * t + 1].z, va[2 * t + 1].w, p0.z, p0.w); \
        FENCE(); \
        mma_1688(z, 0x3F803F80u, 0x3F803F80u, p2); \
        _Pragma("unroll") for (int t = 2; t < 4; t++) mma4(o[t], va[2 * t + 1].x, va[2 * t + 1].y, va[2 * t + 1].z, va[2 * t + 1].w, p0.z, p0.w); \
        mma_1688(o[0], vm[0].x, vm[0].y, p2); mma_1688(o[1], vm[0].z, vm[0].w, p2); mma_1688(o[2], vm[1].x, vm[1].y, p2); mma_1688(o[3], vm[1].z, vm[1].w, p2); \
        const float i0 = rcpf(z[0]), i1 = rcpf(z[1]); \
        _Pragma("unroll") for (int u = 0; u < 2; u++) \
          stsm4t(ls + (dst) + u * 1024, pack_bf16(o[2 * u][0] * i0, o[2 * u][1] * i1), pack_bf16(o[2 * u][2] * i0, o[2 * u][3] * i1), \
                 pack_bf16(o[2 * u + 1][0] * i0, o[2 * u + 1][1] * i1), pack_bf16(o[2 * u + 1][2] * i0, o[2 * u + 1][3] * i1)); } while (0)
#define SOFTMAX(pf, f) do { \
        float mx = fmaxf(fmaxf(fmaxf(sx[2], sx[3]), fmaxf(sx[4], sx[5])), fmaxf(fmaxf(sx[6], sx[7]), fmaxf(sx[8], sx[9]))); \
        mx = fmaxf(mx, fmaxf(sx[0], sx[1])); \
        mx = fmaxf(mx, __shfl_xor_sync(~0u, mx, 1)); \
        mx = fmaxf(mx, __shfl_xor_sync(~0u, mx, 2)); \
        mx *= -(f); \
        _Pragma("unroll") for (int i = 0; i < 10; i++) sx[i] = ex2(fmaf(sx[i], f, mx)); \
        sts128(ls + (pf), pack_bf16(sx[2], sx[3]), pack_bf16(sx[4], sx[5]), pack_bf16(sx[6], sx[7]), pack_bf16(sx[8], sx[9])); \
        sts32(ls - l12 + (pf) + 512, pack_bf16(sx[0], sx[1])); } while (0)
    const uint32_t lq = (l16 ^ ((l16 >> 1) & 64u)) + sb, l12 = (l16 >> 2) * 3;
#define ETA(k, first) do { if (l16 < 32) { unsigned char* pt = P.win + (w_ar(s) + 384 + (cta >> 5) * 8192 + ((cta >> 4) & 1) * 2048 + l16 * 256); \
          asm volatile("red.relaxed.gpu.global.max.u32 [%0+4], %1;" :: "l"(pt), "r"(gt32() + (k)) : "memory"); \
          if (first) asm volatile("red.relaxed.gpu.global.add.u32 [%0], 1;" :: "l"(pt) : "memory"); } } while (0)
    if (wq == 1) {
      const uint32_t xin = w_blk(w_mxa(cta, 0), me2) + l16;
#define F1LOAD() \
          if (F1C ? s == 0 : s < NSEG - 1) {        \
            mbar_wait(sb + SM_BAR + MB_XE1, s & 1); \
            if (l16 == 0) mbar_expect_tx(sb + SM_BAR + MB_F + 8, 32768); \
            mbar_wait(sb + SM_BAR + MB_MEM, s & 1); \
            mbar_wait(sb + SM_BAR + MB_MEM + 8, s & 1); \
            spin(DLY_FA); \
            if (l16 == 0) XLOAD(1, s + 1); \
            __syncwarp(); \
            TS(27); \
          }
      for (int s = 0; s < NSEG; s++) {
        const uint32_t t2 = ((s >> 1) & 1) ^ 1;
        mbar_wait(sb + SM_BAR + MB_XF, s & 1);
        {
        uint4 kx[4], qx[4];
#pragma unroll
        for (int i = 0; i < 4; i++) { kx[i] = ldsm4(ls + (SM_XF + (4 + i) * 512)); qx[i] = ldsm4(ls + (SM_XF + i * 512)); }
        const uint32_t db = w_blk(w_mxa(h * 4, s), me2) + l16 - 640;
#pragma unroll
        for (int mt = 0; mt < 2; mt++) {
          const uint4 q0 = qx[mt], q1 = qx[2 + mt];
          float S[4][4];
          mma4z(S[0], q0.x, q0.z, q0.y, q0.w, kx[0].x, kx[0].y); mma4z(S[1], q0.x, q0.z, q0.y, q0.w, kx[0].z, kx[0].w);
          mma4z(S[2], q0.x, q0.z, q0.y, q0.w, kx[1].x, kx[1].y); mma4z(S[3], q0.x, q0.z, q0.y, q0.w, kx[1].z, kx[1].w);
          mma4(S[0], q1.x, q1.z, q1.y, q1.w, kx[2].x, kx[2].y); mma4(S[1], q1.x, q1.z, q1.y, q1.w, kx[2].z, kx[2].w);
          mma4(S[2], q1.x, q1.z, q1.y, q1.w, kx[3].x, kx[3].y); mma4(S[3], q1.x, q1.z, q1.y, q1.w, kx[3].z, kx[3].w);
#pragma unroll
          for (int u = 0; u < 2; u++) {
            const uint32_t m0 = tagw(pack_f16(S[0][2 * u] * sc, S[0][2 * u + 1] * sc), t2), m1 = pack_f16(S[1][2 * u] * sc, S[1][2 * u + 1] * sc),
                           m2 = pack_f16(S[2][2 * u] * sc, S[2][2 * u + 1] * sc), m3 = pack_f16(S[3][2 * u] * sc, S[3][2 * u + 1] * sc);
            const int e = (2 * mt + u) ^ j;
            if (e) stg_r4(P.win + (db + mt * 16384 + u * 2048 + e * 640), m0, m1, m2, m3);
            else sts128(ls + SM_XS, m0, m1, m2, m3);
          }
        }
        TS(15);
        {
          if (l16 == 0) mbar_expect_tx(sb + SM_BAR + MB_VR, 2048);
          mbar_wait(sb + SM_BAR + MB_VR, s & 1);
          unsigned char* d = P.win + (w_blk(w_mvx(cta, s), me2) + l16);
#pragma unroll
          for (int t = 0; t < 4; t++) {
            const uint4 a0 = lds128(ls + (SM_VL + t * 512)), a1 = lds128(ls + (SM_VR + t * 512));
            stg_r4(d + t * 512, tagw(addb2(a0.x, a1.x), t2), addb2(a0.y, a1.y), addb2(a0.z, a1.z), addb2(a0.w, a1.w));
          }
          TS(23);
        }
        F1LOAD();
        FENCE();
        bar_sync(B_QK1, 288);
        uint32_t kb[2][2];
#pragma unroll
        for (int t = 0; t < 2; t++) {
          const float4 u = lds128f(lq + (SM_QKP + (2 + t) * 512)), v4 = lds128f(lq + (SM_QKP + 2048 + (2 + t) * 512));
          kb[t][0] = pack_bf16(u.x + v4.x, u.y + v4.y); kb[t][1] = pack_bf16(u.z + v4.z, u.w + v4.w);
        }
        float S[2][4];
#pragma unroll
        for (int mt = 0; mt < 2; mt++) mma4z(S[mt], qx[mt].x, qx[mt].z, qx[mt].y, qx[mt].w, kb[0][0], kb[0][1]);
#pragma unroll
        for (int mt = 0; mt < 2; mt++) mma4(S[mt], qx[2 + mt].x, qx[2 + mt].z, qx[2 + mt].y, qx[2 + mt].w, kb[1][0], kb[1][1]);
        if (s < NSEG - 1) bar_arrive(B_PUB, 320);
#pragma unroll
        for (int u = 0; u < 4; u++) {
          const uint32_t m4 = tagw(pack_f16(S[u >> 1][2 * (u & 1)] * sc, S[u >> 1][2 * (u & 1) + 1] * sc), t2);
          const int e = u ^ j;
          if (e) stg_r1(P.win + (db + (u >> 1) * 16384 + (u & 1) * 2048 + e * 640 + 512 - l12), m4);
          else sts32(ls - l12 + SM_XS + 512, m4);
        }
        if (ETW == 1 && s < NSEG - 1) ETA(DLY_K, 1);
        TS(30);
        }
        spin(DLY_XL);
        const unsigned char* pa = P.win + (xin + ((s & 1) << 20));
        uint4 xv[3]; uint32_t xy[3]; int n = 0;
#pragma unroll 1
        do {
#pragma unroll
          for (int i = 0; i < 3; i++) { xv[i] = ldg_r4(pa + i * 640); xy[i] = ldg_r1(pa + i * 640 + 512 - l12); }
        } while (__any_sync(~0u, or3(x3(xv[0].x, xv[1].x, t2), x3(xv[2].x, xy[2], t2), x3(xy[0], xy[1], t2)) & 1u) && ++n < SPIN_LIMIT);
        const uint4 v3 = lds128(ls + SM_XS); const uint32_t y3 = lds32(ls - l12 + SM_XS + 512);
        float sx[10];
        sum_h4(sx[0], sx[1], xy[0], xy[1], xy[2], y3);
        sum_h4(sx[2], sx[3], xv[0].x, xv[1].x, xv[2].x, v3.x); sum_h4(sx[4], sx[5], xv[0].y, xv[1].y, xv[2].y, v3.y);
        sum_h4(sx[6], sx[7], xv[0].z, xv[1].z, xv[2].z, v3.z); sum_h4(sx[8], sx[9], xv[0].w, xv[1].w, xv[2].w, v3.w);
        const int row = 8 * j + g - 2 * tq;
#pragma unroll
        for (int i = 0; i < 8; i++) if ((i >> 1) * 8 + (i & 1) > row) sx[2 + i] = -INFINITY;
        if (s > 0) bar_sync(B_PXF, 96);
        SOFTMAX(SM_PX, 1.f);
        bar_arrive(B_PX, 96);
        TS(1);
      }
    } else {
      const uint32_t ho = (wq & 1) * 512 + l16, hv = wq == 0 ? 0u : H1_V;
      uint32_t ow = w_blk(w_h1(cta) ^ hv, me) + ho, or0 = w_blk(w_h1(cta ^ 1) ^ hv, me) + ho, or1 = w_blk(w_h1((cta ^ 2) & ~1) ^ hv, me) + ho;
#define PTRS() OPAQUE_R(ow); OPAQUE_R(or0); OPAQUE_R(or1); \
      unsigned char* pw0 = P.win + ow; const unsigned char* pr0 = P.win + or0; const unsigned char* pr1 = P.win + or1; \
      OPAQUE_L(pw0); OPAQUE_L(pr0); OPAQUE_L(pr1); FENCE()
      if (wq == 0) {
        const uint32_t xcnt = me ? NCTA - nlo : nlo, xrank = (me ? cta - nlo : cta) + lane * xcnt;
        const uint32_t l8 = l16 >> 1;
        for (int s = 0; s < NSEG; s++) {
          const uint32_t tg = (s & 1) ^ 1;
          mbar_wait(sb + SM_BAR + MB_XF, s & 1);
          uint4 xf[4];
#pragma unroll
          for (int i = 0; i < 4; i++) xf[i] = ldsm4(ls + (SM_XF + (4 + i) * 512));
          PTRS();
          bar_sync(B_QK, 288);
          if (s == NSEG - 1) break;
          float4 u[4], v4[4];
#pragma unroll
          for (int t = 0; t < 4; t++) { u[t] = lds128f(lq + (SM_QKP + t * 512)); v4[t] = lds128f(lq + (SM_QKP + 2048 + t * 512)); }

          FENCE();
          uint32_t f[4][2];
#pragma unroll
          for (int t = 0; t < 4; t++) {
            f[t][0] = pack_bf16(u[t].x + v4[t].x, u[t].y + v4[t].y);
            f[t][1] = pack_bf16(u[t].z + v4[t].z, u[t].w + v4[t].w);
          }
          float S[5][4];
          mma4z(S[1], f[0][0], 0u, f[0][1], 0u, xf[0].x, xf[0].y);
          mma4z(S[2], f[0][0], 0u, f[0][1], 0u, xf[0].z, xf[0].w);
          mma4z(S[3], f[0][0], 0u, f[0][1], 0u, xf[1].x, xf[1].y);
          mma4z(S[4], f[0][0], 0u, f[0][1], 0u, xf[1].z, xf[1].w);
          mma4(S[1], f[1][0], 0u, f[1][1], 0u, xf[2].x, xf[2].y);
          mma4(S[2], f[1][0], 0u, f[1][1], 0u, xf[2].z, xf[2].w);
          mma4z(S[0], f[0][0], 0u, f[0][1], 0u, f[2][0], f[2][1]);
          mma4(S[3], f[1][0], 0u, f[1][1], 0u, xf[3].x, xf[3].y);
          mma4(S[4], f[1][0], 0u, f[1][1], 0u, xf[3].z, xf[3].w);
          mma4(S[0], f[1][0], 0u, f[1][1], 0u, f[3][0], f[3][1]);
          bar_arrive(B_PUB, 320);
          stg_r4(pw0, tagw(f2u(S[1][0]), tg), f2u(S[1][1]), f2u(S[2][0]), f2u(S[2][1]));
          stg_r4(pw0 + 512, tagw(f2u(S[3][0]), tg), f2u(S[3][1]), f2u(S[4][0]), f2u(S[4][1]));
          stg_r2(pw0 + 1024 - l8, tagw(f2u(S[0][0]), tg), f2u(S[0][1]));
          TS(6);
          if (ETW == 0) ETA(DLY_K, 1);
          spin(DLY_S);
          float sx[10];
          {
            uint4 v[3], y[3]; uint2 z[3]; int n = 0; uint32_t bad;
#pragma unroll 1
            do {
              v[0] = ldg_r4(pr0); v[1] = ldg_r4(pr1); v[2] = ldg_r4(pr1 + 2048);
              y[0] = ldg_r4(pr0 + 512); y[1] = ldg_r4(pr1 + 512); y[2] = ldg_r4(pr1 + 2560);
              z[0] = ldg_r2(pr0 + 1024 - l8); z[1] = ldg_r2(pr1 + 1024 - l8); z[2] = ldg_r2(pr1 + 3072 - l8);
              if (n) ETA(DLY_KS, 0);
              bad = (or3(x3(v[0].x, v[1].x, tg), x3(v[2].x, y[0].x, tg), x3(y[1].x, y[2].x, tg)) | x3(z[0].x, z[1].x, tg) | (z[2].x ^ tg)) & 1u;
            } while (__any_sync(~0u, bad) && ++n < SPIN_LIMIT);
            TS(7); TV(19, n);
#define SUM4(o, a, c) ((o + u2f(a[0].c)) + (u2f(a[1].c) + u2f(a[2].c)))
            sx[2] = SUM4(S[1][0], v, x); sx[3] = SUM4(S[1][1], v, y); sx[4] = SUM4(S[2][0], v, z); sx[5] = SUM4(S[2][1], v, w);
            sx[6] = SUM4(S[3][0], y, x); sx[7] = SUM4(S[3][1], y, y); sx[8] = SUM4(S[4][0], y, z); sx[9] = SUM4(S[4][1], y, w);
            sx[0] = SUM4(S[0][0], z, x); sx[1] = SUM4(S[0][1], z, y);
          }
          SOFTMAX(SM_PF, sc);
          TS(12);
          bar_sync(B_P, 96);
          {
            const unsigned char* pe = P.win + w_blk(w_ar(s) + 384 + (l16 & 0x60u) * 256 + (l16 & 16u) * 128, me);
            spin(DLY_E);
            uint2 e = ldg_r2(pe); int n = 0;
            if (s < NSEG - 2) {
              mbar_wait(sb + SM_BAR + MB_XE0, s & 1);
              if (l16 == 0) { mbar_expect_tx(sb + SM_BAR + MB_F, 32768); XLOAD(0, s + 2); }
              __syncwarp();
              TS(25);
            }
#pragma unroll 1
            while (__any_sync(~0u, e.x != 16u) && ++n < SPIN_LIMIT) e = ldg_r2(pe);
            const uint32_t tg0 = __reduce_max_sync(~0u, e.y);
            TS(14); TV(29, n);
            bar_sync(B_M2, 288);
            spin(DLY_M3);
            while (tg0 - gt32() - 1u < 4096u) {}
            bar_arrive(B_GO, 96);
            TS(16);
          }
          if (F1C && s < NSEG - 2) {
            spin(DLY_FA);
            mbar_wait(sb + SM_BAR + MB_XE1, (s + 1) & 1);
            if (l16 == 0) { mbar_expect_tx(sb + SM_BAR + MB_F + 8, 32768); XLOAD(1, s + 2); }
            __syncwarp();
            TST(s + 1, 27, l16, TCLK());
          }
          if (XPF && s + XPF < NSEG) {
            spin(DLY_PF);
            for (uint32_t i = xrank; i < 512; i += 32 * xcnt)
              asm volatile("prefetch.global.L2 [%0];" :: "l"(SP.x + (size_t)(s + XPF) * (SEG * DM) + i * 64));
            __syncwarp();
          }
          stg_2(P.win + (w_ar(s + 2) + cta * 256 + (l16 >> 1)), 0u, 0u);
        }
      } else {
        const int mt = wq - 2;
        const uint32_t lt = ls + mt * 1024;
        const uint32_t vi0 = w_blk(w_mvx(h * 4, 0), me2) + mt * 1024;
        const int m3d = r ? -8192 : 8192;
        for (int s = 0; s < NSEG; s++) {
          const uint32_t tg = (s & 1) ^ 1, t2 = ((s >> 1) & 1) ^ 1;
          {
            OPAQUE_R(l16);
            const uint32_t m3i = (mt * 2 + r) * 8192 + (l16 & 0x70u) + ((l16 & 0x180u) << 1);
            const uint32_t m3j = (mt * 2 + (r ^ (l16 >> 7 & 1))) * 8192 + (l16 & 256u) * 16 + (l16 & 0x70u) * 33 + 128;
            uint32_t m3c = sb + SM_MEM + mt * 8192 + cnt_line(l16 >> 4) * 128 + (l16 >> 2);
            const unsigned char* p3 = P.win + (m3i + w_ar(s - 1)); const unsigned char* pd = P.win + (m3j + w_ar(s - 1));
            OPAQUE_L(pd); OPAQUE_R(m3c);
            const int n = m3_gather(sb, p3, pd, m3d, l16, m3c, mt, me ^ 1 ^ r, s > 0);
            TST(s, mt ? 22 : 17, l16, n);
          }
          uint4 va[8], vm[2], p0; uint32_t p2;
          const unsigned char* a0 = P.win + (vi0 + ((s & 1) << 20) + l16);
#define VALD() _Pragma("unroll") for (int i = 0; i < 4; i++) { va[i] = ldg_r4(a0 + (i >> 1) * 512 + (i & 1) * 2048); va[4 + i] = ldg_r4(a0 + 16384 + (i >> 1) * 512 + (i & 1) * 2048); }
          spin(DLY_WO);
          VALD();
          {
          PTRS();
          bar_sync(B_V, 320);
            const float4 u0 = lds128f(lt + SM_VP), w0 = lds128f(lt + SM_VP + 2048), u1 = lds128f(lt + SM_VP + 512), w1 = lds128f(lt + SM_VP + 2560);
            const uint32_t m0 = tagw(pack_bf16(u0.x + w0.x, u0.y + w0.y), tg), m1 = pack_bf16(u0.z + w0.z, u0.w + w0.w),
                           m2 = pack_bf16(u1.x + w1.x, u1.y + w1.y), m3 = pack_bf16(u1.z + w1.z, u1.w + w1.w);
            stg_r4(pw0, m0, m1, m2, m3);
            if (wq == 2) TS(10);
            FENCE();
            const uint32_t tv = clk32();
            int n = 0;
#pragma unroll 1
            while (__any_sync(~0u, (or3(x3(va[0].x, va[1].x, t2), x3(va[2].x, va[3].x, t2), x3(va[4].x, va[5].x, t2)) | x3(va[6].x, va[7].x, t2)) & 1u) && ++n < SPIN_LIMIT) { VALD(); }
            TST(s, 20, l16 | mt, n);
            while (clk32() - tv < (uint32_t)DLY_V) {}
            uint4 v[3]; n = 0;
#pragma unroll 1
            do {
              v[0] = ldg_r4(pr0); v[1] = ldg_r4(pr1); v[2] = ldg_r4(pr1 + 2048);
              if (n && s < NSEG - 1) ETA(DLY_KS - 192, 0);
            } while (__any_sync(~0u, (x3(v[0].x, v[1].x, tg) | (v[2].x ^ tg)) & 1u) && ++n < SPIN_LIMIT);
            const uint4 A = make_uint4(addb2(m0, v[0].x), addb2(m1, v[0].y), addb2(m2, v[0].z), addb2(m3, v[0].w));
            const uint4 B = make_uint4(addb2(v[1].x, v[2].x), addb2(v[1].y, v[2].y), addb2(v[1].z, v[2].z), addb2(v[1].w, v[2].w));
            vm[0] = p ? B : A; vm[1] = p ? A : B;
            if (wq == 2) TS(11);
            TST(s, 26, l16 | !n, 1);
          }
          FENCE();
          if (s < NSEG - 1) {
          bar_sync(B_P, 96);
          p0 = lds128(ls + SM_PF); p2 = lds32(ls - l12 + SM_PF + 512);
          PV4(va, vm, SM_OF + mt * 512);
          bar_arrive(B_O, 320);
          }
          FENCE();
          if (wq == 2) TS(8);
          spin(DLY_PX);
          bar_sync(B_PX, 96);
          p0 = lds128(ls + SM_PX); p2 = lds32(ls - l12 + SM_PX + 512);
          PV4(va, vm, SM_OX + mt * 512);
          if (s < NSEG - 1) bar_arrive(B_PXF, 96);
          __syncwarp();
          {
            const uint32_t oa = sb + SM_OX + mt * 512 + ((l16 & 48u) << 3) + ((l16 >> 2) & 0x70u);
            const uint4 a = lds128(oa), b = lds128(oa + 1024);
            unsigned char* o = reinterpret_cast<unsigned char*>(g_ox + (size_t)(s * SEG + 8 * j) * (NH * DH) + h * DH + mt * 32) + ((l16 >> 6) * (NH * DH * 2) + (l16 & 48u));
            stg_4(o, a); stg_4(o + 128, b);
          }
          TST(s, 18, l16 | mt, TCLK());
        }
      }
    }
  }
  asm volatile("barrier.cluster.arrive.relaxed.aligned;\nbarrier.cluster.wait.aligned;" ::: "memory");
}
#define PW 2
#define G2_ST 6
#define G2_TB (G2_ST * 32768 + 1024)
#define G2_SMEM (G2_TB + 32768)
static __device__ __forceinline__ void wgmma_n128_ta(float (&d)[64], uint64_t da, uint64_t db) {
  asm volatile(
      "wgmma.mma_async.sync.aligned.m64n128k16.f32.bf16.bf16 "
      "{%0,%1,%2,%3,%4,%5,%6,%7,%8,%9,%10,%11,%12,%13,%14,%15,%16,%17,%18,%19,%20,%21,%22,%23,%24,%25,%26,%27,%28,%29,%30,%31,"
      "%32,%33,%34,%35,%36,%37,%38,%39,%40,%41,%42,%43,%44,%45,%46,%47,%48,%49,%50,%51,%52,%53,%54,%55,%56,%57,%58,%59,%60,%61,%62,%63}, "
      "%64, %65, 1, 1, 1, 1, 0;"
      : "+f"(d[0]), "+f"(d[1]), "+f"(d[2]), "+f"(d[3]), "+f"(d[4]), "+f"(d[5]), "+f"(d[6]), "+f"(d[7]), "+f"(d[8]), "+f"(d[9]), "+f"(d[10]), "+f"(d[11]),
        "+f"(d[12]), "+f"(d[13]), "+f"(d[14]), "+f"(d[15]), "+f"(d[16]), "+f"(d[17]), "+f"(d[18]), "+f"(d[19]), "+f"(d[20]), "+f"(d[21]), "+f"(d[22]), "+f"(d[23]),
        "+f"(d[24]), "+f"(d[25]), "+f"(d[26]), "+f"(d[27]), "+f"(d[28]), "+f"(d[29]), "+f"(d[30]), "+f"(d[31]), "+f"(d[32]), "+f"(d[33]), "+f"(d[34]), "+f"(d[35]),
        "+f"(d[36]), "+f"(d[37]), "+f"(d[38]), "+f"(d[39]), "+f"(d[40]), "+f"(d[41]), "+f"(d[42]), "+f"(d[43]), "+f"(d[44]), "+f"(d[45]), "+f"(d[46]), "+f"(d[47]),
        "+f"(d[48]), "+f"(d[49]), "+f"(d[50]), "+f"(d[51]), "+f"(d[52]), "+f"(d[53]), "+f"(d[54]), "+f"(d[55]), "+f"(d[56]), "+f"(d[57]), "+f"(d[58]), "+f"(d[59]),
        "+f"(d[60]), "+f"(d[61]), "+f"(d[62]), "+f"(d[63])
      : "l"(da), "l"(db));
}
__global__ void __cluster_dims__(2, 1, 1) __launch_bounds__(384, 1)
gemm2_kernel(const __grid_constant__ CUtensorMap tmo, const __grid_constant__ CUtensorMap tmw, const bf16* __restrict__ x, bf16* __restrict__ out, unsigned char* win) {
  extern __shared__ __align__(1024) unsigned char smem[];
  const uint32_t sb = smem_u32(smem), bars = sb + G2_ST * 32768;
  const int tid = threadIdx.x, lane = tid & 31, warp = tid >> 5;
  const int r = blockIdx.x & 1, n0 = (blockIdx.x & 7) * 128, m0 = (blockIdx.x >> 3) * 128;
  if (tid == 0) {
    for (int i = 0; i < G2_ST; i++) { mbar_init(bars + i * 8, 1); mbar_init(bars + 64 + i * 8, 4); }
    asm volatile("fence.mbarrier_init.release.cluster;" ::: "memory");
  }
  if (tid == 32) { asm volatile("prefetch.tensormap [%0];" :: "l"(&tmw) : "memory"); asm volatile("prefetch.tensormap [%0];" :: "l"(&tmo) : "memory"); }
  __syncthreads();
  asm volatile("barrier.cluster.arrive.relaxed.aligned;" ::: "memory");
#define LW(kt, st) do { tma_load_2d(sb + (st) * 32768, &tmw, n0, (kt) * 64, bars + (st) * 8); tma_load_2d(sb + (st) * 32768 + 8192, &tmw, n0 + 64, (kt) * 64, bars + (st) * 8); } while (0)
#define LO(kt, st) asm volatile("cp.async.bulk.tensor.2d.shared::cluster.global.mbarrier::complete_tx::bytes.multicast::cluster [%0], [%1, {%3, %4}], [%2], %5;" \
                     :: "r"(sb + (st) * 32768 + 16384 + r * 8192), "l"(&tmo), "r"(bars + (st) * 8), "r"((kt) * 64), "r"(m0 + r * 64), "h"((uint16_t)3) : "memory")
  if (tid == 256) for (int kt = 0; kt < G2_ST; kt++) { mbar_expect_tx(bars + kt * 8, 32768); if (kt < PW) LW(kt, kt); }
  __syncwarp();
  asm volatile("barrier.cluster.wait.acquire.aligned;" ::: "memory");
  if (warp == 8) {
    if (lane == 0) {
      asm volatile("griddepcontrol.wait;" ::: "memory");
      for (int kt = 0; kt < G2_ST; kt++) { LO(kt, kt); if (kt >= PW) LW(kt, kt); }
      for (int kt = G2_ST; kt < 64; kt++) {
        const int st = kt % G2_ST;
        mbar_wait(bars + 64 + st * 8, ((kt / G2_ST) - 1) & 1);
        mbar_expect_tx(bars + st * 8, 32768);
        LO(kt, st); LW(kt, st);
      }
    }
  } else if (warp > 8) {
    const int t = tid - 288, ch = t & 15;
    asm volatile("griddepcontrol.wait;" ::: "memory");
    int idx[8];
#pragma unroll
    for (int c = 0; c < 8; c++) idx[c] = g_idx[c];
    const int gi = blockIdx.x * 96 + t;
    if (gi < 67) g_side[gi * 32] = 0u;
    if (gi == 0) g_sbar = 0u;
#pragma unroll 4
    for (int row = t >> 4; row < 128; row += 6) {
      const int tok = m0 + row;
      const uint4 xv = *reinterpret_cast<const uint4*>(x + (size_t)tok * DM + n0 + ch * 8);
      const float g = g_gate[tok], omg = rbf(1.f - g);
      int sel = -1;
#pragma unroll
      for (int c = 0; c < 8; c++) if (idx[c] == tok) sel = c;
      uint4 uv = make_uint4(0u, 0u, 0u, 0u);
      if (sel >= 0) uv = *reinterpret_cast<const uint4*>(g_upd + sel * DM + n0 + ch * 8);
      const uint32_t x4[4] = {xv.x, xv.y, xv.z, xv.w}, u4[4] = {uv.x, uv.y, uv.z, uv.w};
      uint32_t o4[4];
#pragma unroll
      for (int e = 0; e < 4; e++) {
        const float b0 = rbf(u2f(x4[e] << 16) + u2f(u4[e] << 16)), b1 = rbf(u2f(x4[e] & 0xffff0000u) + u2f(u4[e] & 0xffff0000u));
        o4[e] = pack_bf16(omg * b0, omg * b1);
      }
      sts128(sb + G2_TB + row * 256 + ch * 16, o4[0], o4[1], o4[2], o4[3]);
      if (ch == 0) sts32(bars + 512 + row * 4, __float_as_uint(g));
    }
    bar_arrive(2, 352);
  } else {
    const int wg = warp >> 2;
    float d[64];
#pragma unroll
    for (int i = 0; i < 64; i++) d[i] = 0.f;
    const uint32_t e0 = mapa(bars + 64, 0), e1 = mapa(bars + 64, 1);
    for (int kt = 0; kt < 64; kt++) {
      const int st = kt % G2_ST;
      mbar_wait(bars + st * 8, (kt / G2_ST) & 1);
      wg_fence();
#pragma unroll
      for (int kk = 0; kk < 4; kk++)
        wgmma_n128_ta(d, make_desc(sb + st * 32768 + wg * 8192 + kk * 2048, 1024, 1024), make_desc(sb + st * 32768 + 16384 + kk * 32, 16, 1024));
      wg_commit();
      asm volatile("wgmma.wait_group.sync.aligned 1;" ::: "memory");
      if (kt > 0 && (tid & 127) == 0) { const int ps = (kt - 1) % G2_ST; mbar_arrive_cluster_rlx(e0 + ps * 8); mbar_arrive_cluster_rlx(e1 + ps * 8); }
    }
    wg_wait0();
    bar_sync(1, 256);
#pragma unroll
    for (int jj = 0; jj < 8; jj++) {
      const uint32_t q0 = pack_bf16(d[8 * jj], d[8 * jj + 1]), q1 = pack_bf16(d[8 * jj + 2], d[8 * jj + 3]);
      const uint32_t q2 = pack_bf16(d[8 * jj + 4], d[8 * jj + 5]), q3 = pack_bf16(d[8 * jj + 6], d[8 * jj + 7]);
      stsm4t(sb + (jj * 16 + (lane >> 4) * 8 + (lane & 7)) * 272 + (warp * 16 + ((lane >> 3) & 1) * 8) * 2, q0, q1, q2, q3);
    }
    bar_sync(2, 352);
#pragma unroll
    for (int it = 0; it < 8; it++) {
      const int row = it * 16 + (tid >> 4), ch = tid & 15, tok = m0 + row;
      const uint4 av = lds128(sb + row * 272 + ch * 16), tv = lds128(sb + G2_TB + row * 256 + ch * 16);
      const float g = u2f(lds32(bars + 512 + row * 4));
      const uint32_t a4[4] = {av.x, av.y, av.z, av.w}, t4[4] = {tv.x, tv.y, tv.z, tv.w};
      uint32_t o4[4];
#pragma unroll
      for (int e = 0; e < 4; e++)
        o4[e] = pack_bf16(rbf(g * u2f(a4[e] << 16)) + u2f(t4[e] << 16), rbf(g * u2f(a4[e] & 0xffff0000u)) + u2f(t4[e] & 0xffff0000u));
      *reinterpret_cast<uint4*>(out + (size_t)tok * DM + n0 + ch * 8) = make_uint4(o4[0], o4[1], o4[2], o4[3]);
    }
  }
  asm volatile("barrier.cluster.arrive.relaxed.aligned;\nbarrier.cluster.wait.aligned;" ::: "memory");
}
#define WPROM CU_TENSOR_MAP_L2_PROMOTION_L2_128B
#define PDL 1
typedef CUresult (*PFN_encodeTiled)(CUtensorMap*, CUtensorMapDataType, cuuint32_t, void*, const cuuint64_t*, const cuuint64_t*,
                                    const cuuint32_t*, const cuuint32_t*, CUtensorMapInterleave, CUtensorMapSwizzle,
                                    CUtensorMapL2promotion, CUtensorMapFloatOOBfill);

extern "C" void kernel_launch(void* const* d_in, const int* in_sizes, int n_in, void* d_out, int out_size) {
  const bf16* x = (const bf16*)d_in[0];
  const bf16* mem0 = (const bf16*)d_in[1];
  const bf16* Wq = (const bf16*)d_in[2];
  const bf16* Wk = (const bf16*)d_in[3];
  const bf16* Wv = (const bf16*)d_in[4];
  const bf16* Wo = (const bf16*)d_in[5];
  const bf16* w_r = (const bf16*)d_in[8];
  const bf16* w_gate = (const bf16*)d_in[9];
  const bf16* w_up = (const bf16*)d_in[10];
  const bf16* w_down = (const bf16*)d_in[11];
  const bf16* gate_w = (const bf16*)d_in[12];
  bf16* out = (bf16*)d_out;

  static PFN_encodeTiled encode = nullptr;
  if (!encode) {
    void* fn = nullptr; cudaDriverEntryPointQueryResult st;
    cudaGetDriverEntryPoint("cuTensorMapEncodeTiled", &fn, cudaEnableDefault, &st);
    encode = (PFN_encodeTiled)fn;
    cudaFuncSetAttribute(rec_kernel, cudaFuncAttributeMaxDynamicSharedMemorySize, SM_TOTAL);
    cudaFuncSetAttribute(gemm2_kernel, cudaFuncAttributeMaxDynamicSharedMemorySize, G2_SMEM);
  }
  CUtensorMap tmx;
  {
    cuuint64_t gd[3] = {64, S_TOK, DM / 64};
    cuuint64_t gs[2] = {DM * 2, 128};
    cuuint32_t bx[3] = {64, SEG, 2};
    cuuint32_t es[3] = {1, 1, 1};
    encode(&tmx, CU_TENSOR_MAP_DATA_TYPE_BFLOAT16, 3, (void*)x, gd, gs, bx, es, CU_TENSOR_MAP_INTERLEAVE_NONE,
           CU_TENSOR_MAP_SWIZZLE_128B, CU_TENSOR_MAP_L2_PROMOTION_L2_128B, CU_TENSOR_MAP_FLOAT_OOB_FILL_NONE);
  }
  bf16* ox;
  cudaGetSymbolAddress((void**)&ox, g_ox);
  CUtensorMap tmo, tmw;
  {
    cuuint64_t gd[2] = {NH * DH, S_TOK}; cuuint64_t gs[1] = {NH * DH * 2}; cuuint32_t bx[2] = {64, 64}; cuuint32_t es[2] = {1, 1};
    encode(&tmo, CU_TENSOR_MAP_DATA_TYPE_BFLOAT16, 2, (void*)ox, gd, gs, bx, es, CU_TENSOR_MAP_INTERLEAVE_NONE,
           CU_TENSOR_MAP_SWIZZLE_128B, CU_TENSOR_MAP_L2_PROMOTION_L2_128B, CU_TENSOR_MAP_FLOAT_OOB_FILL_NONE);
    cuuint64_t gd2[2] = {DM, NH * DH}; cuuint64_t gs2[1] = {DM * 2}; cuuint32_t bx2[2] = {64, 64};
    encode(&tmw, CU_TENSOR_MAP_DATA_TYPE_BFLOAT16, 2, (void*)Wo, gd2, gs2, bx2, es, CU_TENSOR_MAP_INTERLEAVE_NONE,
           CU_TENSOR_MAP_SWIZZLE_128B, CU_TENSOR_MAP_L2_PROMOTION_L2_128B, CU_TENSOR_MAP_FLOAT_OOB_FILL_NONE);
  }
  unsigned char* win;
  cudaGetSymbolAddress((void**)&win, g_win);
  win = (unsigned char*)(((uintptr_t)win + (2u << 20) - 1) & ~(uintptr_t)((2u << 20) - 1));
  WMaps W;
  {
    cuuint64_t gd[2] = {NH * DH, DM}; cuuint64_t gs[1] = {NH * DH * 2}; cuuint32_t b32[2] = {32, 128}, b64[2] = {64, 128}; cuuint32_t es[2] = {1, 1};
    encode(&W.q, CU_TENSOR_MAP_DATA_TYPE_BFLOAT16, 2, (void*)Wq, gd, gs, b32, es, CU_TENSOR_MAP_INTERLEAVE_NONE,
           CU_TENSOR_MAP_SWIZZLE_64B, WPROM, CU_TENSOR_MAP_FLOAT_OOB_FILL_NONE);
    encode(&W.k, CU_TENSOR_MAP_DATA_TYPE_BFLOAT16, 2, (void*)Wk, gd, gs, b32, es, CU_TENSOR_MAP_INTERLEAVE_NONE,
           CU_TENSOR_MAP_SWIZZLE_64B, WPROM, CU_TENSOR_MAP_FLOAT_OOB_FILL_NONE);
    encode(&W.v, CU_TENSOR_MAP_DATA_TYPE_BFLOAT16, 2, (void*)Wv, gd, gs, b64, es, CU_TENSOR_MAP_INTERLEAVE_NONE,
           CU_TENSOR_MAP_SWIZZLE_128B, WPROM, CU_TENSOR_MAP_FLOAT_OOB_FILL_NONE);
  }
  RecParams P{mem0, win};
  SideParams SP{x, w_r, w_gate, w_up, w_down, gate_w, Wo};
  rec_kernel<<<NCTA + 4, 384, SM_TOTAL, cudaStreamPerThread>>>(tmx, tmw, W, P, SP);
  {
    cudaLaunchConfig_t cfg = {};
    cfg.gridDim = dim3(NCTA); cfg.blockDim = dim3(384); cfg.dynamicSmemBytes = G2_SMEM; cfg.stream = cudaStreamPerThread;
    cudaLaunchAttribute at[1];
    at[0].id = cudaLaunchAttributeProgrammaticStreamSerialization; at[0].val.programmaticStreamSerializationAllowed = 1;
    cfg.attrs = at; cfg.numAttrs = PDL;
    cudaLaunchKernelEx(&cfg, gemm2_kernel, tmo, tmw, x, out, win);
  }
}
```

```cpp
#include <cuda_runtime.h>
#include <cuda_bf16.h>
#include <cuda_fp16.h>
#include <cuda.h>
#include <stdint.h>

typedef __nv_bfloat16 bf16;

#define S_TOK 2048
#define DM 1024
#define NH 32
#define DH 128
#define MM 8
#define SEG 32
#define NSEG 64
#define LL 40
#define FF 3584
#define NCTA 128

static __device__ bf16 g_ox[(size_t)S_TOK * NH * DH];
static __device__ float g_gate[S_TOK];
static __device__ float g_r[S_TOK];
static __device__ int g_idx[8];
static __device__ bf16 g_upd[8 * DM];

static __device__ __forceinline__ float rbf(float v) { return __bfloat162float(__float2bfloat16(v)); }
static __device__ __forceinline__ uint32_t smem_u32(const void* p) { return (uint32_t)__cvta_generic_to_shared(p); }
static __device__ __forceinline__ uint32_t pack_bf16(float lo, float hi) {
  __nv_bfloat162 v = __floats2bfloat162_rn(lo, hi);
  return *reinterpret_cast<uint32_t*>(&v);
}

static __device__ __forceinline__ void wg_fence() { asm volatile("wgmma.fence.sync.aligned;" ::: "memory"); }
static __device__ __forceinline__ void wg_commit() { asm volatile("wgmma.commit_group.sync.aligned;" ::: "memory"); }
static __device__ __forceinline__ void wg_wait0() { asm volatile("wgmma.wait_group.sync.aligned 0;" ::: "memory"); }
static __device__ __forceinline__ void fence_async_smem() { asm volatile("fence.proxy.async.shared::cta;" ::: "memory"); }

static __device__ __forceinline__ uint64_t make_desc(uint32_t addr, uint32_t lbo, uint32_t sbo) {
  uint64_t d = 0;
  d |= (uint64_t)((addr & 0x3FFFF) >> 4);
  d |= (uint64_t)((lbo >> 4) & 0x3FFF) << 16;
  d |= (uint64_t)((sbo >> 4) & 0x3FFF) << 32;
  d |= (uint64_t)1 << 62;
  return d;
}

#define DESC_HI(sbo) (((sbo) >> 4) | (1u << 30))
template <int OFF, int SCALE>
static __device__ __forceinline__ void wgmma_n32_ra(float (&d)[16], const uint32_t (&a)[4], uint32_t base16) {
  asm volatile(
      "{\n.reg .b32 t;\n.reg .b64 dd;\nadd.u32 t, %20, %21;\nmov.b64 dd, {t, %22};\n"
      "wgmma.mma_async.sync.aligned.m64n32k16.f32.bf16.bf16 "
      "{%0,%1,%2,%3,%4,%5,%6,%7,%8,%9,%10,%11,%12,%13,%14,%15}, {%16,%17,%18,%19}, dd, %23, 1, 1, 0;\n}"
      : "+f"(d[0]), "+f"(d[1]), "+f"(d[2]), "+f"(d[3]), "+f"(d[4]), "+f"(d[5]), "+f"(d[6]), "+f"(d[7]),
        "+f"(d[8]), "+f"(d[9]), "+f"(d[10]), "+f"(d[11]), "+f"(d[12]), "+f"(d[13]), "+f"(d[14]), "+f"(d[15])
      : "r"(a[0]), "r"(a[1]), "r"(a[2]), "r"(a[3]), "r"(base16), "n"(OFF >> 4), "n"(DESC_HI(1024)), "n"(SCALE));
}
template <int AOFF, int BOFF, int SCALE>
static __device__ __forceinline__ void wgmma_n32_ss_ta(float (&d)[16], uint32_t abase16, uint32_t bbase16) {
  asm volatile(
      "{\n.reg .b32 t, u;\n.reg .b64 da, db;\nadd.u32 t, %16, %18;\nmov.b64 da, {t, %20};\nadd.u32 u, %17, %19;\nmov.b64 db, {u, %20};\n"
      "wgmma.mma_async.sync.aligned.m64n32k16.f32.bf16.bf16 "
      "{%0,%1,%2,%3,%4,%5,%6,%7,%8,%9,%10,%11,%12,%13,%14,%15}, da, db, %21, 1, 1, 1, 0;\n}"
      : "+f"(d[0]), "+f"(d[1]), "+f"(d[2]), "+f"(d[3]), "+f"(d[4]), "+f"(d[5]), "+f"(d[6]), "+f"(d[7]),
        "+f"(d[8]), "+f"(d[9]), "+f"(d[10]), "+f"(d[11]), "+f"(d[12]), "+f"(d[13]), "+f"(d[14]), "+f"(d[15])
      : "r"(abase16), "r"(bbase16), "n"(AOFF >> 4), "n"(BOFF >> 4), "n"(DESC_HI(1024)), "n"(SCALE));
}
static __device__ __forceinline__ void ldmatrix_x4_trans(uint32_t (&r)[4], uint32_t addr) {
  asm volatile("ldmatrix.sync.aligned.m8n8.x4.trans.shared.b16 {%0,%1,%2,%3}, [%4];"
               : "=r"(r[0]), "=r"(r[1]), "=r"(r[2]), "=r"(r[3]) : "r"(addr) : "memory");
}
static __device__ __forceinline__ void mma_16816(float (&d)[4], const uint32_t (&a)[4], uint32_t b0, uint32_t b1) {
  asm volatile("mma.sync.aligned.m16n8k16.row.col.f32.bf16.bf16.f32 {%0,%1,%2,%3}, {%4,%5,%6,%7}, {%8,%9}, {%0,%1,%2,%3};"
               : "+f"(d[0]), "+f"(d[1]), "+f"(d[2]), "+f"(d[3])
               : "r"(a[0]), "r"(a[1]), "r"(a[2]), "r"(a[3]), "r"(b0), "r"(b1));
}

static __device__ __forceinline__ uint32_t mapa(uint32_t addr, uint32_t rank) {
  uint32_t r; asm volatile("mapa.shared::cluster.u32 %0, %1, %2;" : "=r"(r) : "r"(addr), "r"(rank)); return r;
}

static __device__ __forceinline__ void mbar_init(uint32_t bar, int cnt) {
  asm volatile("mbarrier.init.shared::cta.b64 [%0], %1;" :: "r"(bar), "r"(cnt) : "memory");
}
static __device__ __forceinline__ void mbar_expect_tx(uint32_t bar, uint32_t bytes) {
  asm volatile("mbarrier.arrive.expect_tx.shared::cta.b64 _, [%0], %1;" :: "r"(bar), "r"(bytes) : "memory");
}
static __device__ __forceinline__ void tma_load_2d(uint32_t dst, const CUtensorMap* tm, int c0, int c1, uint32_t bar) {
  asm volatile("cp.async.bulk.tensor.2d.shared::cluster.global.mbarrier::complete_tx::bytes [%0], [%1, {%3, %4}], [%2];"
               :: "r"(dst), "l"(tm), "r"(bar), "r"(c0), "r"(c1) : "memory");
}

static __device__ unsigned char g_win[6 << 20];
static __device__ unsigned int g_side[67 * 32];
static __device__ unsigned int g_err;
#define W_UP (1u << 20)
#define W_2 (2u << 20)
static __device__ __forceinline__ uint32_t w_blk(uint32_t off, uint32_t side) { return off | (((__popc((off >> 12) & 0xb3u) ^ side) & 1u) << 12); }
static __device__ __forceinline__ uint32_t w_h1(int c) { return W_UP | (1u << 13) | ((c >> 1) << 14) | ((c & 1) << 11); }
static __device__ __forceinline__ uint32_t w_ar(int s) { return ((s & 1) << 15) | ((s & 2) << 17); }
static __device__ __forceinline__ uint32_t w_mvx(int c, int s) { return W_2 | ((s & 1) << 20) | ((c >> 1) << 14) | ((c & 1) << 11); }
static __device__ __forceinline__ uint32_t w_mxa(int c, int s) { return W_2 | ((s & 1) << 20) | (1u << 13) | ((c >> 1) << 14) | ((c & 1) << 11); }
#define H1_V (1u << 13)

#define SPIN_LIMIT (1 << 18)

#define SM_X 0
#define SM_WOS 65536
#define SM_WVS 131072
#define SM_MEM 163840
#define SM_QKP 180224
#define SM_VP 184320
#define SM_CW 188416
#define SM_VST 196608
#define SM_VR 196608
#define SM_CQ 200704
#define SM_CV 208896
#define SM_XF 217088
#define SM_VL 221184
#define SM_OF 225280
#define SM_OX 227328
#define SM_PF 229376
#define SM_PX 230016
#define SM_RD 223232
#define SM_XS 231168
#define SM_BAR 231808
#define SM_TAB 231936
#define SM_TS 232064
#define NTS 40
#define SM_TOTAL SM_TS
#define MB_F 0
#define MB_XE0 16
#define MB_XE1 112
#define MB_INIT 24
#define MB_MEM 32
#define MB_W 48
#define MB_XF 64
#define MB_VR 72
#define MB_X0 80
#define MB_WO 88
#define SM_SIDE (SM_BAR + 96)
#define MB_PX 120
#define B_QK 1
#define B_V 2
#define B_P 3
#define B_O 4
#define B_M2 5
#define B_PUB 6
#define B_CQ 7
#define B_QK1 8
#define B_ALL 9
#define B_PXF 10
#define B_CV 15
#define B_X2 11
#define B_PX 12
#define B_GO 14
#define B_RD 13

#define TST(a, b, c, d)
#define TSF(i, w)
#define TSP(i, w)
#define TVF(i, v)
#define TS(i)
#define TV(i, v)

static __device__ __forceinline__ void bar_sync(int id, int n) { asm volatile("bar.sync %0, %1;" :: "r"(id), "r"(n) : "memory"); }
static __device__ __forceinline__ void bar_arrive(int id, int n) { asm volatile("bar.arrive %0, %1;" :: "r"(id), "r"(n) : "memory"); }
static __device__ __forceinline__ uint4 ldg_r4(const void* p) { uint4 v;
  asm volatile("ld.relaxed.gpu.global.v4.u32 {%0,%1,%2,%3}, [%4];" : "=r"(v.x), "=r"(v.y), "=r"(v.z), "=r"(v.w) : "l"(p) : "memory"); return v; }
static __device__ __forceinline__ uint32_t ldg_r1(const void* p) { uint32_t v;
  asm volatile("ld.relaxed.gpu.global.u32 %0, [%1];" : "=r"(v) : "l"(p) : "memory"); return v; }
template <int OFF> static __device__ __forceinline__ uint32_t ldg_r1o(const void* p) { uint32_t v;
  asm volatile("ld.relaxed.gpu.global.u32 %0, [%1+%2];" : "=r"(v) : "l"(p), "n"(OFF) : "memory"); return v; }
static __device__ __forceinline__ void stg_r4(void* p, uint32_t a, uint32_t b, uint32_t c, uint32_t d) {
  asm volatile("st.relaxed.gpu.global.v4.u32 [%0], {%1,%2,%3,%4};" :: "l"(p), "r"(a), "r"(b), "r"(c), "r"(d) : "memory"); }
static __device__ __forceinline__ void stg_r2(void* p, uint32_t a, uint32_t b) {
  asm volatile("st.relaxed.gpu.global.v2.u32 [%0], {%1,%2};" :: "l"(p), "r"(a), "r"(b) : "memory"); }
static __device__ __forceinline__ uint2 ldg_r2(const void* p) { uint2 v;
  asm volatile("ld.relaxed.gpu.global.v2.u32 {%0,%1}, [%2];" : "=r"(v.x), "=r"(v.y) : "l"(p) : "memory"); return v; }
static __device__ __forceinline__ void stg_4(void* p, const uint4& v) {
  asm volatile("st.global.v4.u32 [%0], {%1,%2,%3,%4};" :: "l"(p), "r"(v.x), "r"(v.y), "r"(v.z), "r"(v.w) : "memory"); }
static __device__ __forceinline__ uint32_t f2u(float v) { return __float_as_uint(v); }
static __device__ __forceinline__ void stg_2(void* p, uint32_t a, uint32_t b) {
  asm volatile("st.global.v2.u32 [%0], {%1,%2};" :: "l"(p), "r"(a), "r"(b) : "memory"); }
static __device__ __forceinline__ void stg_r1(void* p, uint32_t a) {
  asm volatile("st.relaxed.gpu.global.u32 [%0], %1;" :: "l"(p), "r"(a) : "memory"); }
static __device__ __forceinline__ void sts128(uint32_t a, uint32_t x, uint32_t y, uint32_t z, uint32_t w) {
  asm volatile("st.shared.v4.u32 [%0], {%1,%2,%3,%4};" :: "r"(a), "r"(x), "r"(y), "r"(z), "r"(w) : "memory"); }
static __device__ __forceinline__ void sts128f(uint32_t a, float x, float y, float z, float w) {
  asm volatile("st.shared.v4.f32 [%0], {%1,%2,%3,%4};" :: "r"(a), "f"(x), "f"(y), "f"(z), "f"(w) : "memory"); }
static __device__ __forceinline__ uint4 lds128(uint32_t a) { uint4 v;
  asm volatile("ld.shared.v4.u32 {%0,%1,%2,%3}, [%4];" : "=r"(v.x), "=r"(v.y), "=r"(v.z), "=r"(v.w) : "r"(a) : "memory"); return v; }
static __device__ __forceinline__ float4 lds128f(uint32_t a) { float4 v;
  asm volatile("ld.shared.v4.f32 {%0,%1,%2,%3}, [%4];" : "=f"(v.x), "=f"(v.y), "=f"(v.z), "=f"(v.w) : "r"(a) : "memory"); return v; }
static __device__ __forceinline__ void sts32(uint32_t a, uint32_t x) { asm volatile("st.shared.u32 [%0], %1;" :: "r"(a), "r"(x) : "memory"); }
static __device__ __forceinline__ void sts64f(uint32_t a, float x, float y) { asm volatile("st.shared.v2.f32 [%0], {%1,%2};" :: "r"(a), "f"(x), "f"(y) : "memory"); }
static __device__ __forceinline__ uint2 lds64(uint32_t a) { uint2 v;
  asm volatile("ld.shared.v2.u32 {%0,%1}, [%2];" : "=r"(v.x), "=r"(v.y) : "r"(a) : "memory"); return v; }
static __device__ __forceinline__ void st_async4(uint32_t ra, float x, float y, float z, float w, uint32_t rbar) {
  asm volatile("st.async.weak.shared::cluster.mbarrier::complete_tx::bytes.v4.f32 [%0], {%1,%2,%3,%4}, [%5];"
               :: "r"(ra), "f"(x), "f"(y), "f"(z), "f"(w), "r"(rbar) : "memory"); }
static __device__ __forceinline__ void stsm4t(uint32_t a, uint32_t x, uint32_t y, uint32_t z, uint32_t w) {
  asm volatile("stmatrix.sync.aligned.m8n8.x4.trans.shared.b16 [%0], {%1,%2,%3,%4};" :: "r"(a), "r"(x), "r"(y), "r"(z), "r"(w) : "memory"); }
static __device__ __forceinline__ uint4 ldsm4(uint32_t a) { uint4 v;
  asm volatile("ldmatrix.sync.aligned.m8n8.x4.shared.b16 {%0,%1,%2,%3}, [%4];" : "=r"(v.x), "=r"(v.y), "=r"(v.z), "=r"(v.w) : "r"(a) : "memory"); return v; }
static __device__ __forceinline__ uint4 ldsm4t(uint32_t a) { uint4 v;
  asm volatile("ldmatrix.sync.aligned.m8n8.x4.trans.shared.b16 {%0,%1,%2,%3}, [%4];" : "=r"(v.x), "=r"(v.y), "=r"(v.z), "=r"(v.w) : "r"(a) : "memory"); return v; }
static __device__ __forceinline__ uint32_t movm(uint32_t a) { uint32_t d;
  asm volatile("movmatrix.sync.aligned.m8n8.trans.b16 %0, %1;" : "=r"(d) : "r"(a)); return d; }
static __device__ __forceinline__ float u2f(uint32_t v) { return __uint_as_float(v); }
static __device__ __forceinline__ uint32_t nz(uint32_t w) { return w == 0u ? 0x8000u : w; }
static __device__ __forceinline__ uint32_t tagw(uint32_t w, uint32_t t) { uint32_t d;
  asm("lop3.b32 %0, %1, %2, 1, 0xd8;" : "=r"(d) : "r"(w), "r"(t)); return d; }
static __device__ __forceinline__ uint32_t pack_m2(float lo, float hi, uint32_t t) { return tagw(pack_bf16(lo, hi), t); }
static __device__ __forceinline__ uint32_t pack_f16(float lo, float hi) { uint32_t d;
  asm("cvt.rn.satfinite.f16x2.f32 %0, %1, %2;" : "=r"(d) : "f"(hi), "f"(lo)); return d; }
static __device__ __forceinline__ void sum_h4(float& lo, float& hi, uint32_t a, uint32_t b, uint32_t c, uint32_t d) {
  const float2 x = __half22float2(*reinterpret_cast<__half2*>(&a)), y = __half22float2(*reinterpret_cast<__half2*>(&b));
  const float2 z = __half22float2(*reinterpret_cast<__half2*>(&c)), w = __half22float2(*reinterpret_cast<__half2*>(&d));
  lo = (x.x + y.x) + (z.x + w.x); hi = (x.y + y.y) + (z.y + w.y);
}
static __device__ __forceinline__ void add_q3(float& lo, float& hi, uint32_t a, uint32_t b, uint32_t c) {
  uint32_t t;
  asm("{\n.reg .b32 u;\nmul.rn.f16x2 u, %1, %4;\nfma.rn.f16x2 u, %2, %4, u;\nfma.rn.f16x2 %0, %3, %4, u;\n}" : "=r"(t) : "r"(a), "r"(b), "r"(c), "r"(0x34003400u));
  const float2 x = __half22float2(*reinterpret_cast<__half2*>(&t));
  lo += x.x; hi += x.y;
}
static __device__ __forceinline__ uint32_t lds32(uint32_t a) { uint32_t v; asm volatile("ld.shared.u32 %0, [%1];" : "=r"(v) : "r"(a) : "memory"); return v; }
static __device__ __forceinline__ uint32_t addb2(uint32_t a, uint32_t b) { uint32_t d;
  asm("add.rn.bf16x2 %0, %1, %2;" : "=r"(d) : "r"(a), "r"(b)); return d; }
static __device__ __forceinline__ uint32_t mulb2(uint32_t a, uint32_t b) { uint32_t d;
  asm("mul.rn.bf16x2 %0, %1, %2;" : "=r"(d) : "r"(a), "r"(b)); return d; }
static __device__ __forceinline__ uint32_t x3(uint32_t a, uint32_t b, uint32_t t) { uint32_t d;
  asm("lop3.b32 %0, %1, %2, %3, 0x7e;" : "=r"(d) : "r"(a), "r"(b), "r"(t)); return d; }
static __device__ __forceinline__ uint32_t or3(uint32_t a, uint32_t b, uint32_t c) { uint32_t d;
  asm("lop3.b32 %0, %1, %2, %3, 0xfe;" : "=r"(d) : "r"(a), "r"(b), "r"(c)); return d; }
static __device__ __forceinline__ uint32_t bad4(const uint4& u, uint32_t t) { return x3(u.x, u.y, t) | x3(u.z, u.w, t); }
static __device__ __forceinline__ uint32_t bad8(const uint4& u, const uint4& v, uint32_t t) {
  return or3(x3(u.x, u.y, t), x3(u.z, u.w, t), x3(v.x, v.y, t)) | x3(v.z, v.w, t); }
static __device__ __forceinline__ float ex2(float x) { float y; asm("ex2.approx.ftz.f32 %0, %1;" : "=f"(y) : "f"(x)); return y; }
static __device__ __forceinline__ float rcpf(float x) { float y; asm("rcp.approx.ftz.f32 %0, %1;" : "=f"(y) : "f"(x)); return y; }
static __device__ __forceinline__ void mbar_wait(uint32_t bar, int parity) {
  asm volatile("{\n.reg .pred p, q;\n.reg .u32 n;\nmbarrier.try_wait.parity.shared::cta.b64 p, [%0], %1;\n@p bra W_DONE;\nmov.u32 n, 0;\n"
               "W_LOOP:\nmbarrier.try_wait.parity.shared::cta.b64 p, [%0], %1;\nadd.u32 n, n, 1;\nsetp.lt.and.u32 q, n, %2, !p;\n@q bra W_LOOP;\nW_DONE:\n}"
               :: "r"(bar), "r"(parity), "n"(SPIN_LIMIT) : "memory");
}
static __device__ __forceinline__ uint32_t mbar_test(uint32_t bar, int parity) { uint32_t ok;
  asm volatile("{\n.reg .pred p;\nmbarrier.test_wait.parity.shared::cta.b64 p, [%1], %2;\nselp.u32 %0, 1, 0, p;\n}" : "=r"(ok) : "r"(bar), "r"(parity) : "memory"); return ok; }
static __device__ __forceinline__ void mbar_arrive(uint32_t bar) {
  asm volatile("mbarrier.arrive.shared::cta.b64 _, [%0];" :: "r"(bar) : "memory"); }
static __device__ __forceinline__ void mbar_arrive_cluster_rlx(uint32_t raddr) {
  asm volatile("mbarrier.arrive.relaxed.cluster.shared::cluster.b64 _, [%0];" :: "r"(raddr) : "memory"); }
static __device__ __forceinline__ void tma_load_mc(uint32_t dst, const CUtensorMap* tm, int c1, int c2, uint32_t bar) {
  asm volatile("cp.async.bulk.tensor.3d.shared::cluster.global.mbarrier::complete_tx::bytes.multicast::cluster [%0], [%1, {%3, %4, %5}], [%2], %6;"
               :: "r"(dst), "l"(tm), "r"(bar), "r"(0), "r"(c1), "r"(c2), "h"((uint16_t)3) : "memory"); }
static __device__ __forceinline__ void cp16(uint32_t dst, const void* src) {
  asm volatile("cp.async.cg.shared.global [%0], [%1], 16;" :: "r"(dst), "l"(src) : "memory"); }
static __device__ __forceinline__ void mma_1688(float (&d)[4], uint32_t a0, uint32_t a1, uint32_t b0) {
  asm volatile("mma.sync.aligned.m16n8k8.row.col.f32.bf16.bf16.f32 {%0,%1,%2,%3}, {%4,%5}, {%6}, {%0,%1,%2,%3};"
               : "+f"(d[0]), "+f"(d[1]), "+f"(d[2]), "+f"(d[3]) : "r"(a0), "r"(a1), "r"(b0)); }
static __device__ __forceinline__ void mma4(float (&d)[4], uint32_t a0, uint32_t a1, uint32_t a2, uint32_t a3, uint32_t b0, uint32_t b1) {
  asm volatile("mma.sync.aligned.m16n8k16.row.col.f32.bf16.bf16.f32 {%0,%1,%2,%3}, {%4,%5,%6,%7}, {%8,%9}, {%0,%1,%2,%3};"
               : "+f"(d[0]), "+f"(d[1]), "+f"(d[2]), "+f"(d[3]) : "r"(a0), "r"(a1), "r"(a2), "r"(a3), "r"(b0), "r"(b1)); }
static __device__ __forceinline__ void mma4z(float (&d)[4], uint32_t a0, uint32_t a1, uint32_t a2, uint32_t a3, uint32_t b0, uint32_t b1) {
  asm volatile("mma.sync.aligned.m16n8k16.row.col.f32.bf16.bf16.f32 {%0,%1,%2,%3}, {%4,%5,%6,%7}, {%8,%9}, {%10,%10,%10,%10};"
               : "=f"(d[0]), "=f"(d[1]), "=f"(d[2]), "=f"(d[3]) : "r"(a0), "r"(a1), "r"(a2), "r"(a3), "r"(b0), "r"(b1), "f"(0.f)); }
static __device__ __forceinline__ void mma4h(float (&d)[4], uint32_t a0, uint32_t a1, uint32_t a2, uint32_t a3, uint32_t b) {
  asm volatile("mma.sync.aligned.m16n8k16.row.col.f32.f16.f16.f32 {%0,%1,%2,%3}, {%4,%5,%6,%7}, {%8,%8}, {%0,%1,%2,%3};"
               : "+f"(d[0]), "+f"(d[1]), "+f"(d[2]), "+f"(d[3]) : "r"(a0), "r"(a1), "r"(a2), "r"(a3), "r"(b)); }
static __device__ __forceinline__ void mma2h(float (&d)[4], uint32_t a0, uint32_t a1, uint32_t b) {
  asm volatile("mma.sync.aligned.m16n8k8.row.col.f32.f16.f16.f32 {%0,%1,%2,%3}, {%4,%5}, {%6}, {%0,%1,%2,%3};"
               : "+f"(d[0]), "+f"(d[1]), "+f"(d[2]), "+f"(d[3]) : "r"(a0), "r"(a1), "r"(b)); }
static __device__ __forceinline__ uint32_t clk32() { uint32_t t; asm volatile("mov.u32 %0, %%clock;" : "=r"(t)); return t; }
static __device__ __forceinline__ uint32_t gt32() { uint32_t t; asm volatile("mov.u32 %0, %%globaltimer_lo;" : "=r"(t)); return t; }
static __device__ __forceinline__ void spin(int clk) { if (clk > 0) { uint32_t t = clk32(); while (clk32() - t < (uint32_t)clk) {} } }
#define FENCE() asm volatile("griddepcontrol.launch_dependents;" ::: "memory")
#define OPAQUE_L(p) asm volatile("" : "+l"(p))
#define OPAQUE_R(p) asm volatile("" : "+r"(p))

template <int KK, int K1, int W0, int NW, int FIRST> struct XR {
  static __device__ __forceinline__ void run(float (&d)[16], const uint32_t (&w)[NW][4], uint32_t b16) {
    wgmma_n32_ra<(KK >> 2) * 4096 + (KK & 3) * 32, !FIRST>(d, w[W0 + KK], b16);
    XR<KK + 1, K1, W0, NW, 0>::run(d, w, b16);
  }
};
template <int K1, int W0, int NW, int FIRST> struct XR<K1, K1, W0, NW, FIRST> { static __device__ __forceinline__ void run(float (&)[16], const uint32_t (&)[NW][4], uint32_t) {} };
template <int KK, int K0, int K1, int FIRST> struct XS {
  static __device__ __forceinline__ void run(float (&d)[16], uint32_t a16, uint32_t b16) {
    wgmma_n32_ss_ta<(KK - K0) * 2048, (KK >> 2) * 4096 + (KK & 3) * 32, !FIRST>(d, a16, b16);
    XS<KK + 1, K0, K1, 0>::run(d, a16, b16);
  }
};
template <int K0, int K1, int FIRST> struct XS<K1, K0, K1, FIRST> { static __device__ __forceinline__ void run(float (&)[16], uint32_t, uint32_t) {} };

static __device__ bf16 g_h[8 * FF];
static __device__ unsigned int g_sbar;
struct SideParams { const bf16* x; const bf16* w_r; const bf16* w_gate; const bf16* w_up; const bf16* w_down; const bf16* gate_w; const bf16* Wo; };

static __device__ __forceinline__ void side_barrier(unsigned int target) {
  __syncthreads();
  if (threadIdx.x == 0) {
    __threadfence();
    atomicAdd(&g_sbar, 1u);
    int n = 0;
    while (*(volatile unsigned int*)&g_sbar < target) { if (++n > (1 << 22)) { g_err = 50; break; } }
    __threadfence();
  }
  __syncthreads();
}
static __device__ __forceinline__ uint4 ldg_nc(const void* p) { uint4 v;
  asm volatile("ld.global.nc.L1::no_allocate.v4.u32 {%0,%1,%2,%3}, [%4];" : "=r"(v.x), "=r"(v.y), "=r"(v.z), "=r"(v.w) : "l"(p)); return v; }
#define SPD 3
static __device__ __forceinline__ void l2pf(const void* p) { asm volatile("prefetch.global.L2 [%0];" :: "l"(p)); }
static __device__ __forceinline__ void mm8(float (&acc)[8][4], const bf16* W, const bf16* Wn, int ldw, int nk16, uint32_t abase, int lane) {
  const int g = lane >> 2, t = lane & 3;
  const bf16* wp = W + (size_t)(2 * t) * ldw + g * 8;
#pragma unroll 1
  for (int k = 0; k < nk16; k += 4) {
    {
      const int kp = k + 4 * SPD;
      const bf16* pf = kp < nk16 ? W + (size_t)(kp * 16) * ldw : Wn ? Wn + (size_t)((kp - nk16) * 16) * ldw : nullptr;
      if (pf) { l2pf(pf + (size_t)lane * ldw); l2pf(pf + (size_t)(lane + 32) * ldw); }
    }
    uint4 r[4][4];
#pragma unroll
    for (int u = 0; u < 4; u++) {
      const bf16* q = wp + (size_t)(k + u) * 16 * ldw;
      r[u][0] = ldg_nc(q); r[u][1] = ldg_nc(q + ldw); r[u][2] = ldg_nc(q + 8 * ldw); r[u][3] = ldg_nc(q + 9 * ldw);
    }
#pragma unroll
    for (int u = 0; u < 4; u++) {
      uint32_t a0, a2;
      asm volatile("ld.shared.u32 %0, [%1];" : "=r"(a0) : "r"(abase + (k + u) * 32));
      asm volatile("ld.shared.u32 %0, [%1];" : "=r"(a2) : "r"(abase + (k + u) * 32 + 16));
      const uint32_t* p0 = reinterpret_cast<const uint32_t*>(&r[u][0]); const uint32_t* p1 = reinterpret_cast<const uint32_t*>(&r[u][1]);
      const uint32_t* p2 = reinterpret_cast<const uint32_t*>(&r[u][2]); const uint32_t* p3 = reinterpret_cast<const uint32_t*>(&r[u][3]);
#pragma unroll
      for (int i = 0; i < 8; i++) {
        const uint32_t sel = (i & 1) ? 0x7632u : 0x5410u;
        mma4(acc[i], a0, 0u, a2, 0u, __byte_perm(p0[i >> 1], p1[i >> 1], sel), __byte_perm(p2[i >> 1], p3[i >> 1], sel));
      }
    }
  }
}
static __device__ __noinline__ void side_work(const SideParams& P, unsigned char* smem, int q) {
  const int tid = threadIdx.x, lane = tid & 31, warp = tid >> 5, g = lane >> 2, t = lane & 3;
  const uint32_t sb = smem_u32(smem);
  unsigned int* cand = reinterpret_cast<unsigned int*>(smem);
  bf16* xs = reinterpret_cast<bf16*>(smem + 1024);
  float* part = reinterpret_cast<float*>(smem + 65536);
  {
    for (int i = tid; i < 256; i += 384) *reinterpret_cast<uint4*>(smem + 1024 + i * 16) = ldg_nc((i < 128 ? P.gate_w : P.w_r - DM) + i * 8);
    __syncthreads();
#pragma unroll 1
    for (int it = warp; it < 64; it += 12) {
      const bf16* xp = P.x + (size_t)(q * 512 + (it >> 1) * 16 + g) * DM + (it & 1) * 512 + t * 8;
      for (int a = it == warp ? 0 : 1; a < 2 && it + 12 * a < 64; a++)
#pragma unroll
        for (int i = 0; i < 4; i++) l2pf(P.x + (size_t)(q * 512 + (it >> 1) * 16 + a * 96 + i * 4 + (lane >> 3)) * DM + (it & 1) * 512 + (lane & 7) * 64);
      uint4 lo[16], hi[16];
#pragma unroll
      for (int i = 0; i < 16; i++) { lo[i] = ldg_nc(xp + i * 32); hi[i] = ldg_nc(xp + 8 * DM + i * 32); }
      float sg[4] = {0.f, 0.f, 0.f, 0.f}, sr[4] = {0.f, 0.f, 0.f, 0.f};
#pragma unroll
      for (int i = 0; i < 16; i++) {
        const uint4 gw = lds128(sb + 1024 + (it & 1) * 1024 + i * 64 + t * 16), wr = lds128(sb + 3072 + (it & 1) * 1024 + i * 64 + t * 16);
        mma4(sr, lo[i].x, hi[i].x, lo[i].y, hi[i].y, wr.x, wr.y); mma4(sr, lo[i].z, hi[i].z, lo[i].w, hi[i].w, wr.z, wr.w);
        mma4(sg, mulb2(lo[i].x, gw.x), mulb2(hi[i].x, gw.x), mulb2(lo[i].y, gw.y), mulb2(hi[i].y, gw.y), 0x3F803F80u, 0x3F803F80u);
        mma4(sg, mulb2(lo[i].z, gw.z), mulb2(hi[i].z, gw.z), mulb2(lo[i].w, gw.w), mulb2(hi[i].w, gw.w), 0x3F803F80u, 0x3F803F80u);
      }
      if (t == 0) {
        float* pp = part + (it & 1) * 1024 + (it >> 1) * 16 + g;
        pp[0] = sg[0]; pp[8] = sg[2]; pp[512] = sr[0]; pp[520] = sr[2];
      }
    }
    __syncthreads();
    for (int i = tid; i < 512; i += 384) {
      g_gate[q * 512 + i] = rbf(1.f / (1.f + expf(-rbf(part[i] + part[1024 + i]))));
      g_r[q * 512 + i] = rbf(part[512 + i] + part[1536 + i]);
    }
  }
#define GU(u) (((u) % 28) / 14 ? P.w_up : P.w_gate) + (size_t)((u) / 28) * 512 * FF + q * 896 + ((u) % 14) * 64
  for (int i = lane; i < 64 * SPD; i += 32) l2pf(GU(warp) + (size_t)i * FF);
  side_barrier(4);
  {
    unsigned int key[8];
#pragma unroll
    for (int i = 0; i < 8; i++) {
      const int tok = (warp & 7) * 256 + i * 32 + lane;
      const uint32_t b = __float_as_uint(__ldcg(&g_r[tok]) + 0.f) >> 16;
      key[i] = (((b & 0x8000u) ? (~b & 0xffffu) : (b | 0x8000u)) << 16) | (uint32_t)(2047 - tok);
    }
    for (int pass = 0; pass < 2; pass++) {
      if (pass == 0 ? warp < 8 : warp == 0) {
        for (int c = 0; c < 8; c++) {
          const unsigned int m = __reduce_max_sync(~0u, max(max(max(key[0], key[1]), max(key[2], key[3])), max(max(key[4], key[5]), max(key[6], key[7]))));
#pragma unroll
          for (int i = 0; i < 8; i++) if (key[i] == m) key[i] = 0u;
          if (lane == 0) cand[pass ? 128 + c : warp * 8 + c] = m;
        }
      }
      __syncthreads();
      if (pass == 0 && warp == 0) {
#pragma unroll
        for (int i = 0; i < 8; i++) key[i] = i < 2 ? cand[i * 32 + lane] : 0u;
      }
    }
    if (q == 0 && tid < 8) g_idx[tid] = 2047 - (int)(cand[128 + tid] & 0xffffu);
    for (int i = tid; i < 1024; i += 384) {
      const int c = i >> 7, tok = 2047 - (int)(cand[128 + c] & 0xffffu);
      *reinterpret_cast<uint4*>(xs + c * (FF + 8) + (i & 127) * 8) = ldg_nc(P.x + (size_t)tok * DM + (i & 127) * 8);
    }
    __syncthreads();
  }
  const uint32_t abase = sb + 1024 + g * (FF + 8) * 2 + t * 4;
  for (int u = warp; u < 56; u += 12) {
    const int kh = u / 28, mat = (u % 28) / 14, cb = u % 14;
    float acc[8][4];
#pragma unroll
    for (int i = 0; i < 8; i++) acc[i][0] = acc[i][1] = acc[i][2] = acc[i][3] = 0.f;
    mm8(acc, GU(u), u + 12 < 56 ? GU(u + 12) : nullptr, FF, DM / 32, abase + kh * 1024, lane);
    float* pp = part + ((kh * 2 + mat) * 8 + g) * 896 + cb * 64 + 16 * t;
#pragma unroll
    for (int i = 0; i < 8; i++) { pp[i] = acc[i][0]; pp[8 + i] = acc[i][1]; }
  }
  for (int i = lane; i < 64 * SPD; i += 32) l2pf(P.w_down + (size_t)((warp >> 2) * 1216 + i) * DM + q * 256 + (warp & 3) * 64);
  __syncthreads();
  for (int i = tid; i < 8 * 896; i += 384) {
    const float ag = rbf(part[i] + part[16 * 896 + i]), au = rbf(part[8 * 896 + i] + part[24 * 896 + i]);
    g_h[(i / 896) * FF + q * 896 + i % 896] = __float2bfloat16(rbf(ag / (1.f + expf(-ag))) * au);
  }
  side_barrier(8);
  for (int i = tid; i < 8 * FF / 8; i += 384) {
    const int c = i / (FF / 8), o = i % (FF / 8);
    *reinterpret_cast<uint4*>(xs + c * (FF + 8) + o * 8) = __ldcg(reinterpret_cast<const uint4*>(g_h + c * FF + o * 8));
  }
  __syncthreads();
  {
    const int cb = warp & 3, kq = warp >> 2;
    float acc[8][4];
#pragma unroll
    for (int i = 0; i < 8; i++) acc[i][0] = acc[i][1] = acc[i][2] = acc[i][3] = 0.f;
    mm8(acc, P.w_down + (size_t)kq * 1216 * DM + q * 256 + cb * 64, nullptr, DM, kq == 2 ? 72 : 76, abase + kq * 1216 * 2, lane);
#pragma unroll
    for (int i = 0; i < 8; i++) { part[(kq * 8 + g) * 256 + cb * 64 + 16 * t + i] = acc[i][0]; part[(kq * 8 + g) * 256 + cb * 64 + 16 * t + 8 + i] = acc[i][1]; }
    __syncthreads();
    for (int i = tid; i < 2048; i += 384) {
      const int c = i >> 8, tok = 2047 - (int)(cand[128 + c] & 0xffffu);
      const float y = (part[i] + part[2048 + i]) + part[4096 + i];
      const float rs = rbf(1.f / (1.f + expf(-__ldcg(&g_r[tok]))));
      g_upd[c * DM + q * 256 + (i & 255)] = __float2bfloat16(rbf(y) * rs);
    }
  }
}
struct RecParams { const bf16* mem0; unsigned char* win; };
struct WMaps { CUtensorMap q, k, v; };
#define RLX 1
#define DLY_SIDE 16000
#define WSPL 1

#define DLY_S 120
#define DLY_V 200
#define DLY_M3 100
#define RF_FAT 208
#define RF_CTL 88
#define NCH 2
#define WPF 7
#define WRF 7
#define VPF 2
#define DLY_WO 850
#define XPF 4
#define DLY_FA 50
#define DLY_XL 30
#define NPROBE 3
#define BORD 2
#define BG 1
#define VI 1
#define DLY_VI 0
#define WNS -1
#define DLY_NW 50
#define ETW 1
#define KB 8
#define H16 1
#define DLY_N 30
#define F1C 2
#define KA 0
#define KEEP() do { float kd[4]; mma4z(kd, 0u, 0u, 0u, 0u, 0u, 0u); } while (0)
#define WKA 8
#define WPA 4
#define F0T 1
#define DLY_K 1064
#define DLY_KS 992
#define DLY_E 60
#define DLY_PF 10
#define DLY_F0 300
#define XXORD 1
#define DLY_PX 150
#define DLY_TB 700
#define ADD3(a, b, c) addb2(addb2(a, c), b)
#define STR2(x) #x
#define STR(x) STR2(x)

static __device__ __forceinline__ void cp16p(uint32_t dst, const void* src, uint32_t v) {
  asm volatile("{\n.reg .pred q;\nsetp.ne.u32 q, %2, 0;\n@q cp.async.cg.shared.global [%0], [%1], 16;\n}" :: "r"(dst), "l"(src), "r"(v) : "memory"); }
static __device__ __forceinline__ void red_bf2(void* p, uint32_t v) {
  asm volatile("red.relaxed.gpu.global.add.noftz.bf16x2 [%0], %1;" :: "l"(p), "r"(v) : "memory"); }
static __device__ __forceinline__ void red_bf2p(void* p, uint32_t v, uint32_t e) {
  asm volatile("{\n.reg .pred q;\nsetp.lt.u32 q, %2, 2;\n@q red.relaxed.gpu.global.add.noftz.bf16x2 [%0], %1;\n}" :: "l"(p), "r"(v), "r"(e) : "memory"); }
static __device__ __forceinline__ void red_bf2p4(void* p, uint32_t v, uint32_t e) {
  asm volatile("{\n.reg .pred q;\nsetp.lt.u32 q, %2, 4;\n@q red.relaxed.gpu.global.add.noftz.bf16x2 [%0], %1;\n}" :: "l"(p), "r"(v), "r"(e) : "memory"); }
static __device__ __forceinline__ void sts16(uint32_t a, uint32_t x) { asm volatile("{\n.reg .b16 h;\ncvt.u16.u32 h, %1;\nst.shared.u16 [%0], h;\n}" :: "r"(a), "r"(x) : "memory"); }
static __device__ __forceinline__ uint32_t cnt_word(uint32_t L) { return (L & 17u) | ((L & 6u) << 1) | ((L & 8u) >> 2); }
static __device__ __forceinline__ uint32_t cnt_line(uint32_t l) { return (l & 17u) | ((l & 12u) >> 1) | ((l & 2u) << 2); }
static __device__ __forceinline__ int m3_gather(uint32_t sb, const unsigned char* p3, const unsigned char* pd, int dq, uint32_t l16, uint32_t mc, int hf, int tf, int go) {
  const uint32_t md = l16 + (sb + SM_MEM + hf * 8192), dd = l16 + (sb + SM_RD + hf * 256), dc = (l16 >> 2) + (sb + SM_RD + hf * 256);
  {
    const unsigned char* p0f = p3 + tf * 4096; const unsigned char* p0n = p3 + (tf ^ 1) * 4096; const unsigned char* p1f = p0n + dq; const unsigned char* p1n = p0f + dq;
    uint32_t mf = md + tf * 2048, mn = md + (tf ^ 1) * 2048, far = l16 < 256u ? 1u + (((l16 >> 6) ^ (l16 >> 7) ^ tf) & 1u) : 0u;
    OPAQUE_L(p0f); OPAQUE_L(p0n); OPAQUE_L(p1f); OPAQUE_L(p1n); OPAQUE_R(mf); OPAQUE_R(mn); OPAQUE_R(far); FENCE();
    if (go) bar_sync(B_GO, 96);
#pragma unroll
    for (int i = 0; i < 4; i++) { cp16(mn + 4096 + i * 512, p1f + i * 1024); cp16(mf + i * 512, p0f + i * 1024); }
    cp16p(dd, pd, far & 1u);
    spin(DLY_N);
#pragma unroll
    for (int i = 0; i < 4; i++) { cp16(mf + 4096 + i * 512, p1n + i * 1024); cp16(mn + i * 512, p0n + i * 1024); }
    cp16p(dd, pd, far & 2u);
  }
  int n = 0;
  uint32_t d0, d1;
#pragma unroll 1
  for (;;) {
    asm volatile("cp.async.commit_group;\ncp.async.wait_group 0;" ::: "memory");
    __syncwarp();
    const uint32_t c0 = lds32(mc), c1 = lds32(mc + 4096);
    d0 = lds32(dc); d1 = lds32(dc + 128);
    if (!__any_sync(~0u, (x3(c0, c1, 0x42000000u) | x3(d0, d1, 0x42000000u)) >= 0x10000u) || ++n > SPIN_LIMIT) break;
    const int src = cnt_word(l16 >> 4);
    const uint32_t m0 = __ballot_sync(~0u, (__shfl_sync(~0u, c0, src) >> 16) != 0x4200u) >> (l16 >> 7), m1 = __ballot_sync(~0u, (__shfl_sync(~0u, c1, src) >> 16) != 0x4200u) >> (l16 >> 7);
    const uint32_t m2 = __ballot_sync(~0u, (d0 >> 16) != 0x4200u), m3 = __ballot_sync(~0u, (d1 >> 16) != 0x4200u);
#pragma unroll
    for (int i = 0; i < 8; i++) { cp16p(md + i * 512, p3 + i * 1024, m0 & (1u << (4 * i))); cp16p(md + 4096 + i * 512, p3 + dq + i * 1024, m1 & (1u << (4 * i))); }
    cp16p(dd, pd, l16 < 256u ? (((l16 & 128u) ? m3 : m2) >> ((l16 >> 2) & 28u)) & 15u : 0u);
  }
  sts16(mc + 2, d0); sts16(mc + 4098, d1);
  __syncwarp();
  if (l16 == 0) mbar_arrive(sb + SM_BAR + MB_MEM + hf * 8);
  return n;
}

__global__ void __cluster_dims__(2, 1, 1) __launch_bounds__(384, 1)
rec_kernel(const __grid_constant__ CUtensorMap tmx, const __grid_constant__ CUtensorMap tmw, const __grid_constant__ WMaps W, RecParams P, const __grid_constant__ SideParams SP) {
  extern __shared__ __align__(1024) unsigned char smem[];
  asm volatile("griddepcontrol.launch_dependents;");
  const uint32_t sb = smem_u32(smem);
  const int tid = threadIdx.x, lane = tid & 31, t128 = tid & 127;
  const int wg = __shfl_sync(~0u, tid >> 7, 0), wq = __shfl_sync(~0u, (tid >> 5) & 3, 0);
  const int r = blockIdx.x & 1, pp = blockIdx.x >> 1;
  const int mi = lane >> 3, r8 = lane & 7;

  if (tid == 0) {
    mbar_init(sb + SM_BAR + MB_F, 1); mbar_init(sb + SM_BAR + MB_F + 8, 1); mbar_init(sb + SM_BAR + MB_XE0, 2); mbar_init(sb + SM_BAR + MB_XE1, 2); mbar_init(sb + SM_BAR + MB_INIT, 2);
    mbar_init(sb + SM_BAR + MB_MEM, 1); mbar_init(sb + SM_BAR + MB_MEM + 8, 1); mbar_init(sb + SM_BAR + MB_W, 1); mbar_init(sb + SM_BAR + MB_W + 8, 1);
    mbar_init(sb + SM_BAR + MB_XF, 8); mbar_init(sb + SM_BAR + MB_X0, 1); mbar_init(sb + SM_BAR + MB_WO, 1); mbar_init(sb + SM_BAR + MB_VR, 5);
    asm volatile("fence.mbarrier_init.release.cluster;" ::: "memory");
  }
  if (tid == 32) {
    asm volatile("prefetch.tensormap [%0];" :: "l"(&W.q) : "memory"); asm volatile("prefetch.tensormap [%0];" :: "l"(&W.k) : "memory");
    asm volatile("prefetch.tensormap [%0];" :: "l"(&W.v) : "memory"); asm volatile("prefetch.tensormap [%0];" :: "l"(&tmx) : "memory");
  }
  if (tid >= 256 && tid < 320) {
    unsigned char* pl = P.win + r * W_2 + (W_UP | (1u << 19) | ((pp >> 5) << 14)) + (pp & 31) * 128 + wq * 4096;
    stg_r1(pl + lane * 4, 0u);
    uint32_t best = 1u << 30, acc = 0;
#pragma unroll 1
    for (int rep = 0; rep < NPROBE; rep++) {
      uint32_t v = 0, t1; const uint32_t t0 = clk32();
      if (lane == 0) asm volatile("atom.relaxed.gpu.global.add.u32 %0, [%1], 2;" : "=r"(v) : "l"(pl + acc) : "memory");
      acc = v >> 31;
      asm volatile("{\n.reg .u32 x;\nadd.u32 x, %1, 0;\nmov.u32 %0, %%clock;\n}" : "=r"(t1) : "r"(acc));
      best = min(best, t1 - t0 + acc);
    }
    if (lane == 0) sts32(sb + SM_SIDE + wq * 4, best);
    bar_sync(B_P, 64);
    if (wq == 0) {
      const uint2 bt = lds64(sb + SM_SIDE);
      if (lane < 8 && (r == 0 || pp == 0)) stg_r1(&g_side[(r ? 66 : pp) * 32 + lane], 2u | (bt.x < bt.y ? 1u : 0u));
      spin(DLY_TB);
      uint32_t a, b, c; int n = 0;
#pragma unroll 1
      do {
        a = ldg_r1(&g_side[lane * 32]); b = ldg_r1(&g_side[(32 + lane) * 32]); c = ldg_r1(&g_side[(64 + min(lane, 2)) * 32]);
      } while (!__all_sync(~0u, a & b & c & 2u) && ++n < SPIN_LIMIT);
      a = __ballot_sync(~0u, a & 1u); b = __ballot_sync(~0u, b & 1u); c = __ballot_sync(~0u, c & 1u);
      const uint32_t pol2 = (a ^ (c >> 2)) & 1u;
      c &= 3u;
      const unsigned long long ab = ((unsigned long long)b << 32) | a;
      const int sd = pp < 64 ? (int)(ab >> pp) & 1 : (int)(c >> (pp - 64)) & 1;
      const int n1 = __popcll(ab) + __popc(c), n0 = 66 - n1;
      const int below1 = pp < 64 ? __popcll(ab & ((1ull << pp) - 1)) : __popcll(ab) + (pp == 65 ? (int)(c & 1u) : 0);
      const int rk = sd ? below1 : pp - below1;
      const int k0 = (n0 & 1) ? n0 - 1 : n0 >= n1 ? n0 - 2 : n0, k1 = 64 - k0;
      const int role = rk >= (sd ? k1 : k0) ? 64 + ((n0 & 1) ? sd : rk - (sd ? k1 : k0)) : sd ? k0 + rk : rk;
      __syncwarp();
      if (lane == 0) sts128(sb + SM_SIDE, 2 * k0, 0u, pol2, role * 2 + r);
    }
  }
  __syncthreads();
  const int cta = __shfl_sync(~0u, (int)lds32(sb + SM_SIDE + 12), 0), h = cta >> 2, j = cta & 3, p = j >> 1;
  if (cta >= NCTA) {
    spin(DLY_SIDE);
    side_work(SP, smem, cta - NCTA);
    return;
  }
  asm volatile("barrier.cluster.arrive.relaxed.aligned;" ::: "memory");
#define WLOAD(i0, i1) _Pragma("unroll 1") for (int u = i0; u < i1; u++) {        \
    const int g2 = u >> 2, i = u & 3, k = g2 * 512 + ((i * 128 + r * 256) & 511); \
    const uint32_t mb = sb + SM_BAR + MB_W + g2 * 8; \
    tma_load_2d(sb + g2 * 65536 + i * 8192, &W.q, h * DH + j * 32, k, mb); \
    tma_load_2d(sb + g2 * 65536 + 32768 + i * 8192, &W.k, h * DH + j * 32, k, mb); \
    if (i < 2) tma_load_2d(sb + (i ? SM_WVS : SM_VST) + g2 * 16384, &W.v, h * DH + p * 64, k, mb); }
  if (tid == 288) {
    mbar_expect_tx(sb + SM_BAR + MB_X0, 32768);
#pragma unroll 1
    for (int i = 0; i < 4; i++)
      asm volatile("cp.async.bulk.tensor.3d.shared::cluster.global.mbarrier::complete_tx::bytes [%0], [%1, {%3, %3, %4}], [%2];"
                   :: "r"(sb + SM_MEM + i * 8192), "l"(&tmx), "r"(sb + SM_BAR + MB_X0), "r"(0), "r"(i * 2) : "memory");
    mbar_expect_tx(sb + SM_BAR + MB_W, 98304); mbar_expect_tx(sb + SM_BAR + MB_W + 8, 98304);
    WLOAD(0, 4 + WSPL);
  }
  __syncwarp();
  asm volatile("barrier.cluster.wait.acquire.aligned;" ::: "memory");
#define SIDES() const uint4 sm2 = lds128(sb + SM_SIDE); const int nlo = sm2.x; const uint32_t me = cta >= nlo

#define XLOAD(t, sg) do { tma_load_mc(sb + SM_X + ((t) * 8 + r * 4) * 4096, &tmx, (sg) * SEG, (t) * 8 + r * 4, sb + SM_BAR + MB_F + (t) * 8); \
                          tma_load_mc(sb + SM_X + ((t) * 8 + r * 4 + 2) * 4096, &tmx, (sg) * SEG, (t) * 8 + r * 4 + 2, sb + SM_BAR + MB_F + (t) * 8); } while (0)
  if (wg < 2) {
    asm volatile("setmaxnreg.inc.sync.aligned.u32 " STR(RF_FAT) ";");
    uint32_t w[32][4], wv[8][4];
    uint32_t lm = ((mi >> 1) * 8 + r8) * 128 + (((wq * 2 + (mi & 1)) ^ r8) << 4), l16 = lane * 16;
    lm = __shfl_sync(~0u, lm, lane); l16 = __shfl_sync(~0u, l16, lane);
    mbar_wait(sb + SM_BAR + MB_W + wg * 8, 0);
    {
      const uint32_t lq0 = sb + wg * 65536 + (wq >> 1) * 32768 + ((mi >> 1) * 8 + r8) * 64 + ((((wq & 1) * 2 + (mi & 1)) ^ (r8 >> 1)) << 4);
#pragma unroll
      for (int kk = 0; kk < 32; kk++) ldmatrix_x4_trans(w[kk], lq0 + kk * 1024);
    }
#pragma unroll
    for (int kk = 0; kk < 8; kk++) ldmatrix_x4_trans(wv[kk], sb + SM_VST + wg * 16384 + kk * 2048 + lm);
    if (wg == 0) bar_sync(B_V, 160);
    else bar_arrive(B_P, 224);
    const int w8 = wg * 4 + wq;
    const int near = __shfl_sync(~0u, (cta >= (int)lds32(sb + SM_SIDE) ? 0 : 1) ^ r ^ wg, 0);
    const uint32_t xb16 = (((sb + SM_X + wg * 32768 + r * 16384) & 0x3FFFF) >> 4) | (1u << 16), xh16 = xb16 ^ 1024u;
    const uint32_t rsb = mapa(sb, r ^ 1);
    const uint32_t va16 = (((sb + SM_WVS + wg * 16384) & 0x3FFFF) >> 4) | (64u << 16);
#define MT (l16 + (sb + SM_MEM + wg * 8192))
#define WA (lm + (sb + SM_WVS + wg * 16384))
#define WOF(f) (lm + (sb + SM_WOS + wg * 32768 + ((f) & 1) * 16384 + ((f) >> 1) * 2048))
#define TH(base) (l16 + (sb + (base) + w8 * 512))
#define TQ(base) (l16 + (sb + (base) + wq * 512))
#define DUMP(base) _Pragma("unroll") for (int n = 0; n < 4; n++) sts128f(TQ((base) + n * 2048), d[4 * n], d[4 * n + 1], d[4 * n + 2], d[4 * n + 3])
#define INIT(base) _Pragma("unroll") for (int n = 0; n < 4; n++) { const float4 t = lds128f(TQ((base) + n * 2048)); d[4 * n] = t.x; d[4 * n + 1] = t.y; d[4 * n + 2] = t.z; d[4 * n + 3] = t.w; }
#define XQK(first, b0, b1) do { wg_fence(); XR<0, 16, 0, 32, first>::run(d, w, b0); XR<0, 16, 16, 32, 0>::run(d, w, b1); wg_commit(); wg_wait0(); } while (0)
#define XVS(first, b0) do { wg_fence(); XS<8, 8, 16, first>::run(d, va16, b0); XR<0, 8, 0, 8, 0>::run(d, wv, b0); wg_commit(); wg_wait0(); } while (0)
#define XVR(first, b0) do { wg_fence(); XR<0, 8, 0, 8, first>::run(d, wv, b0); XS<8, 8, 16, 0>::run(d, va16, b0); wg_commit(); wg_wait0(); } while (0)
#define XREL(mb) do { if (wq == 0 && l16 == 0) { mbar_arrive_cluster_rlx(rsb + SM_BAR + (mb)); mbar_arrive(sb + SM_BAR + (mb)); } } while (0)
#define XFOUT() do { \
          _Pragma("unroll") for (int hf = 0; hf < 2; hf++) \
            stsm4t(l16 + (sb + SM_XF + (wq * 2 + hf) * 512), pack_bf16(d[8 * hf], d[8 * hf + 1]), pack_bf16(d[8 * hf + 2], d[8 * hf + 3]), \
                   pack_bf16(d[8 * hf + 4], d[8 * hf + 5]), pack_bf16(d[8 * hf + 6], d[8 * hf + 7])); \
          __syncwarp(); \
          if (l16 < 32) mbar_arrive(sb + SM_BAR + MB_XF); } while (0)
#define ADDIN(base) _Pragma("unroll") for (int n = 0; n < 4; n++) { const float4 t = lds128f(TQ((base) + n * 2048)); d[4 * n] += t.x; d[4 * n + 1] += t.y; d[4 * n + 2] += t.z; d[4 * n + 3] += t.w; }
    if (wg == 0) {
      float d[16];
      const uint32_t x0 = (((sb + SM_MEM + r * 16384) & 0x3FFFF) >> 4) | (1u << 16), x1 = (((sb + SM_MEM + (r ^ 1) * 16384) & 0x3FFFF) >> 4) | (1u << 16);
      mbar_wait(sb + SM_BAR + MB_X0, 0);
      XQK(1, x0, x1);
      DUMP(SM_CQ);
      XVS(1, x0);
      bar_sync(B_CQ, 256);
      DUMP(SM_CV);
      bar_sync(B_X2, 384);
    } else {
      float d[16];
      bar_sync(B_CQ, 256);
      INIT(SM_CQ);
      bar_sync(B_X2, 384);
      mbar_wait(sb + SM_BAR + MB_F + 8, 0);
      XQK(0, xb16, xh16);
      XFOUT();
    }
    uint32_t f0ok = 0;
    for (int s = 0;; s++) {
      OPAQUE_R(lm); OPAQUE_R(l16);
      if (wg || s < NSEG - 1) {
        float d[16];
        const uint32_t cv = ((s ^ wg) & 1) ? SM_CV : SM_CW;
        if (!wg && !f0ok) mbar_wait(sb + SM_BAR + MB_F, s & 1);
        TSP(9, 1);
        if (BORD == 2) XVR(1, xb16); else XVS(1, xb16);
        OPAQUE_R(l16);
        if (wg == 0) {
          DUMP(cv);
          if (KB) { wg_fence(); XR<0, KB, 0, 32, 1>::run(d, w, xb16); wg_commit(); wg_wait0(); OPAQUE_R(l16); DUMP(SM_CQ); }
          TSP(5, 1);
        } else {
          XREL(MB_XE1);
          ADDIN(cv);
          uint32_t q[4], o[4];
#pragma unroll
          for (int i = 0; i < 4; i++) { const uint32_t a = pack_bf16(d[2 * i], d[2 * i + 1]), b = pack_bf16(d[8 + 2 * i], d[9 + 2 * i]); q[i] = r ? b : a; o[i] = r ? a : b; }
          st_async4(l16 + (rsb + SM_VR + wq * 512), u2f(o[0]), u2f(o[1]), u2f(o[2]), u2f(o[3]), rsb + SM_BAR + MB_VR);
          sts128(TQ(SM_VL), q[0], q[1], q[2], q[3]);
          __syncwarp();
          if (l16 == 0) mbar_arrive(sb + SM_BAR + MB_VR);
          TSP(28, 5);
        }
      }
      OPAQUE_R(lm); OPAQUE_R(l16);
      {
        uint32_t sa[4][4];
#pragma unroll
        for (int i = 0; i < VPF; i++) ldmatrix_x4_trans(sa[i], WA + i * 2048);
        float a[NCH][4], v[2][4]; uint4 c[4];
        FENCE();
        mbar_wait(sb + SM_BAR + MB_MEM + wg * 8, s & 1);
        TSF(0, 1);
        TSF(21, 5);
#define QP(i) ((i) >= 12 ? (i) - 8 : (i) % 3 == 1 ? (i) / 3 : 8 + (i) - ((i) + 2) / 3)
#pragma unroll
        for (int i = 0; i < 3; i++) c[i] = ldsm4t(MT + QP(i) * 512);
#pragma unroll
        for (int i = 0; i < 16; i++) {
          if (i + 3 < 16) c[(i + 3) & 3] = ldsm4t(MT + QP(i + 3) * 512);
          if (2 * i < NCH) mma4z(a[2 * i], w[2 * QP(i)][0], w[2 * QP(i)][1], w[2 * QP(i)][2], w[2 * QP(i)][3], c[i & 3].x, c[i & 3].y);
          else mma_16816(a[(2 * i) % NCH], w[2 * QP(i)], c[i & 3].x, c[i & 3].y);
          if (2 * i + 1 < NCH) mma4z(a[2 * i + 1], w[2 * QP(i) + 1][0], w[2 * QP(i) + 1][1], w[2 * QP(i) + 1][2], w[2 * QP(i) + 1][3], c[i & 3].z, c[i & 3].w);
          else mma_16816(a[(2 * i + 1) % NCH], w[2 * QP(i) + 1], c[i & 3].z, c[i & 3].w);
          if (VI && QP(i) == 0) {
            mma4z(v[0], wv[0][0], wv[0][1], wv[0][2], wv[0][3], c[i & 3].x, c[i & 3].y);
            mma4z(v[1], wv[1][0], wv[1][1], wv[1][2], wv[1][3], c[i & 3].z, c[i & 3].w);
          } else if (VI && QP(i) < 4) {
            mma_16816(v[0], wv[2 * (QP(i) & 3)], c[i & 3].x, c[i & 3].y);
            mma_16816(v[1], wv[2 * (QP(i) & 3) + 1], c[i & 3].z, c[i & 3].w);
          }
          FENCE();
        }
        {
          const uint32_t qa = (((l16 & 0x30u) << 3) | ((l16 & 0x10u) << 2) | ((l16 >> 3) & 0x30u) | ((l16 >> 4) & 4u)) + (sb + SM_QKP + w8 * 512);
#pragma unroll
          for (int i = 0; i < 4; i++) {
            const float t = NCH == 4 ? (a[0][i] + a[1][i]) + (a[2 % NCH][i] + a[3 % NCH][i]) : NCH == 3 ? (a[0][i] + a[1][i]) + a[2 % NCH][i] : a[0][i] + a[1][i];
            sts32((qa ^ ((i & 1) << 6)) + (i >> 1) * 8, __float_as_uint(t));
          }
        }
        bar_arrive(B_QK, 288);
        bar_arrive(B_QK1, 288);
        FENCE();
        spin(DLY_VI);
#pragma unroll
        for (int i = VPF; i < 4; i++) ldmatrix_x4_trans(sa[i], WA + i * 2048);
        FENCE();
#pragma unroll
        for (int i = 0; i < 4; i++) {
          mma_16816(v[0], sa[(2 * i) & 3], c[i].x, c[i].y);
          mma_16816(v[1], sa[(2 * i + 1) & 3], c[i].z, c[i].w);
          if (i < 2) { ldmatrix_x4_trans(sa[2 * i], WA + (4 + 2 * i) * 2048); ldmatrix_x4_trans(sa[2 * i + 1], WA + (5 + 2 * i) * 2048); }
          FENCE();
        }
        sts128f(TH(SM_VP), v[0][0] + v[1][0], v[0][1] + v[1][1], v[0][2] + v[1][2], v[0][3] + v[1][3]);
        bar_arrive(B_V, 320);
        TSF(24, 5);
      }
      if (s == NSEG - 1) break;
      if (s == 0) mbar_wait(sb + SM_BAR + MB_WO, 0);
      OPAQUE_R(lm); OPAQUE_R(l16);
      {
        uint32_t wo[WPF][4];
        {
          float d[16];
          if (wg) mbar_wait(sb + SM_BAR + MB_F + 8, (s + 1) & 1);
          if (KB && wg == 0) {
            INIT(SM_CQ);
            bar_sync(B_PUB, 320);
            wg_fence();
            XR<KB, 16, 0, 32, 0>::run(d, w, xb16); XR<0, 16, 16, 32, 0>::run(d, w, xh16);
            wg_commit(); wg_wait0();
#pragma unroll
            for (int f = 0; f < WPA; f++) ldmatrix_x4_trans(wo[f], WOF(f));
          } else {
          bar_sync(B_PUB, 320);
          wg_fence();
          XR<0, WKA, 0, 32, 1>::run(d, w, xb16);
#pragma unroll
          for (int f = 0; f < WPA; f++) ldmatrix_x4_trans(wo[f], WOF(f));
          XR<WKA, 16, 0, 32, 0>::run(d, w, xb16); XR<0, 16, 16, 32, 0>::run(d, w, xh16);
          wg_commit(); wg_wait0();
          }
          TSF(31, 5); TSF(13, 1);
          OPAQUE_R(l16);
#define XHALF(g) do { \
            _Pragma("unroll") for (int n = 0; n < 2; n++) sts128f(TQ(SM_CQ + ((g) * 2 + n) * 2048), d[8 - 8 * (g) + 4 * n], d[9 - 8 * (g) + 4 * n], d[10 - 8 * (g) + 4 * n], d[11 - 8 * (g) + 4 * n]); \
            bar_sync(B_CQ, 256); \
            const float4 t0 = lds128f(TQ(SM_CQ + (2 - 2 * (g)) * 2048)), t1 = lds128f(TQ(SM_CQ + (3 - 2 * (g)) * 2048)); \
            stsm4t(l16 + (sb + SM_XF + (wq * 2 + (g)) * 512), pack_bf16(d[8 * (g)] + t0.x, d[8 * (g) + 1] + t0.y), pack_bf16(d[8 * (g) + 2] + t0.z, d[8 * (g) + 3] + t0.w), \
                   pack_bf16(d[8 * (g) + 4] + t1.x, d[8 * (g) + 5] + t1.y), pack_bf16(d[8 * (g) + 6] + t1.z, d[8 * (g) + 7] + t1.w)); } while (0)
          if (wg == 0) { XREL(MB_XE0); XHALF(0); } else XHALF(1);
          __syncwarp();
          if (l16 == 0) mbar_arrive(sb + SM_BAR + MB_XF);
          TSF(3, 5);
        }
#pragma unroll
        for (int f = WPA; f < WPF; f++) ldmatrix_x4_trans(wo[f], WOF(f));
        unsigned char* pa = P.win + (w_ar(s) + (j * 32 + wg * 16 + wq * 2) * 256 + (l16 >> 2));
        uint32_t ce = (l16 >> 4) - 4 * w8;
        OPAQUE_L(pa); OPAQUE_R(ce);
        FENCE();
        bar_sync(B_O, 320);
        if (WNS < 0 && near) spin(DLY_NW);
        uint4 ob[2];
        ob[0] = ldsm4(l16 + (sb + SM_OF)); ob[1] = ldsm4(l16 + (sb + SM_OF + 512));
        float acc[2][4];
#pragma unroll
        for (int f = 0; f < 16; f++) {
          const int ks = f >> 1;
          const uint32_t b0 = (ks & 1) ? ob[(ks >> 1) & 1].z : ob[(ks >> 1) & 1].x, b1 = (ks & 1) ? ob[(ks >> 1) & 1].w : ob[(ks >> 1) & 1].y;
          if (f < 2) mma4z(acc[f], wo[f][0], wo[f][1], wo[f][2], wo[f][3], b0, b1);
          else mma_16816(acc[f % 2], wo[f < WPF ? f : 2 + (f - WPF) % (WPF - 2)], b0, b1);
          if (f - 1 >= 2 && f - 1 + (WPF - 2) < 16) {
            const int nf = f - 1 + (WPF - 2);
            ldmatrix_x4_trans(wo[2 + (nf - WPF) % (WPF - 2)], WOF(nf));
          }
          if (f == 4 || f == 8) ob[((f >> 2) - 1) & 1] = ldsm4(l16 + (sb + SM_OF + (1 + (f >> 2)) * 512));
          if (f == WNS && near) spin(DLY_NW);
          FENCE();
        }
        if (F0T) f0ok = mbar_test(sb + SM_BAR + MB_F, (s + 1) & 1);
        if (near) bar_sync(B_CV, 256);
        FENCE();
        red_bf2(pa, pack_bf16(acc[0][0], ce == 0 ? 1.f : acc[0][1])); red_bf2(pa + 256, pack_bf16(acc[0][2], ce == 1 ? 1.f : acc[0][3]));
        red_bf2(pa + 2048, pack_bf16(acc[1][0], ce == 2 ? 1.f : acc[1][1])); red_bf2(pa + 2304, pack_bf16(acc[1][2], ce == 3 ? 1.f : acc[1][3]));
        red_bf2p4(pa + 128, pack_bf16(ce == 0 ? acc[0][1] : ce == 1 ? acc[0][3] : ce == 2 ? acc[1][1] : acc[1][3], 1.f), ce);
        TSF(4, 1);
        TSF(2, 6);
        bar_arrive(B_M2, 288);
        if (!near) bar_sync(B_CV, 256);
      }
    }
  } else {
    asm volatile("setmaxnreg.dec.sync.aligned.u32 " STR(RF_CTL) ";");
    const int g = lane >> 2, tq = lane & 3;
    if (wq == 0) {
      if (lane < 12) asm volatile("prefetch.global.L2 [%0];" :: "l"(SP.x + (size_t)(cta * 12 + lane) * 64));
      __syncwarp();
      {
        SIDES();
        const uint32_t o[6] = {w_blk(w_h1(cta), me), w_blk(w_h1(cta) ^ H1_V, me), w_blk(w_mvx(cta, 0), me ^ sm2.z), w_blk(w_mvx(cta, 1), me ^ sm2.z),
                               w_blk(w_mxa(cta, 0), me ^ sm2.z), w_blk(w_mxa(cta, 1), me ^ sm2.z)};
#pragma unroll
        for (int i = 0; i < 24; i++) stg_r4(P.win + (o[i >> 2] + (i & 3) * 512 + lane * 16), 0u, 0u, 0u, 0u);
#pragma unroll
        for (int i = 0; i < 6; i++) stg_r1(P.win + (w_ar(i >> 1) + cta * 256 + (i & 1) * 128 + lane * 4), 0u);
        __threadfence();
        __syncwarp();
      }
      {
        const uint32_t wv = movm(*reinterpret_cast<const uint32_t*>(P.mem0 + g * DM + cta * 8 + tq * 2));
        const bool sp = lane == cnt_word(cta & 31);
        stg_r1(P.win + (w_ar(-1) + cta * 256 + lane * 4), sp ? (wv & 0xffffu) | 0x42000000u : wv);
        if (sp) stg_r1(P.win + (w_ar(-1) + (cta & ~9) * 256 + 128 + lane * 4), (wv >> 16) | 0x42000000u);
      }
      bar_sync(B_V, 160);
      if (lane == 0) {
        fence_async_smem(); mbar_arrive_cluster_rlx(mapa(sb + SM_BAR + MB_INIT, 0)); mbar_arrive_cluster_rlx(mapa(sb + SM_BAR + MB_INIT, 1));
        mbar_wait(sb + SM_BAR + MB_INIT, 0);
        mbar_expect_tx(sb + SM_BAR + MB_F, 32768);
        mbar_expect_tx(sb + SM_BAR + MB_F + 8, 32768);
        XLOAD(1, 0); XLOAD(0, 1);
        WLOAD(4 + WSPL, 8);
      }
      __syncwarp();
      bar_sync(B_X2, 384);
    } else {
      bar_sync(B_P, 224);
      if (t128 == 96) {
        fence_async_smem();
        mbar_expect_tx(sb + SM_BAR + MB_WO, 65536);
        for (int i = 0; i < 8; i++) tma_load_2d(sb + SM_WOS + i * 8192, &tmw, j * 256 + (i >> 1) * 64, h * DH + (i & 1) * 64, sb + SM_BAR + MB_WO);
      }
      __syncwarp();
      bar_sync(B_X2, 384);
    }
    SIDES();
    uint32_t l16 = __shfl_sync(~0u, lane * 16, lane);
    const uint32_t me2 = me ^ sm2.z;
    const float sc = 0.08838834764831845f * 1.4426950408889634f;
    uint32_t ls = l16 + sb;
#define PV4(va, vm, dst) do { \
        float o[4][4], z[4]; \
        FENCE(); \
        mma4z(z, 0x3F803F80u, 0x3F803F80u, 0x3F803F80u, 0x3F803F80u, p0.x, p0.y); \
        _Pragma("unroll") for (int t = 0; t < 4; t++) mma4z(o[t], va[2 * t].x, va[2 * t].y, va[2 * t].z, va[2 * t].w, p0.x, p0.y); \
        FENCE(); \
        mma4(z, 0x3F803F80u, 0x3F803F80u, 0x3F803F80u, 0x3F803F80u, p0.z, p0.w); \
        _Pragma("unroll") for (int t = 0; t < 2; t++) mma4(o[t], va[2 * t + 1].x, va[2 * t + 1].y, va[2 * t + 1].z, va[2 * t + 1].w, p0.z, p0.w); \
        FENCE(); \
        mma_1688(z, 0x3F803F80u, 0x3F803F80u, p2); \
        _Pragma("unroll") for (int t = 2; t < 4; t++) mma4(o[t], va[2 * t + 1].x, va[2 * t + 1].y, va[2 * t + 1].z, va[2 * t + 1].w, p0.z, p0.w); \
        mma_1688(o[0], vm[0].x, vm[0].y, p2); mma_1688(o[1], vm[0].z, vm[0].w, p2); mma_1688(o[2], vm[1].x, vm[1].y, p2); mma_1688(o[3], vm[1].z, vm[1].w, p2); \
        const float i0 = rcpf(z[0]), i1 = rcpf(z[1]); \
        _Pragma("unroll") for (int u = 0; u < 2; u++) \
          stsm4t(ls + (dst) + u * 1024, pack_bf16(o[2 * u][0] * i0, o[2 * u][1] * i1), pack_bf16(o[2 * u][2] * i0, o[2 * u][3] * i1), \
                 pack_bf16(o[2 * u + 1][0] * i0, o[2 * u + 1][1] * i1), pack_bf16(o[2 * u + 1][2] * i0, o[2 * u + 1][3] * i1)); } while (0)
#define SOFTMAX(pf, f) do { \
        float mx = fmaxf(fmaxf(fmaxf(sx[2], sx[3]), fmaxf(sx[4], sx[5])), fmaxf(fmaxf(sx[6], sx[7]), fmaxf(sx[8], sx[9]))); \
        mx = fmaxf(mx, fmaxf(sx[0], sx[1])); \
        mx = fmaxf(mx, __shfl_xor_sync(~0u, mx, 1)); \
        mx = fmaxf(mx, __shfl_xor_sync(~0u, mx, 2)); \
        mx *= -(f); \
        _Pragma("unroll") for (int i = 0; i < 10; i++) sx[i] = ex2(fmaf(sx[i], f, mx)); \
        sts128(ls + (pf), pack_bf16(sx[2], sx[3]), pack_bf16(sx[4], sx[5]), pack_bf16(sx[6], sx[7]), pack_bf16(sx[8], sx[9])); \
        sts32(ls - l12 + (pf) + 512, pack_bf16(sx[0], sx[1])); } while (0)
    const uint32_t lq = (l16 ^ ((l16 >> 1) & 64u)) + sb, l12 = (l16 >> 2) * 3;
#define ETA(k, first) do { if (l16 < 32) { unsigned char* pt = P.win + (w_ar(s) + 384 + (cta >> 5) * 8192 + ((cta >> 4) & 1) * 2048 + l16 * 256); \
          asm volatile("red.relaxed.gpu.global.max.u32 [%0+4], %1;" :: "l"(pt), "r"(gt32() + (k)) : "memory"); \
          if (first) asm volatile("red.relaxed.gpu.global.add.u32 [%0], 1;" :: "l"(pt) : "memory"); } } while (0)
    if (wq == 1) {
      const uint32_t xin = w_blk(w_mxa(cta, 0), me2) + l16;
#define F1LOAD() \
          if (F1C ? s == 0 : s < NSEG - 1) {        \
            mbar_wait(sb + SM_BAR + MB_XE1, s & 1); \
            if (l16 == 0) mbar_expect_tx(sb + SM_BAR + MB_F + 8, 32768); \
            mbar_wait(sb + SM_BAR + MB_MEM, s & 1); \
            mbar_wait(sb + SM_BAR + MB_MEM + 8, s & 1); \
            spin(DLY_FA); \
            if (l16 == 0) XLOAD(1, s + 1); \
            __syncwarp(); \
            TS(27); \
          }
      for (int s = 0; s < NSEG; s++) {
        const uint32_t t2 = ((s >> 1) & 1) ^ 1;
        mbar_wait(sb + SM_BAR + MB_XF, s & 1);
        {
        uint4 kx[4], qx[4];
#pragma unroll
        for (int i = 0; i < 4; i++) { kx[i] = ldsm4(ls + (SM_XF + (4 + i) * 512)); qx[i] = ldsm4(ls + (SM_XF + i * 512)); }
        const uint32_t db = w_blk(w_mxa(h * 4, s), me2) + l16 - 640;
#pragma unroll
        for (int mt = 0; mt < 2; mt++) {
          const uint4 q0 = qx[mt], q1 = qx[2 + mt];
          float S[4][4];
          mma4z(S[0], q0.x, q0.z, q0.y, q0.w, kx[0].x, kx[0].y); mma4z(S[1], q0.x, q0.z, q0.y, q0.w, kx[0].z, kx[0].w);
          mma4z(S[2], q0.x, q0.z, q0.y, q0.w, kx[1].x, kx[1].y); mma4z(S[3], q0.x, q0.z, q0.y, q0.w, kx[1].z, kx[1].w);
          mma4(S[0], q1.x, q1.z, q1.y, q1.w, kx[2].x, kx[2].y); mma4(S[1], q1.x, q1.z, q1.y, q1.w, kx[2].z, kx[2].w);
          mma4(S[2], q1.x, q1.z, q1.y, q1.w, kx[3].x, kx[3].y); mma4(S[3], q1.x, q1.z, q1.y, q1.w, kx[3].z, kx[3].w);
#pragma unroll
          for (int u = 0; u < 2; u++) {
            const uint32_t m0 = tagw(pack_f16(S[0][2 * u] * sc, S[0][2 * u + 1] * sc), t2), m1 = pack_f16(S[1][2 * u] * sc, S[1][2 * u + 1] * sc),
                           m2 = pack_f16(S[2][2 * u] * sc, S[2][2 * u + 1] * sc), m3 = pack_f16(S[3][2 * u] * sc, S[3][2 * u + 1] * sc);
            const int e = (2 * mt + u) ^ j;
            if (e) stg_r4(P.win + (db + mt * 16384 + u * 2048 + e * 640), m0, m1, m2, m3);
            else sts128(ls + SM_XS, m0, m1, m2, m3);
          }
        }
        TS(15);
        {
          if (l16 == 0) mbar_expect_tx(sb + SM_BAR + MB_VR, 2048);
          mbar_wait(sb + SM_BAR + MB_VR, s & 1);
          unsigned char* d = P.win + (w_blk(w_mvx(cta, s), me2) + l16);
#pragma unroll
          for (int t = 0; t < 4; t++) {
            const uint4 a0 = lds128(ls + (SM_VL + t * 512)), a1 = lds128(ls + (SM_VR + t * 512));
            stg_r4(d + t * 512, tagw(addb2(a0.x, a1.x), t2), addb2(a0.y, a1.y), addb2(a0.z, a1.z), addb2(a0.w, a1.w));
          }
          TS(23);
        }
        F1LOAD();
        float sx[10];
        const unsigned char* pa = P.win + (xin + ((s & 1) << 20));
        {
          uint4 xv[3]; int n = 0;
#pragma unroll 1
          do {
#pragma unroll
            for (int i = 0; i < 3; i++) xv[i] = ldg_r4(pa + i * 640);
          } while (__any_sync(~0u, (x3(xv[0].x, xv[1].x, t2) | (xv[2].x ^ t2)) & 1u) && ++n < SPIN_LIMIT);
          const uint4 v3 = lds128(ls + SM_XS);
          sum_h4(sx[2], sx[3], xv[0].x, xv[1].x, xv[2].x, v3.x); sum_h4(sx[4], sx[5], xv[0].y, xv[1].y, xv[2].y, v3.y);
          sum_h4(sx[6], sx[7], xv[0].z, xv[1].z, xv[2].z, v3.z); sum_h4(sx[8], sx[9], xv[0].w, xv[1].w, xv[2].w, v3.w);
          const int row = 8 * j + g - 2 * tq;
#pragma unroll
          for (int i = 0; i < 8; i++) if ((i >> 1) * 8 + (i & 1) > row) sx[2 + i] = -INFINITY;
        }
        FENCE();
        bar_sync(B_QK1, 288);
        uint32_t kb[2][2];
#pragma unroll
        for (int t = 0; t < 2; t++) {
          const float4 u = lds128f(lq + (SM_QKP + (2 + t) * 512)), v4 = lds128f(lq + (SM_QKP + 2048 + (2 + t) * 512));
          kb[t][0] = pack_bf16(u.x + v4.x, u.y + v4.y); kb[t][1] = pack_bf16(u.z + v4.z, u.w + v4.w);
        }
        float S[2][4];
#pragma unroll
        for (int mt = 0; mt < 2; mt++) mma4z(S[mt], qx[mt].x, qx[mt].z, qx[mt].y, qx[mt].w, kb[0][0], kb[0][1]);
#pragma unroll
        for (int mt = 0; mt < 2; mt++) mma4(S[mt], qx[2 + mt].x, qx[2 + mt].z, qx[2 + mt].y, qx[2 + mt].w, kb[1][0], kb[1][1]);
        if (s < NSEG - 1) bar_arrive(B_PUB, 320);
#pragma unroll
        for (int u = 0; u < 4; u++) {
          const uint32_t m4 = tagw(pack_f16(S[u >> 1][2 * (u & 1)] * sc, S[u >> 1][2 * (u & 1) + 1] * sc), t2);
          const int e = u ^ j;
          if (e) stg_r1(P.win + (db + (u >> 1) * 16384 + (u & 1) * 2048 + e * 640 + 512 - l12), m4);
          else sts32(ls - l12 + SM_XS + 512, m4);
        }
        if (ETW == 1 && s < NSEG - 1) ETA(DLY_K, 1);
        TS(30);
        spin(DLY_XL);
        uint32_t xy[3]; int n = 0;
#pragma unroll 1
        do {
#pragma unroll
          for (int i = 0; i < 3; i++) xy[i] = ldg_r1(pa + i * 640 + 512 - l12);
        } while (__any_sync(~0u, (x3(xy[0], xy[1], t2) | (xy[2] ^ t2)) & 1u) && ++n < SPIN_LIMIT);
        sum_h4(sx[0], sx[1], xy[0], xy[1], xy[2], lds32(ls - l12 + SM_XS + 512));
        if (s > 0) bar_sync(B_PXF, 96);
        SOFTMAX(SM_PX, 1.f);
        bar_arrive(B_PX, 96);
        TS(1);
        }
      }
    } else {
      const uint32_t ho = (wq & 1) * 512 + l16, hv = wq == 0 ? 0u : H1_V;
      uint32_t ow = w_blk(w_h1(cta) ^ hv, me) + ho, or0 = w_blk(w_h1(cta ^ 1) ^ hv, me) + ho, or1 = w_blk(w_h1((cta ^ 2) & ~1) ^ hv, me) + ho;
#define PTRS() OPAQUE_R(ow); OPAQUE_R(or0); OPAQUE_R(or1); \
      unsigned char* pw0 = P.win + ow; const unsigned char* pr0 = P.win + or0; const unsigned char* pr1 = P.win + or1; \
      OPAQUE_L(pw0); OPAQUE_L(pr0); OPAQUE_L(pr1); FENCE()
      if (wq == 0) {
        const uint32_t xcnt = me ? NCTA - nlo : nlo, xrank = (me ? cta - nlo : cta) + lane * xcnt;
        const uint32_t l8 = l16 >> 1;
        for (int s = 0; s < NSEG; s++) {
          const uint32_t tg = (s & 1) ^ 1;
          mbar_wait(sb + SM_BAR + MB_XF, s & 1);
          uint4 xf[4];
#pragma unroll
          for (int i = 0; i < 4; i++) xf[i] = ldsm4(ls + (SM_XF + (4 + i) * 512));
          PTRS();
          bar_sync(B_QK, 288);
          if (s == NSEG - 1) break;
          float4 u[4], v4[4];
#pragma unroll
          for (int t = 0; t < 4; t++) { u[t] = lds128f(lq + (SM_QKP + t * 512)); v4[t] = lds128f(lq + (SM_QKP + 2048 + t * 512)); }

          FENCE();
          uint32_t f[4][2];
#pragma unroll
          for (int t = 0; t < 4; t++) {
            f[t][0] = pack_bf16(u[t].x + v4[t].x, u[t].y + v4[t].y);
            f[t][1] = pack_bf16(u[t].z + v4[t].z, u[t].w + v4[t].w);
          }
          float S[5][4];
          mma4z(S[1], f[0][0], 0u, f[0][1], 0u, xf[0].x, xf[0].y);
          mma4z(S[2], f[0][0], 0u, f[0][1], 0u, xf[0].z, xf[0].w);
          mma4z(S[3], f[0][0], 0u, f[0][1], 0u, xf[1].x, xf[1].y);
          mma4z(S[4], f[0][0], 0u, f[0][1], 0u, xf[1].z, xf[1].w);
          mma4(S[1], f[1][0], 0u, f[1][1], 0u, xf[2].x, xf[2].y);
          mma4(S[2], f[1][0], 0u, f[1][1], 0u, xf[2].z, xf[2].w);
          mma4z(S[0], f[0][0], 0u, f[0][1], 0u, f[2][0], f[2][1]);
          mma4(S[3], f[1][0], 0u, f[1][1], 0u, xf[3].x, xf[3].y);
          mma4(S[4], f[1][0], 0u, f[1][1], 0u, xf[3].z, xf[3].w);
          mma4(S[0], f[1][0], 0u, f[1][1], 0u, f[3][0], f[3][1]);
          bar_arrive(B_PUB, 320);
          stg_r4(pw0, tagw(pack_f16(S[1][0] * sc, S[1][1] * sc), tg), pack_f16(S[2][0] * sc, S[2][1] * sc), pack_f16(S[3][0] * sc, S[3][1] * sc), pack_f16(S[4][0] * sc, S[4][1] * sc));
          stg_r1(pw0 + 512 - l12, tagw(pack_f16(S[0][0] * sc, S[0][1] * sc), tg));
          TS(6);
          if (ETW == 0) ETA(DLY_K, 1);
          float sx[10];
#pragma unroll
          for (int i = 0; i < 10; i++) sx[i] = S[i >> 1][i & 1] * (0.25f * sc);
          spin(DLY_S);
          {
            uint4 v[3]; uint32_t y[3]; int n = 0; uint32_t bad;
#pragma unroll 1
            do {
              v[0] = ldg_r4(pr0); v[1] = ldg_r4(pr1); v[2] = ldg_r4(pr1 + 2048);
              y[0] = ldg_r1(pr0 + 512 - l12); y[1] = ldg_r1(pr1 + 512 - l12); y[2] = ldg_r1(pr1 + 2560 - l12);
              if (n) ETA(DLY_KS, 0);
              bad = or3(x3(v[0].x, v[1].x, tg), x3(v[2].x, y[0], tg), x3(y[1], y[2], tg)) & 1u;
            } while (__any_sync(~0u, bad) && ++n < SPIN_LIMIT);
            TS(7); TV(19, n);
            add_q3(sx[2], sx[3], v[0].x, v[1].x, v[2].x); add_q3(sx[4], sx[5], v[0].y, v[1].y, v[2].y);
            add_q3(sx[6], sx[7], v[0].z, v[1].z, v[2].z); add_q3(sx[8], sx[9], v[0].w, v[1].w, v[2].w);
            add_q3(sx[0], sx[1], y[0], y[1], y[2]);
          }
          SOFTMAX(SM_PF, 4.f);
          TS(12);
          bar_sync(B_P, 96);
          {
            const unsigned char* pe = P.win + w_blk(w_ar(s) + 384 + (l16 & 0x60u) * 256 + (l16 & 16u) * 128, me);
            spin(DLY_E);
            uint2 e = ldg_r2(pe); int n = 0;
            if (s < NSEG - 2) {
              mbar_wait(sb + SM_BAR + MB_XE0, s & 1);
              if (l16 == 0) { mbar_expect_tx(sb + SM_BAR + MB_F, 32768); XLOAD(0, s + 2); }
              __syncwarp();
              TS(25);
            }
#pragma unroll 1
            while (__any_sync(~0u, e.x != 16u) && ++n < SPIN_LIMIT) e = ldg_r2(pe);
            const uint32_t tg0 = __reduce_max_sync(~0u, e.y);
            TS(14); TV(29, n);
            bar_sync(B_M2, 288);
            spin(DLY_M3);
            while (tg0 - gt32() - 1u < 4096u) {}
            bar_arrive(B_GO, 96);
            TS(16);
          }
          if (F1C && s < NSEG - 2) {
            if (F1C == 1) spin(DLY_FA);
            mbar_wait(sb + SM_BAR + MB_XE1, (s + 1) & 1);
            if (l16 == 0) mbar_expect_tx(sb + SM_BAR + MB_F + 8, 32768);
            if (F1C == 2) { mbar_wait(sb + SM_BAR + MB_MEM, (s + 1) & 1); mbar_wait(sb + SM_BAR + MB_MEM + 8, (s + 1) & 1); }
            if (l16 == 0) XLOAD(1, s + 2);
            __syncwarp();
            TST(s + 1, 27, l16, TCLK());
          }
          if (XPF && s + XPF < NSEG) {
            spin(DLY_PF);
            for (uint32_t i = xrank; i < 512; i += 32 * xcnt)
              asm volatile("prefetch.global.L2 [%0];" :: "l"(SP.x + (size_t)(s + XPF) * (SEG * DM) + i * 64));
            __syncwarp();
          }
          stg_2(P.win + (w_ar(s + 2) + cta * 256 + (l16 >> 1)), 0u, 0u);
        }
      } else {
        const int mt = wq - 2;
        const uint32_t lt = ls + mt * 1024;
        const uint32_t vi0 = w_blk(w_mvx(h * 4, 0), me2) + mt * 1024;
        const int m3d = r ? -8192 : 8192;
        for (int s = 0; s < NSEG; s++) {
          const uint32_t tg = (s & 1) ^ 1, t2 = ((s >> 1) & 1) ^ 1;
          {
            OPAQUE_R(l16);
            const uint32_t m3i = (mt * 2 + r) * 8192 + (l16 & 0x70u) + ((l16 & 0x180u) << 1);
            const uint32_t m3j = (mt * 2 + (r ^ (l16 >> 7 & 1))) * 8192 + ((l16 & 64u) * 4 + (l16 & 48u) * 2) * 16 + 128 + (l16 & 0x70u);
            uint32_t m3c = sb + SM_MEM + mt * 8192 + cnt_line(l16 >> 4) * 128 + (l16 >> 2);
            const unsigned char* p3 = P.win + (m3i + w_ar(s - 1)); const unsigned char* pd = P.win + (m3j + w_ar(s - 1));
            OPAQUE_L(pd); OPAQUE_R(m3c);
            const int n = m3_gather(sb, p3, pd, m3d, l16, m3c, mt, me ^ 1 ^ r, s > 0);
            TST(s, mt ? 22 : 17, l16, n);
          }
          uint4 va[8], vm[2], p0; uint32_t p2;
          const unsigned char* a0 = P.win + (vi0 + ((s & 1) << 20) + l16);
#define VALD() _Pragma("unroll") for (int i = 0; i < 4; i++) { va[i] = ldg_r4(a0 + (i >> 1) * 512 + (i & 1) * 2048); va[4 + i] = ldg_r4(a0 + 16384 + (i >> 1) * 512 + (i & 1) * 2048); }
          spin(DLY_WO);
          VALD();
          {
          PTRS();
          bar_sync(B_V, 320);
            const float4 u0 = lds128f(lt + SM_VP), w0 = lds128f(lt + SM_VP + 2048), u1 = lds128f(lt + SM_VP + 512), w1 = lds128f(lt + SM_VP + 2560);
            const uint32_t m0 = tagw(pack_bf16(u0.x + w0.x, u0.y + w0.y), tg), m1 = pack_bf16(u0.z + w0.z, u0.w + w0.w),
                           m2 = pack_bf16(u1.x + w1.x, u1.y + w1.y), m3 = pack_bf16(u1.z + w1.z, u1.w + w1.w);
            stg_r4(pw0, m0, m1, m2, m3);
            if (wq == 2) TS(10);
            FENCE();
            const uint32_t tv = clk32();
            int n = 0;
#pragma unroll 1
            while (__any_sync(~0u, (or3(x3(va[0].x, va[1].x, t2), x3(va[2].x, va[3].x, t2), x3(va[4].x, va[5].x, t2)) | x3(va[6].x, va[7].x, t2)) & 1u) && ++n < SPIN_LIMIT) { VALD(); }
            TST(s, 20, l16 | mt, n);
            while (clk32() - tv < (uint32_t)DLY_V) {}
            uint4 v[3]; n = 0;
#pragma unroll 1
            do {
              v[0] = ldg_r4(pr0); v[1] = ldg_r4(pr1); v[2] = ldg_r4(pr1 + 2048);
              if (n && s < NSEG - 1) ETA(DLY_KS - 192, 0);
            } while (__any_sync(~0u, (x3(v[0].x, v[1].x, tg) | (v[2].x ^ tg)) & 1u) && ++n < SPIN_LIMIT);
            const uint4 A = make_uint4(addb2(m0, v[0].x), addb2(m1, v[0].y), addb2(m2, v[0].z), addb2(m3, v[0].w));
            const uint4 B = make_uint4(addb2(v[1].x, v[2].x), addb2(v[1].y, v[2].y), addb2(v[1].z, v[2].z), addb2(v[1].w, v[2].w));
            vm[0] = p ? B : A; vm[1] = p ? A : B;
            if (wq == 2) TS(11);
            TST(s, 26, l16 | !n, 1);
          }
          FENCE();
          if (s < NSEG - 1) {
          bar_sync(B_P, 96);
          p0 = lds128(ls + SM_PF); p2 = lds32(ls - l12 + SM_PF + 512);
          PV4(va, vm, SM_OF + mt * 512);
          bar_arrive(B_O, 320);
          }
          FENCE();
          if (wq == 2) TS(8);
          spin(DLY_PX);
          bar_sync(B_PX, 96);
          p0 = lds128(ls + SM_PX); p2 = lds32(ls - l12 + SM_PX + 512);
          PV4(va, vm, SM_OX + mt * 512);
          if (s < NSEG - 1) bar_arrive(B_PXF, 96);
          __syncwarp();
          {
            const uint32_t oa = sb + SM_OX + mt * 512 + ((l16 & 48u) << 3) + ((l16 >> 2) & 0x70u);
            const uint4 a = lds128(oa), b = lds128(oa + 1024);
            unsigned char* o = reinterpret_cast<unsigned char*>(g_ox + (size_t)(s * SEG + 8 * j) * (NH * DH) + h * DH + mt * 32) + ((l16 >> 6) * (NH * DH * 2) + (l16 & 48u));
            stg_4(o, a); stg_4(o + 128, b);
          }
          TST(s, 18, l16 | mt, TCLK());
        }
      }
    }
  }
  asm volatile("barrier.cluster.arrive.relaxed.aligned;\nbarrier.cluster.wait.aligned;" ::: "memory");
}
#define PW 2
#define G2_ST 6
#define G2_TB (G2_ST * 32768 + 1024)
#define G2_SMEM (G2_TB + 32768)
static __device__ __forceinline__ void wgmma_n128_ta(float (&d)[64], uint64_t da, uint64_t db) {
  asm volatile(
      "wgmma.mma_async.sync.aligned.m64n128k16.f32.bf16.bf16 "
      "{%0,%1,%2,%3,%4,%5,%6,%7,%8,%9,%10,%11,%12,%13,%14,%15,%16,%17,%18,%19,%20,%21,%22,%23,%24,%25,%26,%27,%28,%29,%30,%31,"
      "%32,%33,%34,%35,%36,%37,%38,%39,%40,%41,%42,%43,%44,%45,%46,%47,%48,%49,%50,%51,%52,%53,%54,%55,%56,%57,%58,%59,%60,%61,%62,%63}, "
      "%64, %65, 1, 1, 1, 1, 0;"
      : "+f"(d[0]), "+f"(d[1]), "+f"(d[2]), "+f"(d[3]), "+f"(d[4]), "+f"(d[5]), "+f"(d[6]), "+f"(d[7]), "+f"(d[8]), "+f"(d[9]), "+f"(d[10]), "+f"(d[11]),
        "+f"(d[12]), "+f"(d[13]), "+f"(d[14]), "+f"(d[15]), "+f"(d[16]), "+f"(d[17]), "+f"(d[18]), "+f"(d[19]), "+f"(d[20]), "+f"(d[21]), "+f"(d[22]), "+f"(d[23]),
        "+f"(d[24]), "+f"(d[25]), "+f"(d[26]), "+f"(d[27]), "+f"(d[28]), "+f"(d[29]), "+f"(d[30]), "+f"(d[31]), "+f"(d[32]), "+f"(d[33]), "+f"(d[34]), "+f"(d[35]),
        "+f"(d[36]), "+f"(d[37]), "+f"(d[38]), "+f"(d[39]), "+f"(d[40]), "+f"(d[41]), "+f"(d[42]), "+f"(d[43]), "+f"(d[44]), "+f"(d[45]), "+f"(d[46]), "+f"(d[47]),
        "+f"(d[48]), "+f"(d[49]), "+f"(d[50]), "+f"(d[51]), "+f"(d[52]), "+f"(d[53]), "+f"(d[54]), "+f"(d[55]), "+f"(d[56]), "+f"(d[57]), "+f"(d[58]), "+f"(d[59]),
        "+f"(d[60]), "+f"(d[61]), "+f"(d[62]), "+f"(d[63])
      : "l"(da), "l"(db));
}
__global__ void __cluster_dims__(2, 1, 1) __launch_bounds__(384, 1)
gemm2_kernel(const __grid_constant__ CUtensorMap tmo, const __grid_constant__ CUtensorMap tmw, const bf16* __restrict__ x, bf16* __restrict__ out, unsigned char* win) {
  extern __shared__ __align__(1024) unsigned char smem[];
  const uint32_t sb = smem_u32(smem), bars = sb + G2_ST * 32768;
  const int tid = threadIdx.x, lane = tid & 31, warp = tid >> 5;
  const int r = blockIdx.x & 1, n0 = (blockIdx.x & 7) * 128, m0 = (blockIdx.x >> 3) * 128;
  if (tid == 0) {
    for (int i = 0; i < G2_ST; i++) { mbar_init(bars + i * 8, 1); mbar_init(bars + 64 + i * 8, 4); }
    asm volatile("fence.mbarrier_init.release.cluster;" ::: "memory");
  }
  if (tid == 32) { asm volatile("prefetch.tensormap [%0];" :: "l"(&tmw) : "memory"); asm volatile("prefetch.tensormap [%0];" :: "l"(&tmo) : "memory"); }
  __syncthreads();
  asm volatile("barrier.cluster.arrive.relaxed.aligned;" ::: "memory");
#define LW(kt, st) do { tma_load_2d(sb + (st) * 32768, &tmw, n0, (kt) * 64, bars + (st) * 8); tma_load_2d(sb + (st) * 32768 + 8192, &tmw, n0 + 64, (kt) * 64, bars + (st) * 8); } while (0)
#define LO(kt, st) asm volatile("cp.async.bulk.tensor.2d.shared::cluster.global.mbarrier::complete_tx::bytes.multicast::cluster [%0], [%1, {%3, %4}], [%2], %5;" \
                     :: "r"(sb + (st) * 32768 + 16384 + r * 8192), "l"(&tmo), "r"(bars + (st) * 8), "r"((kt) * 64), "r"(m0 + r * 64), "h"((uint16_t)3) : "memory")
  if (tid == 256) for (int kt = 0; kt < G2_ST; kt++) { mbar_expect_tx(bars + kt * 8, 32768); if (kt < PW) LW(kt, kt); }
  __syncwarp();
  asm volatile("barrier.cluster.wait.acquire.aligned;" ::: "memory");
  if (warp == 8) {
    if (lane == 0) {
      asm volatile("griddepcontrol.wait;" ::: "memory");
      for (int kt = 0; kt < G2_ST; kt++) { LO(kt, kt); if (kt >= PW) LW(kt, kt); }
      for (int kt = G2_ST; kt < 64; kt++) {
        const int st = kt % G2_ST;
        mbar_wait(bars + 64 + st * 8, ((kt / G2_ST) - 1) & 1);
        mbar_expect_tx(bars + st * 8, 32768);
        LO(kt, st); LW(kt, st);
      }
    }
  } else if (warp > 8) {
    const int t = tid - 288, ch = t & 15;
    asm volatile("griddepcontrol.wait;" ::: "memory");
    int idx[8];
#pragma unroll
    for (int c = 0; c < 8; c++) idx[c] = g_idx[c];
    const int gi = blockIdx.x * 96 + t;
    if (gi < 67) g_side[gi * 32] = 0u;
    if (gi == 0) g_sbar = 0u;
#pragma unroll 4
    for (int row = t >> 4; row < 128; row += 6) {
      const int tok = m0 + row;
      const uint4 xv = *reinterpret_cast<const uint4*>(x + (size_t)tok * DM + n0 + ch * 8);
      const float g = g_gate[tok], omg = rbf(1.f - g);
      int sel = -1;
#pragma unroll
      for (int c = 0; c < 8; c++) if (idx[c] == tok) sel = c;
      uint4 uv = make_uint4(0u, 0u, 0u, 0u);
      if (sel >= 0) uv = *reinterpret_cast<const uint4*>(g_upd + sel * DM + n0 + ch * 8);
      const uint32_t x4[4] = {xv.x, xv.y, xv.z, xv.w}, u4[4] = {uv.x, uv.y, uv.z, uv.w};
      uint32_t o4[4];
#pragma unroll
      for (int e = 0; e < 4; e++) {
        const float b0 = rbf(u2f(x4[e] << 16) + u2f(u4[e] << 16)), b1 = rbf(u2f(x4[e] & 0xffff0000u) + u2f(u4[e] & 0xffff0000u));
        o4[e] = pack_bf16(omg * b0, omg * b1);
      }
      sts128(sb + G2_TB + row * 256 + ch * 16, o4[0], o4[1], o4[2], o4[3]);
      if (ch == 0) sts32(bars + 512 + row * 4, __float_as_uint(g));
    }
    bar_arrive(2, 352);
  } else {
    const int wg = warp >> 2;
    float d[64];
#pragma unroll
    for (int i = 0; i < 64; i++) d[i] = 0.f;
    const uint32_t e0 = mapa(bars + 64, 0), e1 = mapa(bars + 64, 1);
    for (int kt = 0; kt < 64; kt++) {
      const int st = kt % G2_ST;
      mbar_wait(bars + st * 8, (kt / G2_ST) & 1);
      wg_fence();
#pragma unroll
      for (int kk = 0; kk < 4; kk++)
        wgmma_n128_ta(d, make_desc(sb + st * 32768 + wg * 8192 + kk * 2048, 1024, 1024), make_desc(sb + st * 32768 + 16384 + kk * 32, 16, 1024));
      wg_commit();
      asm volatile("wgmma.wait_group.sync.aligned 1;" ::: "memory");
      if (kt > 0 && (tid & 127) == 0) { const int ps = (kt - 1) % G2_ST; mbar_arrive_cluster_rlx(e0 + ps * 8); mbar_arrive_cluster_rlx(e1 + ps * 8); }
    }
    wg_wait0();
    bar_sync(1, 256);
#pragma unroll
    for (int jj = 0; jj < 8; jj++) {
      const uint32_t q0 = pack_bf16(d[8 * jj], d[8 * jj + 1]), q1 = pack_bf16(d[8 * jj + 2], d[8 * jj + 3]);
      const uint32_t q2 = pack_bf16(d[8 * jj + 4], d[8 * jj + 5]), q3 = pack_bf16(d[8 * jj + 6], d[8 * jj + 7]);
      stsm4t(sb + (jj * 16 + (lane >> 4) * 8 + (lane & 7)) * 272 + (warp * 16 + ((lane >> 3) & 1) * 8) * 2, q0, q1, q2, q3);
    }
    bar_sync(2, 352);
#pragma unroll
    for (int it = 0; it < 8; it++) {
      const int row = it * 16 + (tid >> 4), ch = tid & 15, tok = m0 + row;
      const uint4 av = lds128(sb + row * 272 + ch * 16), tv = lds128(sb + G2_TB + row * 256 + ch * 16);
      const float g = u2f(lds32(bars + 512 + row * 4));
      const uint32_t a4[4] = {av.x, av.y, av.z, av.w}, t4[4] = {tv.x, tv.y, tv.z, tv.w};
      uint32_t o4[4];
#pragma unroll
      for (int e = 0; e < 4; e++)
        o4[e] = pack_bf16(rbf(g * u2f(a4[e] << 16)) + u2f(t4[e] << 16), rbf(g * u2f(a4[e] & 0xffff0000u)) + u2f(t4[e] & 0xffff0000u));
      *reinterpret_cast<uint4*>(out + (size_t)tok * DM + n0 + ch * 8) = make_uint4(o4[0], o4[1], o4[2], o4[3]);
    }
  }
  asm volatile("barrier.cluster.arrive.relaxed.aligned;\nbarrier.cluster.wait.aligned;" ::: "memory");
}
#define WPROM CU_TENSOR_MAP_L2_PROMOTION_L2_128B
#define PDL 1
typedef CUresult (*PFN_encodeTiled)(CUtensorMap*, CUtensorMapDataType, cuuint32_t, void*, const cuuint64_t*, const cuuint64_t*,
                                    const cuuint32_t*, const cuuint32_t*, CUtensorMapInterleave, CUtensorMapSwizzle,
                                    CUtensorMapL2promotion, CUtensorMapFloatOOBfill);

extern "C" void kernel_launch(void* const* d_in, const int* in_sizes, int n_in, void* d_out, int out_size) {
  const bf16* x = (const bf16*)d_in[0];
  const bf16* mem0 = (const bf16*)d_in[1];
  const bf16* Wq = (const bf16*)d_in[2];
  const bf16* Wk = (const bf16*)d_in[3];
  const bf16* Wv = (const bf16*)d_in[4];
  const bf16* Wo = (const bf16*)d_in[5];
  const bf16* w_r = (const bf16*)d_in[8];
  const bf16* w_gate = (const bf16*)d_in[9];
  const bf16* w_up = (const bf16*)d_in[10];
  const bf16* w_down = (const bf16*)d_in[11];
  const bf16* gate_w = (const bf16*)d_in[12];
  bf16* out = (bf16*)d_out;

  static PFN_encodeTiled encode = nullptr;
  if (!encode) {
    void* fn = nullptr; cudaDriverEntryPointQueryResult st;
    cudaGetDriverEntryPoint("cuTensorMapEncodeTiled", &fn, cudaEnableDefault, &st);
    encode = (PFN_encodeTiled)fn;
    cudaFuncSetAttribute(rec_kernel, cudaFuncAttributeMaxDynamicSharedMemorySize, SM_TOTAL);
    cudaFuncSetAttribute(gemm2_kernel, cudaFuncAttributeMaxDynamicSharedMemorySize, G2_SMEM);
  }
  CUtensorMap tmx;
  {
    cuuint64_t gd[3] = {64, S_TOK, DM / 64};
    cuuint64_t gs[2] = {DM * 2, 128};
    cuuint32_t bx[3] = {64, SEG, 2};
    cuuint32_t es[3] = {1, 1, 1};
    encode(&tmx, CU_TENSOR_MAP_DATA_TYPE_BFLOAT16, 3, (void*)x, gd, gs, bx, es, CU_TENSOR_MAP_INTERLEAVE_NONE,
           CU_TENSOR_MAP_SWIZZLE_128B, CU_TENSOR_MAP_L2_PROMOTION_L2_128B, CU_TENSOR_MAP_FLOAT_OOB_FILL_NONE);
  }
  bf16* ox;
  cudaGetSymbolAddress((void**)&ox, g_ox);
  CUtensorMap tmo, tmw;
  {
    cuuint64_t gd[2] = {NH * DH, S_TOK}; cuuint64_t gs[1] = {NH * DH * 2}; cuuint32_t bx[2] = {64, 64}; cuuint32_t es[2] = {1, 1};
    encode(&tmo, CU_TENSOR_MAP_DATA_TYPE_BFLOAT16, 2, (void*)ox, gd, gs, bx, es, CU_TENSOR_MAP_INTERLEAVE_NONE,
           CU_TENSOR_MAP_SWIZZLE_128B, CU_TENSOR_MAP_L2_PROMOTION_L2_128B, CU_TENSOR_MAP_FLOAT_OOB_FILL_NONE);
    cuuint64_t gd2[2] = {DM, NH * DH}; cuuint64_t gs2[1] = {DM * 2}; cuuint32_t bx2[2] = {64, 64};
    encode(&tmw, CU_TENSOR_MAP_DATA_TYPE_BFLOAT16, 2, (void*)Wo, gd2, gs2, bx2, es, CU_TENSOR_MAP_INTERLEAVE_NONE,
           CU_TENSOR_MAP_SWIZZLE_128B, CU_TENSOR_MAP_L2_PROMOTION_L2_128B, CU_TENSOR_MAP_FLOAT_OOB_FILL_NONE);
  }
  unsigned char* win;
  cudaGetSymbolAddress((void**)&win, g_win);
  win = (unsigned char*)(((uintptr_t)win + (2u << 20) - 1) & ~(uintptr_t)((2u << 20) - 1));
  WMaps W;
  {
    cuuint64_t gd[2] = {NH * DH, DM}; cuuint64_t gs[1] = {NH * DH * 2}; cuuint32_t b32[2] = {32, 128}, b64[2] = {64, 128}; cuuint32_t es[2] = {1, 1};
    encode(&W.q, CU_TENSOR_MAP_DATA_TYPE_BFLOAT16, 2, (void*)Wq, gd, gs, b32, es, CU_TENSOR_MAP_INTERLEAVE_NONE,
           CU_TENSOR_MAP_SWIZZLE_64B, WPROM, CU_TENSOR_MAP_FLOAT_OOB_FILL_NONE);
    encode(&W.k, CU_TENSOR_MAP_DATA_TYPE_BFLOAT16, 2, (void*)Wk, gd, gs, b32, es, CU_TENSOR_MAP_INTERLEAVE_NONE,
           CU_TENSOR_MAP_SWIZZLE_64B, WPROM, CU_TENSOR_MAP_FLOAT_OOB_FILL_NONE);
    encode(&W.v, CU_TENSOR_MAP_DATA_TYPE_BFLOAT16, 2, (void*)Wv, gd, gs, b64, es, CU_TENSOR_MAP_INTERLEAVE_NONE,
           CU_TENSOR_MAP_SWIZZLE_128B, WPROM, CU_TENSOR_MAP_FLOAT_OOB_FILL_NONE);
  }
  RecParams P{mem0, win};
  SideParams SP{x, w_r, w_gate, w_up, w_down, gate_w, Wo};
  rec_kernel<<<NCTA + 4, 384, SM_TOTAL, cudaStreamPerThread>>>(tmx, tmw, W, P, SP);
  {
    cudaLaunchConfig_t cfg = {};
    cfg.gridDim = dim3(NCTA); cfg.blockDim = dim3(384); cfg.dynamicSmemBytes = G2_SMEM; cfg.stream = cudaStreamPerThread;
    cudaLaunchAttribute at[1];
    at[0].id = cudaLaunchAttributeProgrammaticStreamSerialization; at[0].val.programmaticStreamSerializationAllowed = 1;
    cfg.attrs = at; cfg.numAttrs = PDL;
    cudaLaunchKernelEx(&cfg, gemm2_kernel, tmo, tmw, x, out, win);
  }
}
```

```cpp
#include <cuda_runtime.h>
#include <cuda_bf16.h>
#include <cuda_fp16.h>
#include <cuda.h>
#include <stdint.h>

typedef __nv_bfloat16 bf16;

#define S_TOK 2048
#define DM 1024
#define NH 32
#define DH 128
#define MM 8
#define SEG 32
#define NSEG 64
#define LL 40
#define FF 3584
#define NCTA 128

static __device__ bf16 g_ox[(size_t)S_TOK * NH * DH];
static __device__ float g_gate[S_TOK];
static __device__ float g_r[S_TOK];
static __device__ int g_idx[8];
static __device__ bf16 g_upd[8 * DM];

static __device__ __forceinline__ float rbf(float v) { return __bfloat162float(__float2bfloat16(v)); }
static __device__ __forceinline__ uint32_t smem_u32(const void* p) { return (uint32_t)__cvta_generic_to_shared(p); }
static __device__ __forceinline__ uint32_t pack_bf16(float lo, float hi) {
  __nv_bfloat162 v = __floats2bfloat162_rn(lo, hi);
  return *reinterpret_cast<uint32_t*>(&v);
}

static __device__ __forceinline__ void wg_fence() { asm volatile("wgmma.fence.sync.aligned;" ::: "memory"); }
static __device__ __forceinline__ void wg_commit() { asm volatile("wgmma.commit_group.sync.aligned;" ::: "memory"); }
static __device__ __forceinline__ void wg_wait0() { asm volatile("wgmma.wait_group.sync.aligned 0;" ::: "memory"); }
static __device__ __forceinline__ void fence_async_smem() { asm volatile("fence.proxy.async.shared::cta;" ::: "memory"); }

static __device__ __forceinline__ uint64_t make_desc(uint32_t addr, uint32_t lbo, uint32_t sbo) {
  uint64_t d = 0;
  d |= (uint64_t)((addr & 0x3FFFF) >> 4);
  d |= (uint64_t)((lbo >> 4) & 0x3FFF) << 16;
  d |= (uint64_t)((sbo >> 4) & 0x3FFF) << 32;
  d |= (uint64_t)1 << 62;
  return d;
}

#define DESC_HI(sbo) (((sbo) >> 4) | (1u << 30))
template <int OFF, int SCALE>
static __device__ __forceinline__ void wgmma_n32_ra(float (&d)[16], const uint32_t (&a)[4], uint32_t base16) {
  asm volatile(
      "{\n.reg .b32 t;\n.reg .b64 dd;\nadd.u32 t, %20, %21;\nmov.b64 dd, {t, %22};\n"
      "wgmma.mma_async.sync.aligned.m64n32k16.f32.bf16.bf16 "
      "{%0,%1,%2,%3,%4,%5,%6,%7,%8,%9,%10,%11,%12,%13,%14,%15}, {%16,%17,%18,%19}, dd, %23, 1, 1, 0;\n}"
      : "+f"(d[0]), "+f"(d[1]), "+f"(d[2]), "+f"(d[3]), "+f"(d[4]), "+f"(d[5]), "+f"(d[6]), "+f"(d[7]),
        "+f"(d[8]), "+f"(d[9]), "+f"(d[10]), "+f"(d[11]), "+f"(d[12]), "+f"(d[13]), "+f"(d[14]), "+f"(d[15])
      : "r"(a[0]), "r"(a[1]), "r"(a[2]), "r"(a[3]), "r"(base16), "n"(OFF >> 4), "n"(DESC_HI(1024)), "n"(SCALE));
}
template <int AOFF, int BOFF, int SCALE>
static __device__ __forceinline__ void wgmma_n32_ss_ta(float (&d)[16], uint32_t abase16, uint32_t bbase16) {
  asm volatile(
      "{\n.reg .b32 t, u;\n.reg .b64 da, db;\nadd.u32 t, %16, %18;\nmov.b64 da, {t, %20};\nadd.u32 u, %17, %19;\nmov.b64 db, {u, %20};\n"
      "wgmma.mma_async.sync.aligned.m64n32k16.f32.bf16.bf16 "
      "{%0,%1,%2,%3,%4,%5,%6,%7,%8,%9,%10,%11,%12,%13,%14,%15}, da, db, %21, 1, 1, 1, 0;\n}"
      : "+f"(d[0]), "+f"(d[1]), "+f"(d[2]), "+f"(d[3]), "+f"(d[4]), "+f"(d[5]), "+f"(d[6]), "+f"(d[7]),
        "+f"(d[8]), "+f"(d[9]), "+f"(d[10]), "+f"(d[11]), "+f"(d[12]), "+f"(d[13]), "+f"(d[14]), "+f"(d[15])
      : "r"(abase16), "r"(bbase16), "n"(AOFF >> 4), "n"(BOFF >> 4), "n"(DESC_HI(1024)), "n"(SCALE));
}
static __device__ __forceinline__ void ldmatrix_x4_trans(uint32_t (&r)[4], uint32_t addr) {
  asm volatile("ldmatrix.sync.aligned.m8n8.x4.trans.shared.b16 {%0,%1,%2,%3}, [%4];"
               : "=r"(r[0]), "=r"(r[1]), "=r"(r[2]), "=r"(r[3]) : "r"(addr) : "memory");
}
static __device__ __forceinline__ void mma_16816(float (&d)[4], const uint32_t (&a)[4], uint32_t b0, uint32_t b1) {
  asm volatile("mma.sync.aligned.m16n8k16.row.col.f32.bf16.bf16.f32 {%0,%1,%2,%3}, {%4,%5,%6,%7}, {%8,%9}, {%0,%1,%2,%3};"
               : "+f"(d[0]), "+f"(d[1]), "+f"(d[2]), "+f"(d[3])
               : "r"(a[0]), "r"(a[1]), "r"(a[2]), "r"(a[3]), "r"(b0), "r"(b1));
}

static __device__ __forceinline__ uint32_t mapa(uint32_t addr, uint32_t rank) {
  uint32_t r; asm volatile("mapa.shared::cluster.u32 %0, %1, %2;" : "=r"(r) : "r"(addr), "r"(rank)); return r;
}

static __device__ __forceinline__ void mbar_init(uint32_t bar, int cnt) {
  asm volatile("mbarrier.init.shared::cta.b64 [%0], %1;" :: "r"(bar), "r"(cnt) : "memory");
}
static __device__ __forceinline__ void mbar_expect_tx(uint32_t bar, uint32_t bytes) {
  asm volatile("mbarrier.arrive.expect_tx.shared::cta.b64 _, [%0], %1;" :: "r"(bar), "r"(bytes) : "memory");
}
static __device__ __forceinline__ void tma_load_2d(uint32_t dst, const CUtensorMap* tm, int c0, int c1, uint32_t bar) {
  asm volatile("cp.async.bulk.tensor.2d.shared::cluster.global.mbarrier::complete_tx::bytes [%0], [%1, {%3, %4}], [%2];"
               :: "r"(dst), "l"(tm), "r"(bar), "r"(c0), "r"(c1) : "memory");
}

static __device__ unsigned char g_win[6 << 20];
static __device__ unsigned int g_side[67 * 32];
static __device__ unsigned int g_err;
#define W_UP (1u << 20)
#define W_2 (2u << 20)
static __device__ __forceinline__ uint32_t w_blk(uint32_t off, uint32_t side) { return off | (((__popc((off >> 12) & 0xb3u) ^ side) & 1u) << 12); }
static __device__ __forceinline__ uint32_t w_h1(int c) { return W_UP | (1u << 13) | ((c >> 1) << 14) | ((c & 1) << 11); }
static __device__ __forceinline__ uint32_t w_ar(int s) { return ((s & 1) << 15) | ((s & 2) << 17); }
static __device__ __forceinline__ uint32_t w_mvx(int c, int s) { return W_2 | ((s & 1) << 20) | ((c >> 1) << 14) | ((c & 1) << 11); }
static __device__ __forceinline__ uint32_t w_mxa(int c, int s) { return W_2 | ((s & 1) << 20) | (1u << 13) | ((c >> 1) << 14) | ((c & 1) << 11); }
#define H1_V (1u << 13)

#define SPIN_LIMIT (1 << 18)

#define SM_X 0
#define SM_WOS 65536
#define SM_WVS 131072
#define SM_MEM 163840
#define SM_QKP 180224
#define SM_VP 184320
#define SM_CW 188416
#define SM_VST 196608
#define SM_VR 196608
#define SM_CQ 200704
#define SM_CV 208896
#define SM_XF 217088
#define SM_VL 221184
#define SM_OF 225280
#define SM_OX 227328
#define SM_PF 229376
#define SM_PX 230016
#define SM_RD 223232
#define SM_XS 231168
#define SM_BAR 231808
#define SM_Z 231936
#define SM_TS 232064
#define NTS 40
#define SM_TOTAL SM_TS
#define MB_F 0
#define MB_XE0 16
#define MB_XE1 112
#define MB_INIT 24
#define MB_MEM 32
#define MB_W 48
#define MB_XF 64
#define MB_VR 72
#define MB_X0 80
#define MB_WO 88
#define SM_SIDE (SM_BAR + 96)
#define MB_G 192
#define B_QK 1
#define B_V 2
#define B_P 3
#define B_O 4
#define B_O2 5
#define B_PUB 6
#define B_CQ 7
#define B_QK1 8
#define B_LD 9
#define B_PXF 10
#define B_CV 15
#define B_X2 11
#define B_PX 12
#define B_GO 14
#define B_G1 13

#define TST(a, b, c, d)
#define TSF(i, w)
#define TSP(i, w)
#define TVF(i, v)
#define TS(i)
#define TV(i, v)

static __device__ __forceinline__ void bar_sync(int id, int n) { asm volatile("bar.sync %0, %1;" :: "r"(id), "r"(n) : "memory"); }
static __device__ __forceinline__ void bar_arrive(int id, int n) { asm volatile("bar.arrive %0, %1;" :: "r"(id), "r"(n) : "memory"); }
static __device__ __forceinline__ uint4 ldg_r4(const void* p) { uint4 v;
  asm volatile("ld.relaxed.gpu.global.v4.u32 {%0,%1,%2,%3}, [%4];" : "=r"(v.x), "=r"(v.y), "=r"(v.z), "=r"(v.w) : "l"(p) : "memory"); return v; }
static __device__ __forceinline__ uint32_t ldg_r1(const void* p) { uint32_t v;
  asm volatile("ld.relaxed.gpu.global.u32 %0, [%1];" : "=r"(v) : "l"(p) : "memory"); return v; }
template <int OFF> static __device__ __forceinline__ uint32_t ldg_r1o(const void* p) { uint32_t v;
  asm volatile("ld.relaxed.gpu.global.u32 %0, [%1+%2];" : "=r"(v) : "l"(p), "n"(OFF) : "memory"); return v; }
static __device__ __forceinline__ void stg_r4(void* p, uint32_t a, uint32_t b, uint32_t c, uint32_t d) {
  asm volatile("st.relaxed.gpu.global.v4.u32 [%0], {%1,%2,%3,%4};" :: "l"(p), "r"(a), "r"(b), "r"(c), "r"(d) : "memory"); }
static __device__ __forceinline__ void stg_r2(void* p, uint32_t a, uint32_t b) {
  asm volatile("st.relaxed.gpu.global.v2.u32 [%0], {%1,%2};" :: "l"(p), "r"(a), "r"(b) : "memory"); }
static __device__ __forceinline__ uint2 ldg_r2(const void* p) { uint2 v;
  asm volatile("ld.relaxed.gpu.global.v2.u32 {%0,%1}, [%2];" : "=r"(v.x), "=r"(v.y) : "l"(p) : "memory"); return v; }
static __device__ __forceinline__ void stg_4(void* p, const uint4& v) {
  asm volatile("st.global.v4.u32 [%0], {%1,%2,%3,%4};" :: "l"(p), "r"(v.x), "r"(v.y), "r"(v.z), "r"(v.w) : "memory"); }
static __device__ __forceinline__ uint32_t f2u(float v) { return __float_as_uint(v); }
static __device__ __forceinline__ void stg_2(void* p, uint32_t a, uint32_t b) {
  asm volatile("st.global.v2.u32 [%0], {%1,%2};" :: "l"(p), "r"(a), "r"(b) : "memory"); }
static __device__ __forceinline__ void stg_r1(void* p, uint32_t a) {
  asm volatile("st.relaxed.gpu.global.u32 [%0], %1;" :: "l"(p), "r"(a) : "memory"); }
static __device__ __forceinline__ void sts128(uint32_t a, uint32_t x, uint32_t y, uint32_t z, uint32_t w) {
  asm volatile("st.shared.v4.u32 [%0], {%1,%2,%3,%4};" :: "r"(a), "r"(x), "r"(y), "r"(z), "r"(w) : "memory"); }
static __device__ __forceinline__ void sts128f(uint32_t a, float x, float y, float z, float w) {
  asm volatile("st.shared.v4.f32 [%0], {%1,%2,%3,%4};" :: "r"(a), "f"(x), "f"(y), "f"(z), "f"(w) : "memory"); }
static __device__ __forceinline__ uint4 lds128(uint32_t a) { uint4 v;
  asm volatile("ld.shared.v4.u32 {%0,%1,%2,%3}, [%4];" : "=r"(v.x), "=r"(v.y), "=r"(v.z), "=r"(v.w) : "r"(a) : "memory"); return v; }
static __device__ __forceinline__ float4 lds128f(uint32_t a) { float4 v;
  asm volatile("ld.shared.v4.f32 {%0,%1,%2,%3}, [%4];" : "=f"(v.x), "=f"(v.y), "=f"(v.z), "=f"(v.w) : "r"(a) : "memory"); return v; }
static __device__ __forceinline__ void sts32(uint32_t a, uint32_t x) { asm volatile("st.shared.u32 [%0], %1;" :: "r"(a), "r"(x) : "memory"); }
static __device__ __forceinline__ void sts64f(uint32_t a, float x, float y) { asm volatile("st.shared.v2.f32 [%0], {%1,%2};" :: "r"(a), "f"(x), "f"(y) : "memory"); }
static __device__ __forceinline__ uint2 lds64(uint32_t a) { uint2 v;
  asm volatile("ld.shared.v2.u32 {%0,%1}, [%2];" : "=r"(v.x), "=r"(v.y) : "r"(a) : "memory"); return v; }
static __device__ __forceinline__ void st_async4(uint32_t ra, float x, float y, float z, float w, uint32_t rbar) {
  asm volatile("st.async.weak.shared::cluster.mbarrier::complete_tx::bytes.v4.f32 [%0], {%1,%2,%3,%4}, [%5];"
               :: "r"(ra), "f"(x), "f"(y), "f"(z), "f"(w), "r"(rbar) : "memory"); }
static __device__ __forceinline__ void stsm4t(uint32_t a, uint32_t x, uint32_t y, uint32_t z, uint32_t w) {
  asm volatile("stmatrix.sync.aligned.m8n8.x4.trans.shared.b16 [%0], {%1,%2,%3,%4};" :: "r"(a), "r"(x), "r"(y), "r"(z), "r"(w) : "memory"); }
static __device__ __forceinline__ void stsm2t(uint32_t a, uint32_t x, uint32_t y) {
  asm volatile("stmatrix.sync.aligned.m8n8.x2.trans.shared.b16 [%0], {%1,%2};" :: "r"(a), "r"(x), "r"(y) : "memory"); }
static __device__ __forceinline__ uint32_t hfma2(uint32_t a, uint32_t b, uint32_t c) { uint32_t d;
  asm("fma.rn.f16x2 %0, %1, %2, %3;" : "=r"(d) : "r"(a), "r"(b), "r"(c)); return d; }
static __device__ __forceinline__ uint32_t hmax2(uint32_t a, uint32_t b) { uint32_t d;
  asm("max.f16x2 %0, %1, %2;" : "=r"(d) : "r"(a), "r"(b)); return d; }
static __device__ __forceinline__ uint32_t shfl_x(uint32_t a, int m) { uint32_t d;
  asm volatile("shfl.sync.bfly.b32 %0, %1, %2, 0x1f, 0xffffffff;" : "=r"(d) : "r"(a), "r"(m)); return d; }
static __device__ __forceinline__ void h2f(float& lo, float& hi, uint32_t a) {
  asm volatile("{\n.reg .b16 l, h;\nmov.b32 {l, h}, %2;\ncvt.f32.f16 %0, l;\ncvt.f32.f16 %1, h;\n}" : "=f"(lo), "=f"(hi) : "r"(a)); }
static __device__ __forceinline__ uint4 ldsm4(uint32_t a) { uint4 v;
  asm volatile("ldmatrix.sync.aligned.m8n8.x4.shared.b16 {%0,%1,%2,%3}, [%4];" : "=r"(v.x), "=r"(v.y), "=r"(v.z), "=r"(v.w) : "r"(a) : "memory"); return v; }
static __device__ __forceinline__ uint4 ldsm4t(uint32_t a) { uint4 v;
  asm volatile("ldmatrix.sync.aligned.m8n8.x4.trans.shared.b16 {%0,%1,%2,%3}, [%4];" : "=r"(v.x), "=r"(v.y), "=r"(v.z), "=r"(v.w) : "r"(a) : "memory"); return v; }
static __device__ __forceinline__ uint32_t movm(uint32_t a) { uint32_t d;
  asm volatile("movmatrix.sync.aligned.m8n8.trans.b16 %0, %1;" : "=r"(d) : "r"(a)); return d; }
static __device__ __forceinline__ float u2f(uint32_t v) { return __uint_as_float(v); }
static __device__ __forceinline__ uint32_t nz(uint32_t w) { return w == 0u ? 0x8000u : w; }
static __device__ __forceinline__ uint32_t tagw(uint32_t w, uint32_t t) { uint32_t d;
  asm("lop3.b32 %0, %1, %2, 1, 0xd8;" : "=r"(d) : "r"(w), "r"(t)); return d; }
static __device__ __forceinline__ uint32_t pack_m2(float lo, float hi, uint32_t t) { return tagw(pack_bf16(lo, hi), t); }
static __device__ __forceinline__ uint32_t pack_f16(float lo, float hi) { uint32_t d;
  asm("cvt.rn.satfinite.f16x2.f32 %0, %1, %2;" : "=r"(d) : "f"(hi), "f"(lo)); return d; }
static __device__ __forceinline__ void sum_h4(float& lo, float& hi, uint32_t a, uint32_t b, uint32_t c, uint32_t d) {
  const float2 x = __half22float2(*reinterpret_cast<__half2*>(&a)), y = __half22float2(*reinterpret_cast<__half2*>(&b));
  const float2 z = __half22float2(*reinterpret_cast<__half2*>(&c)), w = __half22float2(*reinterpret_cast<__half2*>(&d));
  lo = (x.x + y.x) + (z.x + w.x); hi = (x.y + y.y) + (z.y + w.y);
}
static __device__ __forceinline__ void add_q3(float& lo, float& hi, uint32_t a, uint32_t b, uint32_t c) {
  uint32_t t;
  asm("{\n.reg .b32 u;\nmul.rn.f16x2 u, %1, %4;\nfma.rn.f16x2 u, %2, %4, u;\nfma.rn.f16x2 %0, %3, %4, u;\n}" : "=r"(t) : "r"(a), "r"(b), "r"(c), "r"(0x34003400u));
  const float2 x = __half22float2(*reinterpret_cast<__half2*>(&t));
  lo += x.x; hi += x.y;
}
static __device__ __forceinline__ uint32_t lds32(uint32_t a) { uint32_t v; asm volatile("ld.shared.u32 %0, [%1];" : "=r"(v) : "r"(a) : "memory"); return v; }
static __device__ __forceinline__ uint32_t addb2(uint32_t a, uint32_t b) { uint32_t d;
  asm("add.rn.bf16x2 %0, %1, %2;" : "=r"(d) : "r"(a), "r"(b)); return d; }
static __device__ __forceinline__ uint32_t mulb2(uint32_t a, uint32_t b) { uint32_t d;
  asm("mul.rn.bf16x2 %0, %1, %2;" : "=r"(d) : "r"(a), "r"(b)); return d; }
static __device__ __forceinline__ uint32_t x3(uint32_t a, uint32_t b, uint32_t t) { uint32_t d;
  asm("lop3.b32 %0, %1, %2, %3, 0x7e;" : "=r"(d) : "r"(a), "r"(b), "r"(t)); return d; }
static __device__ __forceinline__ uint32_t or3(uint32_t a, uint32_t b, uint32_t c) { uint32_t d;
  asm("lop3.b32 %0, %1, %2, %3, 0xfe;" : "=r"(d) : "r"(a), "r"(b), "r"(c)); return d; }
static __device__ __forceinline__ uint32_t bad4(const uint4& u, uint32_t t) { return x3(u.x, u.y, t) | x3(u.z, u.w, t); }
static __device__ __forceinline__ uint32_t bad8(const uint4& u, const uint4& v, uint32_t t) {
  return or3(x3(u.x, u.y, t), x3(u.z, u.w, t), x3(v.x, v.y, t)) | x3(v.z, v.w, t); }
static __device__ __forceinline__ float ex2(float x) { float y; asm("ex2.approx.ftz.f32 %0, %1;" : "=f"(y) : "f"(x)); return y; }
static __device__ __forceinline__ float rcpf(float x) { float y; asm("rcp.approx.ftz.f32 %0, %1;" : "=f"(y) : "f"(x)); return y; }
static __device__ __forceinline__ void mbar_wait(uint32_t bar, int parity) {
  asm volatile("{\n.reg .pred p, q;\n.reg .u32 n;\nmbarrier.try_wait.parity.shared::cta.b64 p, [%0], %1;\n@p bra W_DONE;\nmov.u32 n, 0;\n"
               "W_LOOP:\nmbarrier.try_wait.parity.shared::cta.b64 p, [%0], %1;\nadd.u32 n, n, 1;\nsetp.lt.and.u32 q, n, %2, !p;\n@q bra W_LOOP;\nW_DONE:\n}"
               :: "r"(bar), "r"(parity), "n"(SPIN_LIMIT) : "memory");
}
static __device__ __forceinline__ uint32_t mbar_test(uint32_t bar, int parity) { uint32_t ok;
  asm volatile("{\n.reg .pred p;\nmbarrier.test_wait.parity.shared::cta.b64 p, [%1], %2;\nselp.u32 %0, 1, 0, p;\n}" : "=r"(ok) : "r"(bar), "r"(parity) : "memory"); return ok; }
static __device__ __forceinline__ void mbar_arrive(uint32_t bar) {
  asm volatile("mbarrier.arrive.shared::cta.b64 _, [%0];" :: "r"(bar) : "memory"); }
static __device__ __forceinline__ void mbar_arrive_cluster_rlx(uint32_t raddr) {
  asm volatile("mbarrier.arrive.relaxed.cluster.shared::cluster.b64 _, [%0];" :: "r"(raddr) : "memory"); }
static __device__ __forceinline__ void tma_load_mc(uint32_t dst, const CUtensorMap* tm, int c1, int c2, uint32_t bar) {
  asm volatile("cp.async.bulk.tensor.3d.shared::cluster.global.mbarrier::complete_tx::bytes.multicast::cluster [%0], [%1, {%3, %4, %5}], [%2], %6;"
               :: "r"(dst), "l"(tm), "r"(bar), "r"(0), "r"(c1), "r"(c2), "h"((uint16_t)3) : "memory"); }
static __device__ __forceinline__ void cp16(uint32_t dst, const void* src) {
  asm volatile("cp.async.cg.shared.global [%0], [%1], 16;" :: "r"(dst), "l"(src) : "memory"); }
static __device__ __forceinline__ void mma_1688(float (&d)[4], uint32_t a0, uint32_t a1, uint32_t b0) {
  asm volatile("mma.sync.aligned.m16n8k8.row.col.f32.bf16.bf16.f32 {%0,%1,%2,%3}, {%4,%5}, {%6}, {%0,%1,%2,%3};"
               : "+f"(d[0]), "+f"(d[1]), "+f"(d[2]), "+f"(d[3]) : "r"(a0), "r"(a1), "r"(b0)); }
static __device__ __forceinline__ void mma4(float (&d)[4], uint32_t a0, uint32_t a1, uint32_t a2, uint32_t a3, uint32_t b0, uint32_t b1) {
  asm volatile("mma.sync.aligned.m16n8k16.row.col.f32.bf16.bf16.f32 {%0,%1,%2,%3}, {%4,%5,%6,%7}, {%8,%9}, {%0,%1,%2,%3};"
               : "+f"(d[0]), "+f"(d[1]), "+f"(d[2]), "+f"(d[3]) : "r"(a0), "r"(a1), "r"(a2), "r"(a3), "r"(b0), "r"(b1)); }
static __device__ __forceinline__ void mma4z(float (&d)[4], uint32_t a0, uint32_t a1, uint32_t a2, uint32_t a3, uint32_t b0, uint32_t b1) {
  asm volatile("mma.sync.aligned.m16n8k16.row.col.f32.bf16.bf16.f32 {%0,%1,%2,%3}, {%4,%5,%6,%7}, {%8,%9}, {%10,%10,%10,%10};"
               : "=f"(d[0]), "=f"(d[1]), "=f"(d[2]), "=f"(d[3]) : "r"(a0), "r"(a1), "r"(a2), "r"(a3), "r"(b0), "r"(b1), "f"(0.f)); }
static __device__ __forceinline__ void mma4h(float (&d)[4], uint32_t a0, uint32_t a1, uint32_t a2, uint32_t a3, uint32_t b) {
  asm volatile("mma.sync.aligned.m16n8k16.row.col.f32.f16.f16.f32 {%0,%1,%2,%3}, {%4,%5,%6,%7}, {%8,%8}, {%0,%1,%2,%3};"
               : "+f"(d[0]), "+f"(d[1]), "+f"(d[2]), "+f"(d[3]) : "r"(a0), "r"(a1), "r"(a2), "r"(a3), "r"(b)); }
static __device__ __forceinline__ void mma2h(float (&d)[4], uint32_t a0, uint32_t a1, uint32_t b) {
  asm volatile("mma.sync.aligned.m16n8k8.row.col.f32.f16.f16.f32 {%0,%1,%2,%3}, {%4,%5}, {%6}, {%0,%1,%2,%3};"
               : "+f"(d[0]), "+f"(d[1]), "+f"(d[2]), "+f"(d[3]) : "r"(a0), "r"(a1), "r"(b)); }
static __device__ __forceinline__ uint32_t clk32() { uint32_t t; asm volatile("mov.u32 %0, %%clock;" : "=r"(t)); return t; }
static __device__ __forceinline__ uint32_t gt32() { uint32_t t; asm volatile("mov.u32 %0, %%globaltimer_lo;" : "=r"(t)); return t; }
static __device__ __forceinline__ void spin(int clk) { if (clk > 0) { uint32_t t = clk32(); while (clk32() - t < (uint32_t)clk) {} } }
#define FENCE() asm volatile("griddepcontrol.launch_dependents;" ::: "memory")
#define OPAQUE_L(p) asm volatile("" : "+l"(p))
#define OPAQUE_R(p) asm volatile("" : "+r"(p))

template <int KK, int K1, int W0, int NW, int FIRST> struct XR {
  static __device__ __forceinline__ void run(float (&d)[16], const uint32_t (&w)[NW][4], uint32_t b16) {
    wgmma_n32_ra<(KK >> 2) * 4096 + (KK & 3) * 32, !FIRST>(d, w[W0 + KK], b16);
    XR<KK + 1, K1, W0, NW, 0>::run(d, w, b16);
  }
};
template <int K1, int W0, int NW, int FIRST> struct XR<K1, K1, W0, NW, FIRST> { static __device__ __forceinline__ void run(float (&)[16], const uint32_t (&)[NW][4], uint32_t) {} };
template <int KK, int K0, int K1, int FIRST> struct XS {
  static __device__ __forceinline__ void run(float (&d)[16], uint32_t a16, uint32_t b16) {
    wgmma_n32_ss_ta<(KK - K0) * 2048, (KK >> 2) * 4096 + (KK & 3) * 32, !FIRST>(d, a16, b16);
    XS<KK + 1, K0, K1, 0>::run(d, a16, b16);
  }
};
template <int K0, int K1, int FIRST> struct XS<K1, K0, K1, FIRST> { static __device__ __forceinline__ void run(float (&)[16], uint32_t, uint32_t) {} };

static __device__ bf16 g_h[8 * FF];
static __device__ unsigned int g_sbar;
struct SideParams { const bf16* x; const bf16* w_r; const bf16* w_gate; const bf16* w_up; const bf16* w_down; const bf16* gate_w; const bf16* Wo; };

static __device__ __forceinline__ void side_barrier(unsigned int target) {
  __syncthreads();
  if (threadIdx.x == 0) {
    __threadfence();
    atomicAdd(&g_sbar, 1u);
    int n = 0;
    while (*(volatile unsigned int*)&g_sbar < target) { if (++n > (1 << 22)) { g_err = 50; break; } }
    __threadfence();
  }
  __syncthreads();
}
static __device__ __forceinline__ uint4 ldg_nc(const void* p) { uint4 v;
  asm volatile("ld.global.nc.L1::no_allocate.v4.u32 {%0,%1,%2,%3}, [%4];" : "=r"(v.x), "=r"(v.y), "=r"(v.z), "=r"(v.w) : "l"(p)); return v; }
#define SPD 3
static __device__ __forceinline__ void l2pf(const void* p) { asm volatile("prefetch.global.L2 [%0];" :: "l"(p)); }
static __device__ __forceinline__ void mm8(float (&acc)[8][4], const bf16* W, const bf16* Wn, int ldw, int nk16, uint32_t abase, int lane) {
  const int g = lane >> 2, t = lane & 3;
  const bf16* wp = W + (size_t)(2 * t) * ldw + g * 8;
#pragma unroll 1
  for (int k = 0; k < nk16; k += 4) {
    {
      const int kp = k + 4 * SPD;
      const bf16* pf = kp < nk16 ? W + (size_t)(kp * 16) * ldw : Wn ? Wn + (size_t)((kp - nk16) * 16) * ldw : nullptr;
      if (pf) { l2pf(pf + (size_t)lane * ldw); l2pf(pf + (size_t)(lane + 32) * ldw); }
    }
    uint4 r[4][4];
#pragma unroll
    for (int u = 0; u < 4; u++) {
      const bf16* q = wp + (size_t)(k + u) * 16 * ldw;
      r[u][0] = ldg_nc(q); r[u][1] = ldg_nc(q + ldw); r[u][2] = ldg_nc(q + 8 * ldw); r[u][3] = ldg_nc(q + 9 * ldw);
    }
#pragma unroll
    for (int u = 0; u < 4; u++) {
      uint32_t a0, a2;
      asm volatile("ld.shared.u32 %0, [%1];" : "=r"(a0) : "r"(abase + (k + u) * 32));
      asm volatile("ld.shared.u32 %0, [%1];" : "=r"(a2) : "r"(abase + (k + u) * 32 + 16));
      const uint32_t* p0 = reinterpret_cast<const uint32_t*>(&r[u][0]); const uint32_t* p1 = reinterpret_cast<const uint32_t*>(&r[u][1]);
      const uint32_t* p2 = reinterpret_cast<const uint32_t*>(&r[u][2]); const uint32_t* p3 = reinterpret_cast<const uint32_t*>(&r[u][3]);
#pragma unroll
      for (int i = 0; i < 8; i++) {
        const uint32_t sel = (i & 1) ? 0x7632u : 0x5410u;
        mma4(acc[i], a0, 0u, a2, 0u, __byte_perm(p0[i >> 1], p1[i >> 1], sel), __byte_perm(p2[i >> 1], p3[i >> 1], sel));
      }
    }
  }
}
static __device__ __noinline__ void side_work(const SideParams& P, unsigned char* smem, int q) {
  const int tid = threadIdx.x, lane = tid & 31, warp = tid >> 5, g = lane >> 2, t = lane & 3;
  const uint32_t sb = smem_u32(smem);
  unsigned int* cand = reinterpret_cast<unsigned int*>(smem);
  bf16* xs = reinterpret_cast<bf16*>(smem + 1024);
  float* part = reinterpret_cast<float*>(smem + 65536);
  {
    for (int i = tid; i < 256; i += 384) *reinterpret_cast<uint4*>(smem + 1024 + i * 16) = ldg_nc((i < 128 ? P.gate_w : P.w_r - DM) + i * 8);
    __syncthreads();
#pragma unroll 1
    for (int it = warp; it < 64; it += 12) {
      const bf16* xp = P.x + (size_t)(q * 512 + (it >> 1) * 16 + g) * DM + (it & 1) * 512 + t * 8;
      for (int a = it == warp ? 0 : 1; a < 2 && it + 12 * a < 64; a++)
#pragma unroll
        for (int i = 0; i < 4; i++) l2pf(P.x + (size_t)(q * 512 + (it >> 1) * 16 + a * 96 + i * 4 + (lane >> 3)) * DM + (it & 1) * 512 + (lane & 7) * 64);
      uint4 lo[16], hi[16];
#pragma unroll
      for (int i = 0; i < 16; i++) { lo[i] = ldg_nc(xp + i * 32); hi[i] = ldg_nc(xp + 8 * DM + i * 32); }
      float sg[4] = {0.f, 0.f, 0.f, 0.f}, sr[4] = {0.f, 0.f, 0.f, 0.f};
#pragma unroll
      for (int i = 0; i < 16; i++) {
        const uint4 gw = lds128(sb + 1024 + (it & 1) * 1024 + i * 64 + t * 16), wr = lds128(sb + 3072 + (it & 1) * 1024 + i * 64 + t * 16);
        mma4(sr, lo[i].x, hi[i].x, lo[i].y, hi[i].y, wr.x, wr.y); mma4(sr, lo[i].z, hi[i].z, lo[i].w, hi[i].w, wr.z, wr.w);
        mma4(sg, mulb2(lo[i].x, gw.x), mulb2(hi[i].x, gw.x), mulb2(lo[i].y, gw.y), mulb2(hi[i].y, gw.y), 0x3F803F80u, 0x3F803F80u);
        mma4(sg, mulb2(lo[i].z, gw.z), mulb2(hi[i].z, gw.z), mulb2(lo[i].w, gw.w), mulb2(hi[i].w, gw.w), 0x3F803F80u, 0x3F803F80u);
      }
      if (t == 0) {
        float* pp = part + (it & 1) * 1024 + (it >> 1) * 16 + g;
        pp[0] = sg[0]; pp[8] = sg[2]; pp[512] = sr[0]; pp[520] = sr[2];
      }
    }
    __syncthreads();
    for (int i = tid; i < 512; i += 384) {
      g_gate[q * 512 + i] = rbf(1.f / (1.f + expf(-rbf(part[i] + part[1024 + i]))));
      g_r[q * 512 + i] = rbf(part[512 + i] + part[1536 + i]);
    }
  }
#define GU(u) (((u) % 28) / 14 ? P.w_up : P.w_gate) + (size_t)((u) / 28) * 512 * FF + q * 896 + ((u) % 14) * 64
  for (int i = lane; i < 64 * SPD; i += 32) l2pf(GU(warp) + (size_t)i * FF);
  side_barrier(4);
  {
    unsigned int key[8];
#pragma unroll
    for (int i = 0; i < 8; i++) {
      const int tok = (warp & 7) * 256 + i * 32 + lane;
      const uint32_t b = __float_as_uint(__ldcg(&g_r[tok]) + 0.f) >> 16;
      key[i] = (((b & 0x8000u) ? (~b & 0xffffu) : (b | 0x8000u)) << 16) | (uint32_t)(2047 - tok);
    }
    for (int pass = 0; pass < 2; pass++) {
      if (pass == 0 ? warp < 8 : warp == 0) {
        for (int c = 0; c < 8; c++) {
          const unsigned int m = __reduce_max_sync(~0u, max(max(max(key[0], key[1]), max(key[2], key[3])), max(max(key[4], key[5]), max(key[6], key[7]))));
#pragma unroll
          for (int i = 0; i < 8; i++) if (key[i] == m) key[i] = 0u;
          if (lane == 0) cand[pass ? 128 + c : warp * 8 + c] = m;
        }
      }
      __syncthreads();
      if (pass == 0 && warp == 0) {
#pragma unroll
        for (int i = 0; i < 8; i++) key[i] = i < 2 ? cand[i * 32 + lane] : 0u;
      }
    }
    if (q == 0 && tid < 8) g_idx[tid] = 2047 - (int)(cand[128 + tid] & 0xffffu);
    for (int i = tid; i < 1024; i += 384) {
      const int c = i >> 7, tok = 2047 - (int)(cand[128 + c] & 0xffffu);
      *reinterpret_cast<uint4*>(xs + c * (FF + 8) + (i & 127) * 8) = ldg_nc(P.x + (size_t)tok * DM + (i & 127) * 8);
    }
    __syncthreads();
  }
  const uint32_t abase = sb + 1024 + g * (FF + 8) * 2 + t * 4;
  for (int u = warp; u < 56; u += 12) {
    const int kh = u / 28, mat = (u % 28) / 14, cb = u % 14;
    float acc[8][4];
#pragma unroll
    for (int i = 0; i < 8; i++) acc[i][0] = acc[i][1] = acc[i][2] = acc[i][3] = 0.f;
    mm8(acc, GU(u), u + 12 < 56 ? GU(u + 12) : nullptr, FF, DM / 32, abase + kh * 1024, lane);
    float* pp = part + ((kh * 2 + mat) * 8 + g) * 896 + cb * 64 + 16 * t;
#pragma unroll
    for (int i = 0; i < 8; i++) { pp[i] = acc[i][0]; pp[8 + i] = acc[i][1]; }
  }
  for (int i = lane; i < 64 * SPD; i += 32) l2pf(P.w_down + (size_t)((warp >> 2) * 1216 + i) * DM + q * 256 + (warp & 3) * 64);
  __syncthreads();
  for (int i = tid; i < 8 * 896; i += 384) {
    const float ag = rbf(part[i] + part[16 * 896 + i]), au = rbf(part[8 * 896 + i] + part[24 * 896 + i]);
    g_h[(i / 896) * FF + q * 896 + i % 896] = __float2bfloat16(rbf(ag / (1.f + expf(-ag))) * au);
  }
  side_barrier(8);
  for (int i = tid; i < 8 * FF / 8; i += 384) {
    const int c = i / (FF / 8), o = i % (FF / 8);
    *reinterpret_cast<uint4*>(xs + c * (FF + 8) + o * 8) = __ldcg(reinterpret_cast<const uint4*>(g_h + c * FF + o * 8));
  }
  __syncthreads();
  {
    const int cb = warp & 3, kq = warp >> 2;
    float acc[8][4];
#pragma unroll
    for (int i = 0; i < 8; i++) acc[i][0] = acc[i][1] = acc[i][2] = acc[i][3] = 0.f;
    mm8(acc, P.w_down + (size_t)kq * 1216 * DM + q * 256 + cb * 64, nullptr, DM, kq == 2 ? 72 : 76, abase + kq * 1216 * 2, lane);
#pragma unroll
    for (int i = 0; i < 8; i++) { part[(kq * 8 + g) * 256 + cb * 64 + 16 * t + i] = acc[i][0]; part[(kq * 8 + g) * 256 + cb * 64 + 16 * t + 8 + i] = acc[i][1]; }
    __syncthreads();
    for (int i = tid; i < 2048; i += 384) {
      const int c = i >> 8, tok = 2047 - (int)(cand[128 + c] & 0xffffu);
      const float y = (part[i] + part[2048 + i]) + part[4096 + i];
      const float rs = rbf(1.f / (1.f + expf(-__ldcg(&g_r[tok]))));
      g_upd[c * DM + q * 256 + (i & 255)] = __float2bfloat16(rbf(y) * rs);
    }
  }
}
struct RecParams { const bf16* mem0; unsigned char* win; };
struct WMaps { CUtensorMap q, k, v; };
#define RLX 1
#define DLY_SIDE 16000
#define WSPL 1

#define DLY_S 230
#define DLY_V 350
#define DLY_M3 480
#define RF_FAT 208
#define RF_CTL 88
#define NCH 2
#define WPF 7
#define WRF 7
#define VPF 2
#define DLY_WO 860
#define XPF 4
#define DLY_FA 50
#define DLY_XL 80
#define NPROBE 3
#define GW 0
#define BI 0
#define BR 8
#define BG 1
#define VI 1
#define DLY_VI 0
#define F0W 0
#define DLY_B 0
#define BGT 0
#define EG 0
#define W0I 0
#define XH 1
#define F1L 1
#define QB 0
#define LN 0
#define NSW 0
#define EPI 0
#define PXE 0
#define GF 12
#define WNS -1
#define DLY_NW 180
#define ETW 0
#define KB 6
#define H16 1
#define DLY_N 0
#define F1C 2
#define KA 0
#define KEEP() do { float kd[4]; mma4z(kd, 0u, 0u, 0u, 0u, 0u, 0u); } while (0)
#define WKA 8
#define WPA 4
#define F0T 1
#define DLY_K 1344
#define DLY_KS 964
#define DLY_E 0
#define DLY_PF 10
#define DLY_F0 300
#define DLY_XD 200
#define DLY_PX 80
#define DLY_TB 700
#define NTUNE 10
#define TUNE_NAMES {"OM3", "XL", "S", "NW", "WO", "PX", "V", "OK", "OKS", "XD"}
__constant__ int g_tune[NTUNE] = {DLY_M3, DLY_XL, DLY_S, DLY_NW, DLY_WO, DLY_PX, DLY_V, DLY_K, DLY_KS, DLY_XD};
#undef DLY_M3
#define DLY_M3 g_tune[0]
#undef DLY_XL
#define DLY_XL g_tune[1]
#undef DLY_S
#define DLY_S g_tune[2]
#undef DLY_NW
#define DLY_NW g_tune[3]
#undef DLY_WO
#define DLY_WO g_tune[4]
#undef DLY_PX
#define DLY_PX g_tune[5]
#undef DLY_V
#define DLY_V g_tune[6]
#undef DLY_K
#define DLY_K g_tune[7]
#undef DLY_XD
#define DLY_XD g_tune[9]
#undef DLY_KS
#define DLY_KS g_tune[8]
#define PRB(i)
#define ADD3(a, b, c) addb2(addb2(a, c), b)
#define STR2(x) #x
#define STR(x) STR2(x)

static __device__ __forceinline__ void cp16p(uint32_t dst, const void* src, uint32_t v) {
  asm volatile("{\n.reg .pred q;\nsetp.ne.u32 q, %2, 0;\n@q cp.async.cg.shared.global [%0], [%1], 16;\n}" :: "r"(dst), "l"(src), "r"(v) : "memory"); }
static __device__ __forceinline__ void red_bf2(void* p, uint32_t v) {
  asm volatile("red.relaxed.gpu.global.add.noftz.bf16x2 [%0], %1;" :: "l"(p), "r"(v) : "memory"); }
static __device__ __forceinline__ void red_bf2p(void* p, uint32_t v, uint32_t e) {
  asm volatile("{\n.reg .pred q;\nsetp.lt.u32 q, %2, 2;\n@q red.relaxed.gpu.global.add.noftz.bf16x2 [%0], %1;\n}" :: "l"(p), "r"(v), "r"(e) : "memory"); }
static __device__ __forceinline__ void red_bf2p4(void* p, uint32_t v, uint32_t e) {
  asm volatile("{\n.reg .pred q;\nsetp.lt.u32 q, %2, 4;\n@q red.relaxed.gpu.global.add.noftz.bf16x2 [%0], %1;\n}" :: "l"(p), "r"(v), "r"(e) : "memory"); }
static __device__ __forceinline__ void sts16(uint32_t a, uint32_t x) { asm volatile("{\n.reg .b16 h;\ncvt.u16.u32 h, %1;\nst.shared.u16 [%0], h;\n}" :: "r"(a), "r"(x) : "memory"); }
static __device__ __forceinline__ uint32_t cnt_word(uint32_t L) { return (L & 17u) | ((L & 6u) << 1) | ((L & 8u) >> 2); }
static __device__ __forceinline__ uint32_t cnt_line(uint32_t l) { return (l & 17u) | ((l & 12u) >> 1) | ((l & 2u) << 2); }
static __device__ __forceinline__ int m3_check(uint32_t sb, const unsigned char* p3, const unsigned char* pd, int dq, uint32_t l16, uint32_t mc, int hf, int par) {
  const uint32_t md = l16 + (sb + SM_MEM + hf * 8192), dd = l16 + (sb + SM_RD + hf * 256), dc = (l16 >> 2) + (sb + SM_RD + hf * 256);
  int n = 0;
  uint32_t c0 = 0, c1 = 0, d0 = 0, d1 = 0;
#pragma unroll 1
  do {
    if (n) {
      const int src = cnt_word(l16 >> 4);
      const uint32_t m0 = __ballot_sync(~0u, (__shfl_sync(~0u, c0, src) >> 16) != 0x4200u) >> (l16 >> 7), m1 = __ballot_sync(~0u, (__shfl_sync(~0u, c1, src) >> 16) != 0x4200u) >> (l16 >> 7);
      const uint32_t m2 = __ballot_sync(~0u, (d0 >> 16) != 0x4200u), m3 = __ballot_sync(~0u, (d1 >> 16) != 0x4200u);
#pragma unroll
      for (int i = 0; i < 8; i++) { cp16p(md + i * 512, p3 + i * 1024, m0 & (1u << (4 * i))); cp16p(md + 4096 + i * 512, p3 + dq + i * 1024, m1 & (1u << (4 * i))); }
      cp16p(dd, pd, l16 < 256u ? (((l16 & 128u) ? m3 : m2) >> ((l16 >> 2) & 28u)) & 15u : 0u);
      asm volatile("cp.async.commit_group;\ncp.async.wait_group 0;" ::: "memory");
      __syncwarp();
    }
    n++;
    mbar_wait(sb + SM_BAR + MB_G + hf * 8, par);
    c0 = lds32(mc); c1 = lds32(mc + 4096); d0 = lds32(dc); d1 = lds32(dc + 128);
  } while (__any_sync(~0u, (x3(c0, c1, 0x42000000u) | x3(d0, d1, 0x42000000u)) >= 0x10000u) && n < SPIN_LIMIT);
  PRB(4);
  sts16(mc + 2, d0); sts16(mc + 4098, d1);
  mbar_arrive(sb + SM_BAR + MB_MEM + hf * 8);
  return n - 1;
}

__global__ void __cluster_dims__(2, 1, 1) __launch_bounds__(384, 1)
rec_kernel(const __grid_constant__ CUtensorMap tmx, const __grid_constant__ CUtensorMap tmw, const __grid_constant__ WMaps W, RecParams P, const __grid_constant__ SideParams SP) {
  extern __shared__ __align__(1024) unsigned char smem[];
  asm volatile("griddepcontrol.launch_dependents;");
  const uint32_t sb = smem_u32(smem);
  const int tid = threadIdx.x, lane = tid & 31, t128 = tid & 127;
  const int wg = __shfl_sync(~0u, tid >> 7, 0), wq = __shfl_sync(~0u, (tid >> 5) & 3, 0);
  const int r = blockIdx.x & 1, pp = blockIdx.x >> 1;
  const int mi = lane >> 3, r8 = lane & 7;
  const uint32_t xb16 = __shfl_sync(~0u, (((sb + SM_X + (tid >> 7) * 32768 + r * 16384) & 0x3FFFF) >> 4) | (1u << 16), 0);
  const uint32_t va16 = __shfl_sync(~0u, (((sb + SM_WVS + (tid >> 7) * 16384) & 0x3FFFF) >> 4) | (64u << 16), 0);

  if (tid == 0) {
    mbar_init(sb + SM_BAR + MB_F, BGT == 2 ? 8 : BGT == 1 ? 4 : 1); mbar_init(sb + SM_BAR + MB_F + 8, 1); mbar_init(sb + SM_BAR + MB_XE0, 2); mbar_init(sb + SM_BAR + MB_XE1, 2); mbar_init(sb + SM_BAR + MB_INIT, 2);
    mbar_init(sb + SM_BAR + MB_MEM, 32); mbar_init(sb + SM_BAR + MB_MEM + 8, 32); mbar_init(sb + SM_BAR + MB_W, 1); mbar_init(sb + SM_BAR + MB_W + 8, 1);
    mbar_init(sb + SM_BAR + MB_XF, 8); mbar_init(sb + SM_BAR + MB_X0, 1); mbar_init(sb + SM_BAR + MB_WO, 1); mbar_init(sb + SM_BAR + MB_VR, 5); mbar_init(sb + SM_BAR + MB_G, 32); mbar_init(sb + SM_BAR + MB_G + 8, 32);
    asm volatile("fence.mbarrier_init.release.cluster;" ::: "memory");
  }
  if (tid == 32) {
    asm volatile("prefetch.tensormap [%0];" :: "l"(&W.q) : "memory"); asm volatile("prefetch.tensormap [%0];" :: "l"(&W.k) : "memory");
    asm volatile("prefetch.tensormap [%0];" :: "l"(&W.v) : "memory"); asm volatile("prefetch.tensormap [%0];" :: "l"(&tmx) : "memory");
  }
  if (tid >= 256 && tid < 320) {
    unsigned char* pl = P.win + r * W_2 + (W_UP | (1u << 19) | ((pp >> 5) << 14)) + (pp & 31) * 128 + wq * 4096;
    stg_r1(pl + lane * 4, 0u);
    uint32_t best = 1u << 30, acc = 0;
#pragma unroll 1
    for (int rep = 0; rep < NPROBE; rep++) {
      uint32_t v = 0, t1; const uint32_t t0 = clk32();
      if (lane == 0) asm volatile("atom.relaxed.gpu.global.add.u32 %0, [%1], 2;" : "=r"(v) : "l"(pl + acc) : "memory");
      acc = v >> 31;
      asm volatile("{\n.reg .u32 x;\nadd.u32 x, %1, 0;\nmov.u32 %0, %%clock;\n}" : "=r"(t1) : "r"(acc));
      best = min(best, t1 - t0 + acc);
    }
    if (lane == 0) sts32(sb + SM_SIDE + wq * 4, best);
    bar_sync(B_P, 64);
    if (wq == 0) {
      const uint2 bt = lds64(sb + SM_SIDE);
      if (lane < 8 && (r == 0 || pp == 0)) stg_r1(&g_side[(r ? 66 : pp) * 32 + lane], 2u | (bt.x < bt.y ? 1u : 0u));
      spin(DLY_TB);
      uint32_t a, b, c; int n = 0;
#pragma unroll 1
      do {
        a = ldg_r1(&g_side[lane * 32]); b = ldg_r1(&g_side[(32 + lane) * 32]); c = ldg_r1(&g_side[(64 + min(lane, 2)) * 32]);
      } while (!__all_sync(~0u, a & b & c & 2u) && ++n < SPIN_LIMIT);
      a = __ballot_sync(~0u, a & 1u); b = __ballot_sync(~0u, b & 1u); c = __ballot_sync(~0u, c & 1u);
      const uint32_t pol2 = (a ^ (c >> 2)) & 1u;
      c &= 3u;
      const unsigned long long ab = ((unsigned long long)b << 32) | a;
      const int sd = pp < 64 ? (int)(ab >> pp) & 1 : (int)(c >> (pp - 64)) & 1;
      const int n1 = __popcll(ab) + __popc(c), n0 = 66 - n1;
      const int below1 = pp < 64 ? __popcll(ab & ((1ull << pp) - 1)) : __popcll(ab) + (pp == 65 ? (int)(c & 1u) : 0);
      const int rk = sd ? below1 : pp - below1;
      const int k0 = (n0 & 1) ? n0 - 1 : n0 >= n1 ? n0 - 2 : n0, k1 = 64 - k0;
      const int role = rk >= (sd ? k1 : k0) ? 64 + ((n0 & 1) ? sd : rk - (sd ? k1 : k0)) : sd ? k0 + rk : rk;
      __syncwarp();
      if (lane == 0) sts128(sb + SM_SIDE, 2 * k0, 0u, pol2, role * 2 + r);
    }
  }
  __syncthreads();
  const int cta = __shfl_sync(~0u, (int)lds32(sb + SM_SIDE + 12), 0), h = cta >> 2, j = cta & 3, p = j >> 1;
  const int sw = (cta >= __shfl_sync(~0u, (int)lds32(sb + SM_SIDE), 0) ? 1 : 0) ^ r ^ NSW;
  if (cta >= NCTA) {
    spin(DLY_SIDE);
    side_work(SP, smem, cta - NCTA);
    return;
  }
  asm volatile("barrier.cluster.arrive.relaxed.aligned;" ::: "memory");
#define WLOAD(i0, i1) _Pragma("unroll 1") for (int u = i0; u < i1; u++) {        \
    const int g2 = u >> 2, i = u & 3, k = g2 * 512 + ((i * 128 + r * 256) & 511); \
    const uint32_t mb = sb + SM_BAR + MB_W + g2 * 8; \
    tma_load_2d(sb + g2 * 65536 + i * 8192, &W.q, h * DH + j * 32, k, mb); \
    tma_load_2d(sb + g2 * 65536 + 32768 + i * 8192, &W.k, h * DH + j * 32, k, mb); \
    if (i < 2) tma_load_2d(sb + (i ? SM_WVS : SM_VST) + g2 * 16384, &W.v, h * DH + p * 64, k, mb); }
  if (tid == 288) {
    mbar_expect_tx(sb + SM_BAR + MB_X0, 32768);
#pragma unroll 1
    for (int i = 0; i < 2; i++)
      asm volatile("cp.async.bulk.tensor.3d.shared::cluster.global.mbarrier::complete_tx::bytes [%0], [%1, {%3, %3, %4}], [%2];"
                   :: "r"(sb + SM_MEM + i * 16384), "l"(&tmx), "r"(sb + SM_BAR + MB_X0), "r"(0), "r"(i * 4) : "memory");
    mbar_expect_tx(sb + SM_BAR + MB_W, 98304); mbar_expect_tx(sb + SM_BAR + MB_W + 8, 98304);
    WLOAD(0, 4 + WSPL);
  }
  __syncwarp();
  asm volatile("barrier.cluster.wait.acquire.aligned;" ::: "memory");
#define SIDES() const uint4 sm2 = lds128(sb + SM_SIDE); const int nlo = sm2.x; const uint32_t me = cta >= nlo

#define XLOAD(t, sg) tma_load_mc(sb + SM_X + ((t) * 8 + r * 4) * 4096, &tmx, (sg) * SEG, (t) * 8 + r * 4, sb + SM_BAR + MB_F + (t) * 8)
#define F0LOAD() do { mbar_wait(sb + SM_BAR + MB_XE0, s & 1); \
    if (l16 == 0) XLOAD(0, s + 2); \
    __syncwarp(); } while (0)
  if (wg < 2) {
    asm volatile("setmaxnreg.inc.sync.aligned.u32 " STR(RF_FAT) ";");
    uint32_t w[32][4], wv[8][4];
    uint32_t lm = ((mi >> 1) * 8 + r8) * 128 + (((wq * 2 + (mi & 1)) ^ r8) << 4), l16 = lane * 16;
    lm = __shfl_sync(~0u, lm, lane); l16 = __shfl_sync(~0u, l16, lane);
    mbar_wait(sb + SM_BAR + MB_W + wg * 8, 0);
    {
      const uint32_t lq0 = sb + wg * 65536 + (wq >> 1) * 32768 + ((mi >> 1) * 8 + r8) * 64 + ((((wq & 1) * 2 + (mi & 1)) ^ (r8 >> 1)) << 4);
#pragma unroll
      for (int kk = 0; kk < 32; kk++) ldmatrix_x4_trans(w[kk], lq0 + kk * 1024);
    }
#pragma unroll
    for (int kk = 0; kk < 8; kk++) ldmatrix_x4_trans(wv[kk], sb + SM_VST + wg * 16384 + kk * 2048 + lm);
    if (wg == 0) bar_sync(B_V, 160);
    else bar_arrive(B_P, 224);
    const int w8 = wg * 4 + wq;
    const int cw = sw ^ wg, near = wg ^ 1 ^ NSW;
    const uint32_t xh16 = xb16 ^ 1024u;
    const uint32_t rsb = mapa(sb, r ^ 1);
#define MT (l16 + (sb + SM_MEM + wg * 8192))
#define WA (lm + (sb + SM_WVS + wg * 16384))
#define WOF(f) (lm + (sb + SM_WOS + wg * 32768 + ((f) & 1) * 16384 + ((f) >> 1) * 2048))
#define TH(base) (l16 + (sb + (base) + w8 * 512))
#define TQ(base) (l16 + (sb + (base) + wq * 512))
#define DUMP(base) _Pragma("unroll") for (int n = 0; n < 4; n++) sts128f(TQ((base) + n * 2048), d[4 * n], d[4 * n + 1], d[4 * n + 2], d[4 * n + 3])
#define INIT(base) _Pragma("unroll") for (int n = 0; n < 4; n++) { const float4 t = lds128f(TQ((base) + n * 2048)); d[4 * n] = t.x; d[4 * n + 1] = t.y; d[4 * n + 2] = t.z; d[4 * n + 3] = t.w; }
#define XQK(first, b0, b1) do { wg_fence(); XR<0, 16, 0, 32, first>::run(d, w, b0); XR<0, 16, 16, 32, 0>::run(d, w, b1); wg_commit(); wg_wait0(); } while (0)
#define XVS(first, b0) do { wg_fence(); XS<8, 8, 16, first>::run(d, va16, b0); XR<0, 8, 0, 8, 0>::run(d, wv, b0); wg_commit(); wg_wait0(); } while (0)
#define XVR(first, b0) do { wg_fence(); XR<0, 8, 0, 8, first>::run(d, wv, b0); XS<8, 8, 16, 0>::run(d, va16, b0); wg_commit(); wg_wait0(); } while (0)
#define XREL(mb) do { if (wq == 0 && l16 == 0) { mbar_arrive_cluster_rlx(rsb + SM_BAR + (mb)); mbar_arrive(sb + SM_BAR + (mb)); } } while (0)
#define XFOUT() do { \
          _Pragma("unroll") for (int hf = 0; hf < 2; hf++) \
            stsm4t(l16 + (sb + SM_XF + (wq * 2 + hf) * 512), pack_bf16(d[8 * hf], d[8 * hf + 1]), pack_bf16(d[8 * hf + 2], d[8 * hf + 3]), \
                   pack_bf16(d[8 * hf + 4], d[8 * hf + 5]), pack_bf16(d[8 * hf + 6], d[8 * hf + 7])); \
          __syncwarp(); \
          if (l16 < 32) mbar_arrive(sb + SM_BAR + MB_XF); } while (0)
#define ADDIN(base) _Pragma("unroll") for (int n = 0; n < 4; n++) { const float4 t = lds128f(TQ((base) + n * 2048)); d[4 * n] += t.x; d[4 * n + 1] += t.y; d[4 * n + 2] += t.z; d[4 * n + 3] += t.w; }
    if (wg == 0) {
      float d[16];
      const uint32_t x0 = (((sb + SM_MEM + r * 16384) & 0x3FFFF) >> 4) | (1u << 16), x1 = (((sb + SM_MEM + (r ^ 1) * 16384) & 0x3FFFF) >> 4) | (1u << 16);
      mbar_wait(sb + SM_BAR + MB_X0, 0);
      XQK(1, x0, x1);
      DUMP(SM_CQ);
      XVS(1, x0);
      bar_sync(B_CQ, 256);
      DUMP(SM_CV);
      bar_sync(B_X2, 384);
    } else {
      float d[16];
      bar_sync(B_CQ, 256);
      INIT(SM_CQ);
      bar_sync(B_X2, 384);
      mbar_wait(sb + SM_BAR + MB_F + 8, 0);
      XQK(0, xb16, xh16);
      XFOUT();
    }
    if (wg == 0) mbar_wait(sb + SM_BAR + MB_F, 0);
    for (int s = 0;; s++) {
      OPAQUE_R(lm); OPAQUE_R(l16);
      if (wg || s < NSEG - 1) {
        float d[16];
        const uint32_t cv = ((s ^ wg) & 1) ? SM_CV : SM_CW;
        PRB(2 + wg);
        spin(DLY_B);
        TSP(9, 1);

        wg_fence(); XR<0, BR, 0, 8, 1>::run(d, wv, xb16); XS<8, 8, 16, BR == 0>::run(d, va16, xb16); XR<BR, 8, 0, 8, 0>::run(d, wv, xb16); wg_commit(); wg_wait0();
        OPAQUE_R(l16);
        if (wg == 0) {
          DUMP(cv);
          if (KB) { wg_fence(); XR<0, KB, 0, 32, 1>::run(d, w, xb16); wg_commit(); wg_wait0(); OPAQUE_R(l16); DUMP(SM_CQ); }
          TSP(5, 1);
        } else {
          XREL(MB_XE1);
          ADDIN(cv);
          uint32_t q[4], o[4];
#pragma unroll
          for (int i = 0; i < 4; i++) { const uint32_t a = pack_bf16(d[2 * i], d[2 * i + 1]), b = pack_bf16(d[8 + 2 * i], d[9 + 2 * i]); q[i] = r ? b : a; o[i] = r ? a : b; }
          st_async4(l16 + (rsb + SM_VR + wq * 512), u2f(o[0]), u2f(o[1]), u2f(o[2]), u2f(o[3]), rsb + SM_BAR + MB_VR);
          sts128(TQ(SM_VL), q[0], q[1], q[2], q[3]);
          __syncwarp();
          if (l16 == 0) mbar_arrive(sb + SM_BAR + MB_VR);
          TSP(28, 5);
        }
      }
      OPAQUE_R(lm); OPAQUE_R(l16);
      {
        uint32_t sa[4][4];
#pragma unroll
        for (int i = 0; i < VPF; i++) ldmatrix_x4_trans(sa[i], WA + i * 2048);
        float a[NCH][4], v[2][4]; uint4 c[4];
        FENCE();
        mbar_wait(sb + SM_BAR + MB_MEM + wg * 8, s & 1);
        TSF(0, 1);
        TSF(21, 5);
#define QP(i) ((i) >= 12 ? (i) - 8 : (i) % 3 == 1 ? (i) / 3 : 8 + (i) - ((i) + 2) / 3)
#pragma unroll
        for (int i = 0; i < 3; i++) c[i] = ldsm4t(MT + QP(i) * 512);
#pragma unroll
        for (int i = 0; i < 16; i++) {
          if (i + 3 < 16) c[(i + 3) & 3] = ldsm4t(MT + QP(i + 3) * 512);
          if (2 * i < NCH) mma4z(a[2 * i], w[2 * QP(i)][0], w[2 * QP(i)][1], w[2 * QP(i)][2], w[2 * QP(i)][3], c[i & 3].x, c[i & 3].y);
          else mma_16816(a[(2 * i) % NCH], w[2 * QP(i)], c[i & 3].x, c[i & 3].y);
          if (2 * i + 1 < NCH) mma4z(a[2 * i + 1], w[2 * QP(i) + 1][0], w[2 * QP(i) + 1][1], w[2 * QP(i) + 1][2], w[2 * QP(i) + 1][3], c[i & 3].z, c[i & 3].w);
          else mma_16816(a[(2 * i + 1) % NCH], w[2 * QP(i) + 1], c[i & 3].z, c[i & 3].w);
          if (VI && QP(i) == 0) {
            mma4z(v[0], wv[0][0], wv[0][1], wv[0][2], wv[0][3], c[i & 3].x, c[i & 3].y);
            mma4z(v[1], wv[1][0], wv[1][1], wv[1][2], wv[1][3], c[i & 3].z, c[i & 3].w);
          } else if (VI && QP(i) < 4) {
            mma_16816(v[0], wv[2 * (QP(i) & 3)], c[i & 3].x, c[i & 3].y);
            mma_16816(v[1], wv[2 * (QP(i) & 3) + 1], c[i & 3].z, c[i & 3].w);
          }
          FENCE();
        }
        {
          const float f = wq < 2 ? 0.125f : 1.f;
          const uint32_t qa = (((l16 & 0x30u) << 3) | ((l16 & 0x10u) << 2) | ((l16 >> 3) & 0x30u) | ((l16 >> 4) & 4u)) + (sb + SM_QKP + w8 * 512);
#pragma unroll
          for (int i = 0; i < 4; i++) sts32((qa ^ ((i & 1) << 6)) + (i >> 1) * 8, f2u(fmaf(a[0][i], f, a[1][i] * f)));
        }
        bar_arrive(B_QK, 288);
        bar_arrive(B_QK1, 288);
        FENCE();
        spin(DLY_VI);
#pragma unroll
        for (int i = VPF; i < 4; i++) ldmatrix_x4_trans(sa[i], WA + i * 2048);
        FENCE();
#pragma unroll
        for (int i = 0; i < 4; i++) {
          mma_16816(v[0], sa[(2 * i) & 3], c[i].x, c[i].y);
          mma_16816(v[1], sa[(2 * i + 1) & 3], c[i].z, c[i].w);
          if (i < 2) { ldmatrix_x4_trans(sa[2 * i], WA + (4 + 2 * i) * 2048); ldmatrix_x4_trans(sa[2 * i + 1], WA + (5 + 2 * i) * 2048); }
          FENCE();
        }
        if (EG && s < NSEG - 1) bar_sync(B_PUB, 320);
        sts128f(TH(SM_VP), v[0][0] + v[1][0], v[0][1] + v[1][1], v[0][2] + v[1][2], v[0][3] + v[1][3]);
        bar_arrive(B_V, 320);
      }
      if (s == NSEG - 1) break;
      if (s == 0) mbar_wait(sb + SM_BAR + MB_WO, 0);
      OPAQUE_R(lm); OPAQUE_R(l16);
      {
        uint32_t wo[WPF][4];
        {
          float d[16];
          PRB(0);
          if (!F1L && wg) mbar_wait(sb + SM_BAR + MB_F + 8, (s + 1) & 1);
          if (KB && wg == 0) {
            INIT(SM_CQ);
#pragma unroll
            for (int f = 0; f < (W0I == 2 ? WPA : 0); f++) ldmatrix_x4_trans(wo[f], WOF(f));
            if (!EG) bar_sync(B_PUB, 320);
            wg_fence();
            XR<KB, KB + 1, 0, 32, 0>::run(d, w, xb16);
            TSF(26, 1);
            XR<KB + 1, 16, 0, 32, 0>::run(d, w, xb16);
            if (W0I == 3) wg_commit();
#pragma unroll
            for (int f = 0; f < (W0I & 1 ? WPA : 0); f++) ldmatrix_x4_trans(wo[f], WOF(f));
            if (W0I == 3) wg_fence();
            XR<0, 16, 16, 32, 0>::run(d, w, xh16);
            wg_commit(); wg_wait0();
            TSF(13, 1);
            XREL(MB_XE0);
#pragma unroll
            for (int f = 0; f < (W0I ? 0 : WPA); f++) ldmatrix_x4_trans(wo[f], WOF(f));
          } else {
          const uint32_t f1ok = EG ? 0u : F1L ? mbar_test(sb + SM_BAR + MB_F + 8, (s + 1) & 1) : 1u;
          if (!EG) bar_sync(B_PUB, 320);
          if (!f1ok) mbar_wait(sb + SM_BAR + MB_F + 8, (s + 1) & 1);
#pragma unroll
          for (int f = 0; f < (W0I == 2 ? WPA : 0); f++) ldmatrix_x4_trans(wo[f], WOF(f));
          wg_fence();
          XR<0, 1, 0, 32, 1>::run(d, w, xb16);
          TSF(7, 5);
          XR<1, WKA, 0, 32, 0>::run(d, w, xb16);
          if (W0I == 3) wg_commit();
#pragma unroll
          for (int f = 0; f < (W0I == 2 ? 0 : WPA); f++) ldmatrix_x4_trans(wo[f], WOF(f));
          if (W0I == 3) wg_fence();
          XR<WKA, 16, 0, 32, 0>::run(d, w, xb16); XR<0, 16, 16, 32, 0>::run(d, w, xh16);
          wg_commit(); wg_wait0();
          }
          TSF(31, 5);
          OPAQUE_R(l16);
          PRB(1);
#define XHALF(g) do { \
            _Pragma("unroll") for (int n = 0; n < 2; n++) sts128f(TQ(SM_CQ + ((g) * 2 + n) * 2048), d[8 - 8 * (g) + 4 * n], d[9 - 8 * (g) + 4 * n], d[10 - 8 * (g) + 4 * n], d[11 - 8 * (g) + 4 * n]); \
            if (F0W == 1 && (g) == 0 && wq == 0 && s < NSEG - 2) F0LOAD(); \
            bar_sync(B_CQ, 256); \
            const float4 t0 = lds128f(TQ(SM_CQ + (2 - 2 * (g)) * 2048)), t1 = lds128f(TQ(SM_CQ + (3 - 2 * (g)) * 2048)); \
            stsm4t(l16 + (sb + SM_XF + (wq * 2 + (g)) * 512), pack_bf16(d[8 * (g)] + t0.x, d[8 * (g) + 1] + t0.y), pack_bf16(d[8 * (g) + 2] + t0.z, d[8 * (g) + 3] + t0.w), \
                   pack_bf16(d[8 * (g) + 4] + t1.x, d[8 * (g) + 5] + t1.y), pack_bf16(d[8 * (g) + 6] + t1.z, d[8 * (g) + 7] + t1.w)); } while (0)
          if (wg) { DUMP(SM_CQ); bar_arrive(B_CQ, 256); }
          else {
            bar_sync(B_CQ, 256);
#pragma unroll
            for (int hf = 0; hf < 2; hf++) {
              const float4 t0 = lds128f(TQ(SM_CQ + 2 * hf * 2048)), t1 = lds128f(TQ(SM_CQ + (2 * hf + 1) * 2048));
              stsm4t(l16 + (sb + SM_XF + (wq * 2 + hf) * 512), pack_bf16(d[8 * hf] + t0.x, d[8 * hf + 1] + t0.y), pack_bf16(d[8 * hf + 2] + t0.z, d[8 * hf + 3] + t0.w),
                     pack_bf16(d[8 * hf + 4] + t1.x, d[8 * hf + 5] + t1.y), pack_bf16(d[8 * hf + 6] + t1.z, d[8 * hf + 7] + t1.w));
            }
            __syncwarp();
            if (l16 < 32) mbar_arrive(sb + SM_BAR + MB_XF);
          }
          TSF(3, 5);
        }
#pragma unroll
        for (int f = WPA; f < WPF; f++) ldmatrix_x4_trans(wo[f], WOF(f));
        unsigned char* pa = P.win + (w_ar(s) + (j * 32 + cw * 16 + wq * 2) * 256 + (l16 >> 2));
        uint32_t ce = (l16 >> 4) - 4 * (cw * 4 + wq);
        OPAQUE_L(pa); OPAQUE_R(ce);
        FENCE();
        if (XH) bar_sync(wg ? B_O : B_O2, 192); else bar_sync(B_O, LN ? 352 : 320);
        if (WNS < 0 && near) spin(DLY_NW);
        uint4 ob[2];
        ob[0] = ldsm4(l16 + (sb + SM_OF)); ob[1] = ldsm4(l16 + (sb + SM_OF + 512));
        float acc[2][4]; uint2 zi; uint32_t f0ok;
#pragma unroll
        for (int f = 0; f < 16; f++) {
          const int ks = f >> 1;
          const uint32_t b0 = (ks & 1) ? ob[(ks >> 1) & 1].z : ob[(ks >> 1) & 1].x, b1 = (ks & 1) ? ob[(ks >> 1) & 1].w : ob[(ks >> 1) & 1].y;
          if (f < 2) mma4z(acc[f], wo[f][0], wo[f][1], wo[f][2], wo[f][3], b0, b1);
          else mma_16816(acc[f % 2], wo[f < WPF ? f : 2 + (f - WPF) % (WPF - 2)], b0, b1);
          if (f - 1 >= 2 && f - 1 + (WPF - 2) < 16) {
            const int nf = f - 1 + (WPF - 2);
            ldmatrix_x4_trans(wo[2 + (nf - WPF) % (WPF - 2)], WOF(nf));
          }
          if (f == 4 || f == 8) ob[((f >> 2) - 1) & 1] = ldsm4(l16 + (sb + SM_OF + (1 + (f >> 2)) * 512));
          if (f == WNS && near) spin(DLY_NW);
          if (f == GF) f0ok = mbar_test(sb + SM_BAR + MB_F, (s + 1) & 1);
          if (LN && f == 12) zi = lds64(((l16 >> 1) & 24u) + (sb + SM_Z));
          if (f < 15) FENCE();
        }
        if (wg) { if (BGT == 2 && l16 == 0) mbar_arrive(sb + SM_BAR + MB_F); } else if (!BGT || f0ok) bar_arrive(B_CV, 256);
        PRB(7 + wg);
        if (LN) {
#pragma unroll
          for (int i = 0; i < 8; i++) acc[i >> 2][i & 3] *= u2f((i & 1) ? zi.y : zi.x);
        }
        red_bf2(pa, pack_bf16(acc[0][0], ce == 0 ? 1.f : acc[0][1])); red_bf2(pa + 256, pack_bf16(acc[0][2], ce == 1 ? 1.f : acc[0][3]));
        red_bf2(pa + 2048, pack_bf16(acc[1][0], ce == 2 ? 1.f : acc[1][1])); red_bf2(pa + 2304, pack_bf16(acc[1][2], ce == 3 ? 1.f : acc[1][3]));
        red_bf2p4(pa + (128 + (wq & 1) * 256), pack_bf16(ce == 0 ? acc[0][1] : ce == 1 ? acc[0][3] : ce == 2 ? acc[1][1] : acc[1][3], 1.f), ce);
        TSF(4, 1);
        TSF(2, 6);
        if (wg) bar_sync(B_CV, 256);
        else if (!f0ok) { mbar_wait(sb + SM_BAR + MB_F, (s + 1) & 1); if (BGT) bar_arrive(B_CV, 256); }
      }
    }
  } else {
    asm volatile("setmaxnreg.dec.sync.aligned.u32 " STR(RF_CTL) ";");
    const int g = lane >> 2, tq = lane & 3;
    if (wq == 0) {
      if (lane < 12) asm volatile("prefetch.global.L2 [%0];" :: "l"(SP.x + (size_t)(cta * 12 + lane) * 64));
      __syncwarp();
      {
        SIDES();
        const uint32_t o[6] = {w_blk(w_h1(cta), me), w_blk(w_h1(cta) ^ H1_V, me), w_blk(w_mvx(cta, 0), me ^ sm2.z), w_blk(w_mvx(cta, 1), me ^ sm2.z),
                               w_blk(w_mxa(cta, 0), me ^ sm2.z), w_blk(w_mxa(cta, 1), me ^ sm2.z)};
#pragma unroll
        for (int i = 0; i < 24; i++) stg_r4(P.win + (o[i >> 2] + (i & 3) * 512 + lane * 16), 0u, 0u, 0u, 0u);
#pragma unroll
        for (int i = 0; i < 6; i++) stg_r1(P.win + (w_ar(i >> 1) + cta * 256 + (i & 1) * 128 + lane * 4), 0u);
        __threadfence();
        __syncwarp();
      }
      {
        const uint32_t wv = movm(*reinterpret_cast<const uint32_t*>(P.mem0 + g * DM + cta * 8 + tq * 2));
        const bool sp = lane == cnt_word(cta & 31);
        stg_r1(P.win + (w_ar(-1) + cta * 256 + lane * 4), sp ? (wv & 0xffffu) | 0x42000000u : wv);
        if (sp) stg_r1(P.win + (w_ar(-1) + ((cta & ~9) + ((cta >> 1) & 1)) * 256 + 128 + lane * 4), (wv >> 16) | 0x42000000u);
      }
      bar_sync(B_V, 160);
      if (lane == 0) {
        fence_async_smem(); mbar_arrive_cluster_rlx(mapa(sb + SM_BAR + MB_INIT, 0)); mbar_arrive_cluster_rlx(mapa(sb + SM_BAR + MB_INIT, 1));
        mbar_wait(sb + SM_BAR + MB_INIT, 0);
        mbar_expect_tx(sb + SM_BAR + MB_F, 32768);
        for (int i = 0; i < (BGT == 2 ? 7 : BGT == 1 ? 3 : 0); i++) mbar_arrive(sb + SM_BAR + MB_F);
        mbar_expect_tx(sb + SM_BAR + MB_F + 8, 32768);
        XLOAD(1, 0); XLOAD(0, 1);
        WLOAD(4 + WSPL, 8);
      }
      __syncwarp();
      bar_sync(B_X2, 384);
    } else {
      bar_sync(B_P, 224);
      if (t128 == 96) {
        fence_async_smem();
        mbar_expect_tx(sb + SM_BAR + MB_WO, 65536);
        for (int i = 0; i < 8; i++) tma_load_2d(sb + SM_WOS + i * 8192, &tmw, j * 256 + ((i >> 1) ^ (2 * sw)) * 64, h * DH + (i & 1) * 64, sb + SM_BAR + MB_WO);
      }
      __syncwarp();
      bar_sync(B_X2, 384);
    }
    SIDES();
    uint32_t l16 = __shfl_sync(~0u, lane * 16, lane);
    const uint32_t me2 = me ^ sm2.z;
    const float sc = 0.08838834764831845f * 1.4426950408889634f;
    uint32_t ls = l16 + sb;
#define PVM(o, zs, p0, p2) do { \
        FENCE(); \
        mma4z(zs, 0x3F803F80u, 0x3F803F80u, 0x3F803F80u, 0x3F803F80u, p0.x, p0.y); \
        _Pragma("unroll") for (int t = 0; t < 4; t++) mma4z(o[t], va[2 * t].x, va[2 * t].y, va[2 * t].z, va[2 * t].w, p0.x, p0.y); \
        FENCE(); \
        mma4(zs, 0x3F803F80u, 0x3F803F80u, 0x3F803F80u, 0x3F803F80u, p0.z, p0.w); \
        _Pragma("unroll") for (int t = 0; t < 2; t++) mma4(o[t], va[2 * t + 1].x, va[2 * t + 1].y, va[2 * t + 1].z, va[2 * t + 1].w, p0.z, p0.w); \
        FENCE(); \
        mma_1688(zs, 0x3F803F80u, 0x3F803F80u, p2); \
        _Pragma("unroll") for (int t = 2; t < 4; t++) mma4(o[t], va[2 * t + 1].x, va[2 * t + 1].y, va[2 * t + 1].z, va[2 * t + 1].w, p0.z, p0.w); \
        mma_1688(o[0], vm[0].x, vm[0].y, p2); mma_1688(o[1], vm[0].z, vm[0].w, p2); mma_1688(o[2], vm[1].x, vm[1].y, p2); mma_1688(o[3], vm[1].z, vm[1].w, p2); } while (0)
#define PVE(o, z, dst) do { \
        const float i0 = rcpf(z[0]), i1 = rcpf(z[1]); \
        _Pragma("unroll") for (int u = 0; u < 2; u++) \
          stsm4t(ls + (dst) + u * 1024, pack_bf16(o[2 * u][0] * i0, o[2 * u][1] * i1), pack_bf16(o[2 * u][2] * i0, o[2 * u][3] * i1), \
                 pack_bf16(o[2 * u + 1][0] * i0, o[2 * u + 1][1] * i1), pack_bf16(o[2 * u + 1][2] * i0, o[2 * u + 1][3] * i1)); } while (0)
#define SOFTMAX(pf, f) do { \
        float mx = fmaxf(fmaxf(fmaxf(sx[2], sx[3]), fmaxf(sx[4], sx[5])), fmaxf(fmaxf(sx[6], sx[7]), fmaxf(sx[8], sx[9]))); \
        mx = fmaxf(mx, fmaxf(sx[0], sx[1])); \
        mx = fmaxf(mx, __shfl_xor_sync(~0u, mx, 1)); \
        mx = fmaxf(mx, __shfl_xor_sync(~0u, mx, 2)); \
        mx *= -(f); \
        _Pragma("unroll") for (int i = 0; i < 10; i++) sx[i] = ex2(fmaf(sx[i], f, mx)); \
        sts128(ls + (pf), pack_bf16(sx[2], sx[3]), pack_bf16(sx[4], sx[5]), pack_bf16(sx[6], sx[7]), pack_bf16(sx[8], sx[9])); \
        sts32(ls - l12 + (pf) + 512, pack_bf16(sx[0], sx[1])); } while (0)
    const uint32_t lq = (l16 ^ ((l16 >> 1) & 64u)) + sb, l12 = (l16 >> 2) * 3;
#define M3PTR(sl) \
            const uint32_t tf = me ^ 1 ^ r, m3i = w_ar(sl) + (wq & 1) * 16384 + (l16 & 0x70u) + ((l16 & 0x180u) << 1); \
            const unsigned char* p0f = P.win + (m3i + r * 8192 + tf * 4096); const unsigned char* p0n = P.win + (m3i + r * 8192 + (tf ^ 1) * 4096); \
            const unsigned char* p1f = P.win + (m3i + (r ^ 1) * 8192 + (tf ^ 1) * 4096); const unsigned char* p1n = P.win + (m3i + (r ^ 1) * 8192 + tf * 4096); \
            const unsigned char* pd = P.win + (w_ar(sl) + (wq & 1) * 16384 + (((l16 >> 7) ^ r) & 1u) * 8192 + ((l16 & 64u) * 4 + (l16 & 48u) * 2 + (l16 & 16u)) * 16 + 128 + (l16 & 0x70u)); \
            uint32_t mf = ls + SM_MEM + (wq & 1) * 8192 + tf * 2048, mn = ls + SM_MEM + (wq & 1) * 8192 + (tf ^ 1) * 2048, nr = l16 < 256u ? 1u + (((l16 >> 6) ^ (l16 >> 7) ^ tf) & 1u) : 0u; \
            OPAQUE_L(p0f); OPAQUE_L(p0n); OPAQUE_L(p1f); OPAQUE_L(p1n); OPAQUE_L(pd); OPAQUE_R(mf); OPAQUE_R(mn); OPAQUE_R(nr); FENCE()
#define M3REQ(arr) \
            _Pragma("unroll") for (int i = 0; i < 4; i++) { cp16(mn + 4096 + i * 512, p1f + i * 1024); cp16(mf + i * 512, p0f + i * 1024); } \
            cp16p(ls + SM_RD + (wq & 1) * 256, pd, nr & 1u); \
            _Pragma("unroll") for (int i = 0; i < 4; i++) { cp16(mf + 4096 + i * 512, p1n + i * 1024); cp16(mn + i * 512, p0n + i * 1024); } \
            cp16p(ls + SM_RD + (wq & 1) * 256, pd, nr & 2u); \
            asm volatile("cp.async.mbarrier.arrive.noinc.shared::cta.b64 [%0];" :: "r"(sb + SM_BAR + MB_G + (wq & 1) * 8) : "memory"); \
            if (BI == 4 && (arr)) bar_arrive(B_LD, 320)
    if (wq < 2) { M3PTR(-1); M3REQ(1); }
#define ETA(k, first) ETAT(gt32() + (k), first)
#define ETAT(tm, first) do { unsigned char* pt = P.win + (w_ar(s) + 384 + (cta >> 5) * 8192 + ((cta >> 4) & 1) * 2048 + (l16 & 16u) * 256); \
          asm volatile("{\n.reg .pred q;\nsetp.lt.u32 q, %2, 32;\n@q red.relaxed.gpu.global.max.u32 [%0+4], %1;\n}" :: "l"(pt), "r"(tm), "r"(l16) : "memory"); \
          if (first) asm volatile("{\n.reg .pred q;\nsetp.lt.u32 q, %1, 32;\n@q red.relaxed.gpu.global.add.u32 [%0], 1;\n}" :: "l"(pt), "r"(l16) : "memory"); } while (0)
    if (wq == 1) {
      const uint32_t xin = w_blk(w_mxa(cta, 0), me2) + l16;
      const uint32_t lsq = sb + ((l16 & 0x70u) | ((l16 & 0x80u) << 1) | ((l16 & 0x100u) >> 1));
      mbar_wait(sb + SM_BAR + MB_MEM, 0); mbar_wait(sb + SM_BAR + MB_MEM + 8, 0);
      for (int s = 0; s < NSEG; s++) {
        const uint32_t t2 = ((s >> 1) & 1) ^ 1;
        mbar_wait(sb + SM_BAR + MB_XF, s & 1);
        PRB(10);
        {
        uint4 kx[4], qx[4];
#pragma unroll
        for (int i = 0; i < 4; i++) { kx[i] = ldsm4(ls + (SM_XF + (4 + i) * 512)); qx[i] = ldsm4(lsq + (SM_XF + i * 512)); }
        const uint32_t db = w_blk(w_mxa(h * 4, s), me2) + l16 - 512;
        {
          float S[2][4][4];
#pragma unroll
          for (int mt = 0; mt < 2; mt++) {
            const uint4 q0 = qx[mt];
            mma4z(S[mt][0], q0.x, q0.y, q0.z, q0.w, kx[0].x, kx[0].y); mma4z(S[mt][1], q0.x, q0.y, q0.z, q0.w, kx[0].z, kx[0].w);
            mma4z(S[mt][2], q0.x, q0.y, q0.z, q0.w, kx[1].x, kx[1].y); mma4z(S[mt][3], q0.x, q0.y, q0.z, q0.w, kx[1].z, kx[1].w);
          }
#pragma unroll
          for (int mt = 0; mt < 2; mt++) {
            const uint4 q1 = qx[2 + mt];
            mma4(S[mt][0], q1.x, q1.y, q1.z, q1.w, kx[2].x, kx[2].y); mma4(S[mt][1], q1.x, q1.y, q1.z, q1.w, kx[2].z, kx[2].w);
            mma4(S[mt][2], q1.x, q1.y, q1.z, q1.w, kx[3].x, kx[3].y); mma4(S[mt][3], q1.x, q1.y, q1.z, q1.w, kx[3].z, kx[3].w);
          }
          FENCE();
          if (BGT && s > 0 && l16 == 0) mbar_arrive(sb + SM_BAR + MB_F);
          FENCE();
#pragma unroll
          for (int u = 0; u < 4; u++) {
            const int mt = u >> 1, c = 2 * (u & 1);
            const uint32_t m0 = tagw(pack_f16(S[mt][0][c] * sc, S[mt][0][c + 1] * sc), t2), m1 = pack_f16(S[mt][1][c] * sc, S[mt][1][c + 1] * sc),
                           m2 = pack_f16(S[mt][2][c] * sc, S[mt][2][c + 1] * sc), m3 = pack_f16(S[mt][3][c] * sc, S[mt][3][c + 1] * sc);
            const int e = u ^ j;
            if (e) stg_r4(P.win + (db + mt * 16384 + (u & 1) * 2048 + e * 512), m0, m1, m2, m3);
            else sts128(ls + SM_XS, m0, m1, m2, m3);
          }
        }
        TS(15);
        float sx[10];
        const unsigned char* pa = P.win + (xin + ((s & 1) << 20));
        uint4 xv[3];
        if (s > 0) spin(DLY_XD);
#pragma unroll
        for (int i = 0; i < 3; i++) xv[i] = ldg_r4(pa + i * 512);
        FENCE();
        if (GW == 0 && s > 0) {
          M3PTR(s - 1);
          bar_sync(B_GO, 64);
          const uint32_t tg0 = lds32(sb + SM_Z + 32);
          while (tg0 - gt32() - 1u < 8192u) {}
          M3REQ(s < NSEG);
        }
        FENCE();
        int n = 0;
#pragma unroll 1
        while (__any_sync(~0u, (x3(xv[0].x, xv[1].x, t2) | (xv[2].x ^ t2)) & 1u) && ++n < SPIN_LIMIT) {
#pragma unroll
          for (int i = 0; i < 3; i++) xv[i] = ldg_r4(pa + i * 512);
        }
        {
          const uint4 v3 = lds128(ls + SM_XS);
          sum_h4(sx[2], sx[3], xv[0].x, xv[1].x, xv[2].x, v3.x); sum_h4(sx[4], sx[5], xv[0].y, xv[1].y, xv[2].y, v3.y);
          sum_h4(sx[6], sx[7], xv[0].z, xv[1].z, xv[2].z, v3.z); sum_h4(sx[8], sx[9], xv[0].w, xv[1].w, xv[2].w, v3.w);
          const int row = 8 * j + g - 2 * tq;
#pragma unroll
          for (int i = 0; i < 8; i++) if ((i >> 1) * 8 + (i & 1) > row) sx[2 + i] = -INFINITY;
        }
        float mx = fmaxf(fmaxf(fmaxf(sx[2], sx[3]), fmaxf(sx[4], sx[5])), fmaxf(fmaxf(sx[6], sx[7]), fmaxf(sx[8], sx[9])));
        sts32(ls - l12 + SM_XS + 512, f2u(mx));
        {
          if (l16 == 0) mbar_expect_tx(sb + SM_BAR + MB_VR, 2048);
          unsigned char* d = P.win + (w_blk(w_mvx(cta, s), me2) + l16);
          OPAQUE_L(d); FENCE();
          mbar_wait(sb + SM_BAR + MB_VR, s & 1);
          PRB(14);
#pragma unroll
          for (int t = 0; t < 4; t++) {
            const uint4 a0 = lds128(ls + (SM_VL + t * 512)), a1 = lds128(ls + (SM_VR + t * 512));
            stg_r4(d + t * 512, tagw(addb2(a0.x, a1.x), t2), addb2(a0.y, a1.y), addb2(a0.z, a1.z), addb2(a0.w, a1.w));
          }
          TS(23);
        }
        unsigned char* pm = P.win + (db + 2048 + j * 128 - l12);
        const unsigned char* py = pa + 1536 - l12;
        OPAQUE_L(pm); OPAQUE_L(py);
        if (s > 0) bar_sync(B_PXF, 96);
        FENCE();
        bar_sync(B_QK1, 288);
        uint32_t kb[2][2];
#pragma unroll
        for (int t = 0; t < 2; t++) {
          const float4 u = lds128f(lq + (SM_QKP + (2 + t) * 512)), v4 = lds128f(lq + (SM_QKP + 2048 + (2 + t) * 512));
          kb[t][0] = pack_bf16(u.x + v4.x, u.y + v4.y); kb[t][1] = pack_bf16(u.z + v4.z, u.w + v4.w);
        }
        float S[2][4];
#pragma unroll
        for (int mt = 0; mt < 2; mt++) mma4z(S[mt], qx[mt].x, qx[mt].y, qx[mt].z, qx[mt].w, kb[0][0], kb[0][1]);
#pragma unroll
        for (int mt = 0; mt < 2; mt++) mma4(S[mt], qx[2 + mt].x, qx[2 + mt].y, qx[2 + mt].z, qx[2 + mt].w, kb[1][0], kb[1][1]);
        if (s < NSEG - 1) bar_arrive(B_PUB, 320);
        FENCE();
#pragma unroll
        for (int u = 0; u < 4; u++) stg_r1(pm + (u >> 1) * 16384 + (u & 1) * 2048, tagw(pack_f16(S[u >> 1][2 * (u & 1)] * sc, S[u >> 1][2 * (u & 1) + 1] * sc), t2));
        TS(30);
        spin(DLY_XL);
        uint32_t xy[4];
#pragma unroll
        for (int i = 0; i < 4; i++) xy[i] = ldg_r1(py + i * 128);
        FENCE();
        if (ETW == 1 && s < NSEG - 1) ETA(DLY_K, 1);
        FENCE();
        n = 0;
#pragma unroll 1
        while (__any_sync(~0u, (x3(xy[0], xy[1], t2) | x3(xy[2], xy[3], t2)) & 1u) && ++n < SPIN_LIMIT) {
#pragma unroll
          for (int i = 0; i < 4; i++) xy[i] = ldg_r1(py + i * 128);
        }
        sum_h4(sx[0], sx[1], xy[0], xy[1], xy[2], xy[3]);
        mx = fmaxf(mx, fmaxf(sx[0], sx[1]));
        mx = fmaxf(fmaxf(mx, __shfl_xor_sync(~0u, mx, 1)), fmaxf(__shfl_xor_sync(~0u, mx, 2), __shfl_xor_sync(~0u, mx, 3)));
#pragma unroll
        for (int i = 0; i < 10; i++) sx[i] = ex2(sx[i] - mx);
        sts128(ls + SM_PX, pack_bf16(sx[2], sx[3]), pack_bf16(sx[4], sx[5]), pack_bf16(sx[6], sx[7]), pack_bf16(sx[8], sx[9]));
        sts32(ls - l12 + SM_PX + 512, pack_bf16(sx[0], sx[1]));
        bar_arrive(B_PX, 96);
        TS(1);
        }
      }
    } else {
      const uint32_t ho = (wq & 1) * 512 + l16, hv = wq == 0 ? 0u : H1_V;
      uint32_t ow = w_blk(w_h1(cta) ^ hv, me) + ho, or0 = w_blk(w_h1(cta ^ 1) ^ hv, me) + ho, or1 = w_blk(w_h1((cta ^ 2) & ~1) ^ hv, me) + ho;
#define PTRS() OPAQUE_R(ow); OPAQUE_R(or0); OPAQUE_R(or1); \
      unsigned char* pw0 = P.win + ow; const unsigned char* pr0 = P.win + or0; const unsigned char* pr1 = P.win + or1; \
      OPAQUE_L(pw0); OPAQUE_L(pr0); OPAQUE_L(pr1); FENCE()
      if (wq == 0) {
        const uint32_t xcnt = me ? NCTA - nlo : nlo, xrank = (me ? cta - nlo : cta) + lane * xcnt;
        mbar_wait(sb + SM_BAR + MB_XE1, 0);
        if (l16 == 0) { mbar_expect_tx(sb + SM_BAR + MB_F + 8, 32768); XLOAD(1, 1); }
        __syncwarp();
        for (int s = 0; s < NSEG; s++) {
          const uint32_t tg = (s & 1) ^ 1;
          mbar_wait(sb + SM_BAR + MB_XF, s & 1);
          uint4 xf[4];
#pragma unroll
          for (int i = 0; i < 4; i++) xf[i] = ldsm4(ls + (SM_XF + (4 + i) * 512));
          PTRS();
          unsigned char* pw1 = pw0 + 512 - l12; OPAQUE_L(pw1);
          bar_sync(B_QK, 288);
          if (s == NSEG - 1) break;
          PRB(9);
          float4 u[4], v4[4];
#pragma unroll
          for (int t = 0; t < 4; t++) { u[t] = lds128f(lq + (SM_QKP + t * 512)); v4[t] = lds128f(lq + (SM_QKP + 2048 + t * 512)); }
          FENCE();
          uint32_t f[4][2];
#pragma unroll
          for (int t = 0; t < 4; t++) {
            f[t][0] = pack_bf16(u[t].x + v4[t].x, u[t].y + v4[t].y);
            f[t][1] = pack_bf16(u[t].z + v4[t].z, u[t].w + v4[t].w);
          }
          float S[5][4], T[5][4];
#pragma unroll
          for (int i = 0; i < 2; i++) {
            mma4z(S[1 + 2 * i], f[0][0], f[1][0], f[0][1], f[1][1], xf[i].x, xf[i].y); mma4z(T[1 + 2 * i], f[0][0], f[1][0], f[0][1], f[1][1], xf[2 + i].x, xf[2 + i].y);
            mma4z(S[2 + 2 * i], f[0][0], f[1][0], f[0][1], f[1][1], xf[i].z, xf[i].w); mma4z(T[2 + 2 * i], f[0][0], f[1][0], f[0][1], f[1][1], xf[2 + i].z, xf[2 + i].w);
          }
          mma4z(S[0], f[0][0], f[1][0], f[0][1], f[1][1], f[2][0], f[2][1]); mma4z(T[0], f[0][0], f[1][0], f[0][1], f[1][1], f[3][0], f[3][1]);
          bar_arrive(B_PUB, 320);
          FENCE();
          uint32_t m[5];
#pragma unroll
          for (int i = 1; i < 6; i++) m[i % 5] = pack_f16(S[i % 5][0] + T[i % 5][2], S[i % 5][1] + T[i % 5][3]);
          stg_r4(pw0, tagw(m[1], tg), m[2], m[3], m[4]);
          stg_r1(pw1, tagw(m[0], tg));
          TS(6);
          FENCE();
#pragma unroll
          for (int i = 0; i < 5; i++) { OPAQUE_R(m[i]); m[i] = hfma2(m[i], 0x34003400u, 0u); OPAQUE_R(m[i]); }
          const unsigned char* py0 = pr0 + 512 - l12; const unsigned char* py1 = pr1 + 512 - l12;
          OPAQUE_L(py0); OPAQUE_L(py1);
          const uint32_t ts = clk32(), te = gt32() + DLY_K;
          if (l16 == 0) mbar_expect_tx(sb + SM_BAR + MB_F, s < NSEG - 2 ? 32768 : 0);
          while (clk32() - ts < (uint32_t)DLY_S) {}
          {
            uint32_t t[5], x, x1, x2, x3_, bad; int n = 0;
#pragma unroll 1
            do {
              uint4 v[3]; uint32_t y[3];
              v[0] = ldg_r4(pr0); v[1] = ldg_r4(pr1); v[2] = ldg_r4(pr1 + 2048);
              y[0] = ldg_r1(py0); y[1] = ldg_r1(py1); y[2] = ldg_r1(py1 + 2048);
              if (n) ETA(DLY_KS, 0); else if (ETW == 0) ETAT(te, 1);
              n++;
              FENCE();
#define Q3(o, a, b, c) hfma2(c, 0x34003400u, hfma2(b, 0x34003400u, hfma2(a, 0x34003400u, o)))
              t[1] = Q3(m[1], v[0].x, v[1].x, v[2].x); t[2] = Q3(m[2], v[0].y, v[1].y, v[2].y); t[3] = Q3(m[3], v[0].z, v[1].z, v[2].z); t[4] = Q3(m[4], v[0].w, v[1].w, v[2].w);
              t[0] = Q3(m[0], y[0], y[1], y[2]);
              x = hmax2(hmax2(hmax2(t[1], t[2]), hmax2(t[3], t[4])), t[0]);
              x = hmax2(x, __byte_perm(x, 0u, 0x1032));
              x = f2u(__low2float(*reinterpret_cast<__half2*>(&x)) * (-32.f * sc));
              x1 = shfl_x(x, 1); x2 = shfl_x(x, 2); x3_ = shfl_x(x, 3);
              FENCE();
              bad = or3(x3(v[0].x, v[1].x, tg), x3(v[2].x, y[0], tg), x3(y[1], y[2], tg));
            } while (__any_sync(~0u, bad & 1u) && n < SPIN_LIMIT);
            float sx[10];
#pragma unroll
            for (int i = 0; i < 5; i++) h2f(sx[2 * i], sx[2 * i + 1], t[i]);
            FENCE();
            const float mx = fminf(fminf(u2f(x), u2f(x1)), fminf(u2f(x2), u2f(x3_)));
#pragma unroll
            for (int i = 2; i < 12; i++) sx[i % 10] = ex2(fmaf(sx[i % 10], 32.f * sc, mx));
#pragma unroll
            for (int i = 1; i < 6; i++) m[i % 5] = pack_bf16(sx[2 * (i % 5)], sx[2 * (i % 5) + 1]);
            sts128(ls + SM_PF, m[1], m[2], m[3], m[4]);
            sts32(ls - l12 + SM_PF + 512, m[0]);
            TV(19, n - 1);
          }
          TS(12);
          bar_sync(B_P, 96);
          if (LN) {
            const uint4 pa = lds128(ls + SM_PF); const uint32_t pb = lds32(ls - l12 + SM_PF + 512);
#define S2(w) (u2f((w) << 16) + u2f((w) & 0xffff0000u))
            float z = ((S2(pa.x) + S2(pa.y)) + (S2(pa.z) + S2(pa.w))) + S2(pb);
            z += __shfl_xor_sync(~0u, z, 1); z += __shfl_xor_sync(~0u, z, 2);
            sts32(sb + SM_Z + (l16 >> 6) * 4, f2u(rcpf(z)));
            bar_arrive(B_O, 352);
          }
          OPAQUE_R(l16);
          {
            const unsigned char* pe = P.win + w_blk(w_ar(s) + 384 + (l16 & 0x60u) * 256 + (l16 & 16u) * 128, me);
            const uint32_t tp = gt32() + DLY_M3;
            PRB(12);
            if (F0W == 0 && s < NSEG - 2) F0LOAD();
            spin(DLY_E);
            uint2 e = ldg_r2(pe); int n = 0;
#pragma unroll 1
            while (__any_sync(~0u, e.x != 16u) && ++n < SPIN_LIMIT) e = ldg_r2(pe);
            uint32_t tg0 = __reduce_max_sync(~0u, e.y);
            if (tg0 - tp >= 4096u) tg0 = tp;
            sts32(sb + SM_Z + 32, tg0);
            bar_arrive(B_GO, GW ? 96 : 64);

            if (GW == 0) {
            M3PTR(s);
            while (tg0 - gt32() - 1u < 8192u) {}
            PRB(13);
            TS(16);
            M3REQ(s + 1 < NSEG);
            }
            TS(25);
          }
          if (F1C && s < NSEG - 2) {
            if (F1C == 1) spin(DLY_FA);
            mbar_wait(sb + SM_BAR + MB_XE1, (s + 1) & 1);
            if (l16 == 0) mbar_expect_tx(sb + SM_BAR + MB_F + 8, 32768);
            if (F1C == 2) { mbar_wait(sb + SM_BAR + MB_MEM, (s + 1) & 1); mbar_wait(sb + SM_BAR + MB_MEM + 8, (s + 1) & 1); }
            if (F1C == 3) { mbar_wait(sb + SM_BAR + MB_G, (s + 1) & 1); mbar_wait(sb + SM_BAR + MB_G + 8, (s + 1) & 1); }
            PRB(11);
            if (l16 == 0) XLOAD(1, s + 2);
            __syncwarp();
          }
          if (XPF && s + XPF < NSEG) {
            spin(DLY_PF);
            for (uint32_t i = xrank; i < 512; i += 32 * xcnt)
              asm volatile("prefetch.global.L2 [%0];" :: "l"(SP.x + (size_t)(s + XPF) * (SEG * DM) + i * 64));
            __syncwarp();
          }
          stg_2(P.win + (w_ar(s + 2) + cta * 256 + (l16 >> 1)), 0u, 0u);
        }
      } else {
        const int mt = wq - 2;
        const uint32_t lt = ls + mt * 1024;
        const uint32_t vi0 = w_blk(w_mvx(h * 4, 0), me2) + mt * 1024;
        const int m3d = r ? -8192 : 8192;
        float ox[4][4], zx[4];
#pragma unroll
        for (int i = 0; i < 16; i++) ox[i >> 2][i & 3] = zx[i & 3] = 1.f;
        for (int s = 0;; s++) {
          const uint32_t tg = (s & 1) ^ 1, t2 = ((s >> 1) & 1) ^ 1;
          {
            OPAQUE_R(l16);
            const uint32_t m3i = (mt * 2 + r) * 8192 + (l16 & 0x70u) + ((l16 & 0x180u) << 1);
            const uint32_t m3j = (mt * 2 + (r ^ (l16 >> 7 & 1))) * 8192 + ((l16 & 64u) * 4 + (l16 & 48u) * 2 + (l16 & 16u)) * 16 + 128 + (l16 & 0x70u);
            uint32_t m3c = sb + SM_MEM + mt * 8192 + cnt_line(l16 >> 4) * 128 + (l16 >> 2);
            const unsigned char* p3 = P.win + (m3i + w_ar(s - 1)); const unsigned char* pd = P.win + (m3j + w_ar(s - 1));
            OPAQUE_L(pd); OPAQUE_R(m3c);
#define XEPI() do {        \
              PVE(ox, zx, SM_OX + mt * 512); \
              __syncwarp(); \
              const uint32_t oa = sb + SM_OX + mt * 512 + ((l16 & 48u) << 3) + ((l16 >> 2) & 0x70u); \
              const uint4 a = lds128(oa), b = lds128(oa + 1024); \
              unsigned char* o = reinterpret_cast<unsigned char*>(g_ox + (size_t)((s - 1) * SEG + 8 * j) * (NH * DH) + h * DH + mt * 32) + ((l16 >> 6) * (NH * DH * 2) + (l16 & 48u)); \
              stg_4(o, a); stg_4(o + 128, b); \
              TST(s - 1, 18, l16 | mt, TCLK()); } while (0)
            if (s > 0) XEPI();
            if (s == NSEG) break;
            if (GW && s > 0) {
              M3PTR(s - 1);
              bar_sync(B_GO, 96);
              const uint32_t tg0 = lds32(sb + SM_Z + 32);
              while (tg0 - gt32() - 1u < 8192u) {}
              M3REQ(0);
            }
            FENCE();
            const int n = m3_check(sb, p3, pd, m3d, l16, m3c, mt, s & 1);
            FENCE();
            if (ETW == 3 && s < NSEG - 1) ETA(DLY_K, mt);
            TST(s - 1, 14, l16 | mt, TCLK());
            TST(s, mt ? 22 : 17, l16, n);
          }
          uint4 va[8], vm[2], p0, q0; uint32_t p2, q2;
          const unsigned char* a0 = P.win + (vi0 + ((s & 1) << 20) + l16);
#define VALD() _Pragma("unroll") for (int i = 0; i < 4; i++) { va[i] = ldg_r4(a0 + (i >> 1) * 512 + (i & 1) * 2048); va[4 + i] = ldg_r4(a0 + 16384 + (i >> 1) * 512 + (i & 1) * 2048); }
          spin(DLY_WO);
          VALD();
          {
          PTRS();
          bar_sync(B_V, 320);
            const float4 u0 = lds128f(lt + SM_VP), w0 = lds128f(lt + SM_VP + 2048), u1 = lds128f(lt + SM_VP + 512), w1 = lds128f(lt + SM_VP + 2560);
            const uint32_t m0 = tagw(pack_bf16(u0.x + w0.x, u0.y + w0.y), tg), m1 = pack_bf16(u0.z + w0.z, u0.w + w0.w),
                           m2 = pack_bf16(u1.x + w1.x, u1.y + w1.y), m3 = pack_bf16(u1.z + w1.z, u1.w + w1.w);
            stg_r4(pw0, m0, m1, m2, m3);
            if (wq == 2) TS(10);
            FENCE();
            const uint32_t tv = clk32();
            if (ETW == 2 && wq == 3 && s < NSEG - 1) ETA(DLY_K, 1);
            while (clk32() - tv < (uint32_t)DLY_V) {}
            uint4 v[3]; int n = 0; uint32_t bada = 0;
#pragma unroll 1
            do {
              v[0] = ldg_r4(pr0); v[1] = ldg_r4(pr1); v[2] = ldg_r4(pr1 + 2048);
              if (n) {
                if (__any_sync(~0u, bada & 1u)) { VALD(); }
                if (s < NSEG - 1) ETA(DLY_KS - 192, 0);
              }
              n++;
              FENCE();
              bada = or3(x3(va[0].x, va[1].x, t2), x3(va[2].x, va[3].x, t2), x3(va[4].x, va[5].x, t2)) | x3(va[6].x, va[7].x, t2);
            } while (__any_sync(~0u, or3(bada, x3(v[0].x, v[1].x, tg), v[2].x ^ tg) & 1u) && n < SPIN_LIMIT);
            const uint4 A = make_uint4(addb2(m0, v[0].x), addb2(m1, v[0].y), addb2(m2, v[0].z), addb2(m3, v[0].w));
            const uint4 B = make_uint4(addb2(v[1].x, v[2].x), addb2(v[1].y, v[2].y), addb2(v[1].z, v[2].z), addb2(v[1].w, v[2].w));
            vm[0] = p ? B : A; vm[1] = p ? A : B;
            TST(s, 11, l16 | mt, TCLK()); TST(s, 29, l16 | (mt ^ 1), TCLK());
          }
          if (F0W == 2 && wq == 3 && s < NSEG - 2) F0LOAD();
          if (PXE) { bar_sync(B_PX, 96); q0 = lds128(ls + SM_PX); q2 = lds32(ls - l12 + SM_PX + 512); }
          FENCE();
          if (s < NSEG - 1) {
          PRB(5);
          bar_sync(B_P, 96);
          PRB(6);
          p0 = lds128(ls + SM_PF); p2 = lds32(ls - l12 + SM_PF + 512);
          float o[4][4], z[4];
          PVM(o, z, p0, p2);
          PVE(o, z, SM_OF + mt * 512);
          if (XH) { bar_arrive(B_O, 192); bar_arrive(B_O2, 192); } else bar_arrive(B_O, 320);
          TST(s, 20, l16 | mt, tq1);
          }
          FENCE();
          TST(s, 8, l16 | mt, TCLK()); TST(s, 24, l16 | (mt ^ 1), TCLK());
          if (!PXE) { spin(DLY_PX); bar_sync(B_PX, 96); q0 = lds128(ls + SM_PX); q2 = lds32(ls - l12 + SM_PX + 512); }
          if (EPI < 4) PVM(ox, zx, q0, q2);
          FENCE();
          if (s < NSEG - 1) { bar_arrive(B_PXF, 96); if (BGT && l16 == 0) mbar_arrive(sb + SM_BAR + MB_F); }
        }
      }
    }
  }
  asm volatile("barrier.cluster.arrive.relaxed.aligned;\nbarrier.cluster.wait.aligned;" ::: "memory");
}
#define PW 2
#define G2_ST 6
#define G2_TB (G2_ST * 32768 + 1024)
#define G2_SMEM (G2_TB + 32768)
static __device__ __forceinline__ void wgmma_n128_ta(float (&d)[64], uint64_t da, uint64_t db) {
  asm volatile(
      "wgmma.mma_async.sync.aligned.m64n128k16.f32.bf16.bf16 "
      "{%0,%1,%2,%3,%4,%5,%6,%7,%8,%9,%10,%11,%12,%13,%14,%15,%16,%17,%18,%19,%20,%21,%22,%23,%24,%25,%26,%27,%28,%29,%30,%31,"
      "%32,%33,%34,%35,%36,%37,%38,%39,%40,%41,%42,%43,%44,%45,%46,%47,%48,%49,%50,%51,%52,%53,%54,%55,%56,%57,%58,%59,%60,%61,%62,%63}, "
      "%64, %65, 1, 1, 1, 1, 0;"
      : "+f"(d[0]), "+f"(d[1]), "+f"(d[2]), "+f"(d[3]), "+f"(d[4]), "+f"(d[5]), "+f"(d[6]), "+f"(d[7]), "+f"(d[8]), "+f"(d[9]), "+f"(d[10]), "+f"(d[11]),
        "+f"(d[12]), "+f"(d[13]), "+f"(d[14]), "+f"(d[15]), "+f"(d[16]), "+f"(d[17]), "+f"(d[18]), "+f"(d[19]), "+f"(d[20]), "+f"(d[21]), "+f"(d[22]), "+f"(d[23]),
        "+f"(d[24]), "+f"(d[25]), "+f"(d[26]), "+f"(d[27]), "+f"(d[28]), "+f"(d[29]), "+f"(d[30]), "+f"(d[31]), "+f"(d[32]), "+f"(d[33]), "+f"(d[34]), "+f"(d[35]),
        "+f"(d[36]), "+f"(d[37]), "+f"(d[38]), "+f"(d[39]), "+f"(d[40]), "+f"(d[41]), "+f"(d[42]), "+f"(d[43]), "+f"(d[44]), "+f"(d[45]), "+f"(d[46]), "+f"(d[47]),
        "+f"(d[48]), "+f"(d[49]), "+f"(d[50]), "+f"(d[51]), "+f"(d[52]), "+f"(d[53]), "+f"(d[54]), "+f"(d[55]), "+f"(d[56]), "+f"(d[57]), "+f"(d[58]), "+f"(d[59]),
        "+f"(d[60]), "+f"(d[61]), "+f"(d[62]), "+f"(d[63])
      : "l"(da), "l"(db));
}
__global__ void __cluster_dims__(2, 1, 1) __launch_bounds__(384, 1)
gemm2_kernel(const __grid_constant__ CUtensorMap tmo, const __grid_constant__ CUtensorMap tmw, const bf16* __restrict__ x, bf16* __restrict__ out, unsigned char* win) {
  extern __shared__ __align__(1024) unsigned char smem[];
  const uint32_t sb = smem_u32(smem), bars = sb + G2_ST * 32768;
  const int tid = threadIdx.x, lane = tid & 31, warp = tid >> 5;
  const int r = blockIdx.x & 1, n0 = (blockIdx.x & 7) * 128, m0 = (blockIdx.x >> 3) * 128;
  if (tid == 0) {
    for (int i = 0; i < G2_ST; i++) { mbar_init(bars + i * 8, 1); mbar_init(bars + 64 + i * 8, 4); }
    asm volatile("fence.mbarrier_init.release.cluster;" ::: "memory");
  }
  if (tid == 32) { asm volatile("prefetch.tensormap [%0];" :: "l"(&tmw) : "memory"); asm volatile("prefetch.tensormap [%0];" :: "l"(&tmo) : "memory"); }
  __syncthreads();
  asm volatile("barrier.cluster.arrive.relaxed.aligned;" ::: "memory");
#define LW(kt, st) do { tma_load_2d(sb + (st) * 32768, &tmw, n0, (kt) * 64, bars + (st) * 8); tma_load_2d(sb + (st) * 32768 + 8192, &tmw, n0 + 64, (kt) * 64, bars + (st) * 8); } while (0)
#define LO(kt, st) asm volatile("cp.async.bulk.tensor.2d.shared::cluster.global.mbarrier::complete_tx::bytes.multicast::cluster [%0], [%1, {%3, %4}], [%2], %5;" \
                     :: "r"(sb + (st) * 32768 + 16384 + r * 8192), "l"(&tmo), "r"(bars + (st) * 8), "r"((kt) * 64), "r"(m0 + r * 64), "h"((uint16_t)3) : "memory")
  if (tid == 256) for (int kt = 0; kt < G2_ST; kt++) { mbar_expect_tx(bars + kt * 8, 32768); if (kt < PW) LW(kt, kt); }
  __syncwarp();
  asm volatile("barrier.cluster.wait.acquire.aligned;" ::: "memory");
  if (warp == 8) {
    if (lane == 0) {
      asm volatile("griddepcontrol.wait;" ::: "memory");
      for (int kt = 0; kt < G2_ST; kt++) { LO(kt, kt); if (kt >= PW) LW(kt, kt); }
      for (int kt = G2_ST; kt < 64; kt++) {
        const int st = kt % G2_ST;
        mbar_wait(bars + 64 + st * 8, ((kt / G2_ST) - 1) & 1);
        mbar_expect_tx(bars + st * 8, 32768);
        LO(kt, st); LW(kt, st);
      }
    }
  } else if (warp > 8) {
    const int t = tid - 288, ch = t & 15;
    asm volatile("griddepcontrol.wait;" ::: "memory");
    int idx[8];
#pragma unroll
    for (int c = 0; c < 8; c++) idx[c] = g_idx[c];
    const int gi = blockIdx.x * 96 + t;
    if (gi < 67) g_side[gi * 32] = 0u;
    if (gi == 0) g_sbar = 0u;
#pragma unroll 4
    for (int row = t >> 4; row < 128; row += 6) {
      const int tok = m0 + row;
      const uint4 xv = *reinterpret_cast<const uint4*>(x + (size_t)tok * DM + n0 + ch * 8);
      const float g = g_gate[tok], omg = rbf(1.f - g);
      int sel = -1;
#pragma unroll
      for (int c = 0; c < 8; c++) if (idx[c] == tok) sel = c;
      uint4 uv = make_uint4(0u, 0u, 0u, 0u);
      if (sel >= 0) uv = *reinterpret_cast<const uint4*>(g_upd + sel * DM + n0 + ch * 8);
      const uint32_t x4[4] = {xv.x, xv.y, xv.z, xv.w}, u4[4] = {uv.x, uv.y, uv.z, uv.w};
      uint32_t o4[4];
#pragma unroll
      for (int e = 0; e < 4; e++) {
        const float b0 = rbf(u2f(x4[e] << 16) + u2f(u4[e] << 16)), b1 = rbf(u2f(x4[e] & 0xffff0000u) + u2f(u4[e] & 0xffff0000u));
        o4[e] = pack_bf16(omg * b0, omg * b1);
      }
      sts128(sb + G2_TB + row * 256 + ch * 16, o4[0], o4[1], o4[2], o4[3]);
      if (ch == 0) sts32(bars + 512 + row * 4, __float_as_uint(g));
    }
    bar_arrive(2, 352);
  } else {
    const int wg = warp >> 2;
    float d[64];
#pragma unroll
    for (int i = 0; i < 64; i++) d[i] = 0.f;
    const uint32_t e0 = mapa(bars + 64, 0), e1 = mapa(bars + 64, 1);
    for (int kt = 0; kt < 64; kt++) {
      const int st = kt % G2_ST;
      mbar_wait(bars + st * 8, (kt / G2_ST) & 1);
      wg_fence();
#pragma unroll
      for (int kk = 0; kk < 4; kk++)
        wgmma_n128_ta(d, make_desc(sb + st * 32768 + wg * 8192 + kk * 2048, 1024, 1024), make_desc(sb + st * 32768 + 16384 + kk * 32, 16, 1024));
      wg_commit();
      asm volatile("wgmma.wait_group.sync.aligned 1;" ::: "memory");
      if (kt > 0 && (tid & 127) == 0) { const int ps = (kt - 1) % G2_ST; mbar_arrive_cluster_rlx(e0 + ps * 8); mbar_arrive_cluster_rlx(e1 + ps * 8); }
    }
    wg_wait0();
    bar_sync(1, 256);
#pragma unroll
    for (int jj = 0; jj < 8; jj++) {
      const uint32_t q0 = pack_bf16(d[8 * jj], d[8 * jj + 1]), q1 = pack_bf16(d[8 * jj + 2], d[8 * jj + 3]);
      const uint32_t q2 = pack_bf16(d[8 * jj + 4], d[8 * jj + 5]), q3 = pack_bf16(d[8 * jj + 6], d[8 * jj + 7]);
      stsm4t(sb + (jj * 16 + (lane >> 4) * 8 + (lane & 7)) * 272 + (warp * 16 + ((lane >> 3) & 1) * 8) * 2, q0, q1, q2, q3);
    }
    bar_sync(2, 352);
#pragma unroll
    for (int it = 0; it < 8; it++) {
      const int row = it * 16 + (tid >> 4), ch = tid & 15, tok = m0 + row;
      const uint4 av = lds128(sb + row * 272 + ch * 16), tv = lds128(sb + G2_TB + row * 256 + ch * 16);
      const float g = u2f(lds32(bars + 512 + row * 4));
      const uint32_t a4[4] = {av.x, av.y, av.z, av.w}, t4[4] = {tv.x, tv.y, tv.z, tv.w};
      uint32_t o4[4];
#pragma unroll
      for (int e = 0; e < 4; e++)
        o4[e] = pack_bf16(rbf(g * u2f(a4[e] << 16)) + u2f(t4[e] << 16), rbf(g * u2f(a4[e] & 0xffff0000u)) + u2f(t4[e] & 0xffff0000u));
      *reinterpret_cast<uint4*>(out + (size_t)tok * DM + n0 + ch * 8) = make_uint4(o4[0], o4[1], o4[2], o4[3]);
    }
  }
  asm volatile("barrier.cluster.arrive.relaxed.aligned;\nbarrier.cluster.wait.aligned;" ::: "memory");
}
#define WPROM CU_TENSOR_MAP_L2_PROMOTION_L2_128B
#define PDL 1
typedef CUresult (*PFN_encodeTiled)(CUtensorMap*, CUtensorMapDataType, cuuint32_t, void*, const cuuint64_t*, const cuuint64_t*,
                                    const cuuint32_t*, const cuuint32_t*, CUtensorMapInterleave, CUtensorMapSwizzle,
                                    CUtensorMapL2promotion, CUtensorMapFloatOOBfill);

extern "C" void kernel_launch(void* const* d_in, const int* in_sizes, int n_in, void* d_out, int out_size) {
  const bf16* x = (const bf16*)d_in[0];
  const bf16* mem0 = (const bf16*)d_in[1];
  const bf16* Wq = (const bf16*)d_in[2];
  const bf16* Wk = (const bf16*)d_in[3];
  const bf16* Wv = (const bf16*)d_in[4];
  const bf16* Wo = (const bf16*)d_in[5];
  const bf16* w_r = (const bf16*)d_in[8];
  const bf16* w_gate = (const bf16*)d_in[9];
  const bf16* w_up = (const bf16*)d_in[10];
  const bf16* w_down = (const bf16*)d_in[11];
  const bf16* gate_w = (const bf16*)d_in[12];
  bf16* out = (bf16*)d_out;

  static PFN_encodeTiled encode = nullptr;
  if (!encode) {
    void* fn = nullptr; cudaDriverEntryPointQueryResult st;
    cudaGetDriverEntryPoint("cuTensorMapEncodeTiled", &fn, cudaEnableDefault, &st);
    encode = (PFN_encodeTiled)fn;
    cudaFuncSetAttribute(rec_kernel, cudaFuncAttributeMaxDynamicSharedMemorySize, SM_TOTAL);
    cudaFuncSetAttribute(gemm2_kernel, cudaFuncAttributeMaxDynamicSharedMemorySize, G2_SMEM);
  }
  CUtensorMap tmx;
  {
    cuuint64_t gd[3] = {64, S_TOK, DM / 64};
    cuuint64_t gs[2] = {DM * 2, 128};
    cuuint32_t bx[3] = {64, SEG, 4};
    cuuint32_t es[3] = {1, 1, 1};
    encode(&tmx, CU_TENSOR_MAP_DATA_TYPE_BFLOAT16, 3, (void*)x, gd, gs, bx, es, CU_TENSOR_MAP_INTERLEAVE_NONE,
           CU_TENSOR_MAP_SWIZZLE_128B, CU_TENSOR_MAP_L2_PROMOTION_L2_128B, CU_TENSOR_MAP_FLOAT_OOB_FILL_NONE);
  }
  bf16* ox;
  cudaGetSymbolAddress((void**)&ox, g_ox);
  CUtensorMap tmo, tmw;
  {
    cuuint64_t gd[2] = {NH * DH, S_TOK}; cuuint64_t gs[1] = {NH * DH * 2}; cuuint32_t bx[2] = {64, 64}; cuuint32_t es[2] = {1, 1};
    encode(&tmo, CU_TENSOR_MAP_DATA_TYPE_BFLOAT16, 2, (void*)ox, gd, gs, bx, es, CU_TENSOR_MAP_INTERLEAVE_NONE,
           CU_TENSOR_MAP_SWIZZLE_128B, CU_TENSOR_MAP_L2_PROMOTION_L2_128B, CU_TENSOR_MAP_FLOAT_OOB_FILL_NONE);
    cuuint64_t gd2[2] = {DM, NH * DH}; cuuint64_t gs2[1] = {DM * 2}; cuuint32_t bx2[2] = {64, 64};
    encode(&tmw, CU_TENSOR_MAP_DATA_TYPE_BFLOAT16, 2, (void*)Wo, gd2, gs2, bx2, es, CU_TENSOR_MAP_INTERLEAVE_NONE,
           CU_TENSOR_MAP_SWIZZLE_128B, CU_TENSOR_MAP_L2_PROMOTION_L2_128B, CU_TENSOR_MAP_FLOAT_OOB_FILL_NONE);
  }
  unsigned char* win;
  cudaGetSymbolAddress((void**)&win, g_win);
  win = (unsigned char*)(((uintptr_t)win + (2u << 20) - 1) & ~(uintptr_t)((2u << 20) - 1));
  WMaps W;
  {
    cuuint64_t gd[2] = {NH * DH, DM}; cuuint64_t gs[1] = {NH * DH * 2}; cuuint32_t b32[2] = {32, 128}, b64[2] = {64, 128}; cuuint32_t es[2] = {1, 1};
    encode(&W.q, CU_TENSOR_MAP_DATA_TYPE_BFLOAT16, 2, (void*)Wq, gd, gs, b32, es, CU_TENSOR_MAP_INTERLEAVE_NONE,
           CU_TENSOR_MAP_SWIZZLE_64B, WPROM, CU_TENSOR_MAP_FLOAT_OOB_FILL_NONE);
    encode(&W.k, CU_TENSOR_MAP_DATA_TYPE_BFLOAT16, 2, (void*)Wk, gd, gs, b32, es, CU_TENSOR_MAP_INTERLEAVE_NONE,
           CU_TENSOR_MAP_SWIZZLE_64B, WPROM, CU_TENSOR_MAP_FLOAT_OOB_FILL_NONE);
    encode(&W.v, CU_TENSOR_MAP_DATA_TYPE_BFLOAT16, 2, (void*)Wv, gd, gs, b64, es, CU_TENSOR_MAP_INTERLEAVE_NONE,
           CU_TENSOR_MAP_SWIZZLE_128B, WPROM, CU_TENSOR_MAP_FLOAT_OOB_FILL_NONE);
  }
  RecParams P{mem0, win};
  SideParams SP{x, w_r, w_gate, w_up, w_down, gate_w, Wo};
  rec_kernel<<<NCTA + 4, 384, SM_TOTAL, cudaStreamPerThread>>>(tmx, tmw, W, P, SP);
  {
    cudaLaunchConfig_t cfg = {};
    cfg.gridDim = dim3(NCTA); cfg.blockDim = dim3(384); cfg.dynamicSmemBytes = G2_SMEM; cfg.stream = cudaStreamPerThread;
    cudaLaunchAttribute at[1];
    at[0].id = cudaLaunchAttributeProgrammaticStreamSerialization; at[0].val.programmaticStreamSerializationAllowed = 1;
    cfg.attrs = at; cfg.numAttrs = PDL;
    cudaLaunchKernelEx(&cfg, gemm2_kernel, tmo, tmw, x, out, win);
  }
}
```

```cpp
#include <cuda_runtime.h>
#include <cuda_bf16.h>
#include <cuda_fp16.h>
#include <cuda.h>
#include <stdint.h>

typedef __nv_bfloat16 bf16;

#define S_TOK 2048
#define DM 1024
#define NH 32
#define DH 128
#define MM 8
#define SEG 32
#define NSEG 64
#define LL 40
#define FF 3584
#define NCTA 128

static __device__ bf16 g_ox[(size_t)S_TOK * NH * DH];
static __device__ float g_gate[S_TOK];
static __device__ float g_r[S_TOK];
static __device__ int g_idx[8];
static __device__ bf16 g_upd[8 * DM];

static __device__ __forceinline__ float rbf(float v) { return __bfloat162float(__float2bfloat16(v)); }
static __device__ __forceinline__ uint32_t smem_u32(const void* p) { return (uint32_t)__cvta_generic_to_shared(p); }
static __device__ __forceinline__ uint32_t pack_bf16(float lo, float hi) {
  __nv_bfloat162 v = __floats2bfloat162_rn(lo, hi);
  return *reinterpret_cast<uint32_t*>(&v);
}

static __device__ __forceinline__ void wg_fence() { asm volatile("wgmma.fence.sync.aligned;" ::: "memory"); }
static __device__ __forceinline__ void wg_commit() { asm volatile("wgmma.commit_group.sync.aligned;" ::: "memory"); }
static __device__ __forceinline__ void wg_wait0() { asm volatile("wgmma.wait_group.sync.aligned 0;" ::: "memory"); }
static __device__ __forceinline__ void fence_async_smem() { asm volatile("fence.proxy.async.shared::cta;" ::: "memory"); }

static __device__ __forceinline__ uint64_t make_desc(uint32_t addr, uint32_t lbo, uint32_t sbo) {
  uint64_t d = 0;
  d |= (uint64_t)((addr & 0x3FFFF) >> 4);
  d |= (uint64_t)((lbo >> 4) & 0x3FFF) << 16;
  d |= (uint64_t)((sbo >> 4) & 0x3FFF) << 32;
  d |= (uint64_t)1 << 62;
  return d;
}

#define DESC_HI(sbo) (((sbo) >> 4) | (1u << 30))
template <int OFF, int SCALE>
static __device__ __forceinline__ void wgmma_n32_ra(float (&d)[16], const uint32_t (&a)[4], uint32_t base16) {
  asm volatile(
      "{\n.reg .b32 t;\n.reg .b64 dd;\nadd.u32 t, %20, %21;\nmov.b64 dd, {t, %22};\n"
      "wgmma.mma_async.sync.aligned.m64n32k16.f32.bf16.bf16 "
      "{%0,%1,%2,%3,%4,%5,%6,%7,%8,%9,%10,%11,%12,%13,%14,%15}, {%16,%17,%18,%19}, dd, %23, 1, 1, 0;\n}"
      : "+f"(d[0]), "+f"(d[1]), "+f"(d[2]), "+f"(d[3]), "+f"(d[4]), "+f"(d[5]), "+f"(d[6]), "+f"(d[7]),
        "+f"(d[8]), "+f"(d[9]), "+f"(d[10]), "+f"(d[11]), "+f"(d[12]), "+f"(d[13]), "+f"(d[14]), "+f"(d[15])
      : "r"(a[0]), "r"(a[1]), "r"(a[2]), "r"(a[3]), "r"(base16), "n"(OFF >> 4), "n"(DESC_HI(1024)), "n"(SCALE));
}
template <int AOFF, int BOFF, int SCALE>
static __device__ __forceinline__ void wgmma_n32_ss_ta(float (&d)[16], uint32_t abase16, uint32_t bbase16) {
  asm volatile(
      "{\n.reg .b32 t, u;\n.reg .b64 da, db;\nadd.u32 t, %16, %18;\nmov.b64 da, {t, %20};\nadd.u32 u, %17, %19;\nmov.b64 db, {u, %20};\n"
      "wgmma.mma_async.sync.aligned.m64n32k16.f32.bf16.bf16 "
      "{%0,%1,%2,%3,%4,%5,%6,%7,%8,%9,%10,%11,%12,%13,%14,%15}, da, db, %21, 1, 1, 1, 0;\n}"
      : "+f"(d[0]), "+f"(d[1]), "+f"(d[2]), "+f"(d[3]), "+f"(d[4]), "+f"(d[5]), "+f"(d[6]), "+f"(d[7]),
        "+f"(d[8]), "+f"(d[9]), "+f"(d[10]), "+f"(d[11]), "+f"(d[12]), "+f"(d[13]), "+f"(d[14]), "+f"(d[15])
      : "r"(abase16), "r"(bbase16), "n"(AOFF >> 4), "n"(BOFF >> 4), "n"(DESC_HI(1024)), "n"(SCALE));
}
static __device__ __forceinline__ void ldmatrix_x4_trans(uint32_t (&r)[4], uint32_t addr) {
  asm volatile("ldmatrix.sync.aligned.m8n8.x4.trans.shared.b16 {%0,%1,%2,%3}, [%4];"
               : "=r"(r[0]), "=r"(r[1]), "=r"(r[2]), "=r"(r[3]) : "r"(addr) : "memory");
}
static __device__ __forceinline__ void mma_16816(float (&d)[4], const uint32_t (&a)[4], uint32_t b0, uint32_t b1) {
  asm volatile("mma.sync.aligned.m16n8k16.row.col.f32.bf16.bf16.f32 {%0,%1,%2,%3}, {%4,%5,%6,%7}, {%8,%9}, {%0,%1,%2,%3};"
               : "+f"(d[0]), "+f"(d[1]), "+f"(d[2]), "+f"(d[3])
               : "r"(a[0]), "r"(a[1]), "r"(a[2]), "r"(a[3]), "r"(b0), "r"(b1));
}

static __device__ __forceinline__ uint32_t mapa(uint32_t addr, uint32_t rank) {
  uint32_t r; asm volatile("mapa.shared::cluster.u32 %0, %1, %2;" : "=r"(r) : "r"(addr), "r"(rank)); return r;
}

static __device__ __forceinline__ void mbar_init(uint32_t bar, int cnt) {
  asm volatile("mbarrier.init.shared::cta.b64 [%0], %1;" :: "r"(bar), "r"(cnt) : "memory");
}
static __device__ __forceinline__ void mbar_expect_tx(uint32_t bar, uint32_t bytes) {
  asm volatile("mbarrier.arrive.expect_tx.shared::cta.b64 _, [%0], %1;" :: "r"(bar), "r"(bytes) : "memory");
}
static __device__ __forceinline__ void tma_load_2d(uint32_t dst, const CUtensorMap* tm, int c0, int c1, uint32_t bar) {
  asm volatile("cp.async.bulk.tensor.2d.shared::cluster.global.mbarrier::complete_tx::bytes [%0], [%1, {%3, %4}], [%2];"
               :: "r"(dst), "l"(tm), "r"(bar), "r"(c0), "r"(c1) : "memory");
}

static __device__ unsigned char g_win[6 << 20];
static __device__ unsigned int g_side[67 * 32];
static __device__ unsigned int g_err;
#define W_UP (1u << 20)
#define W_2 (2u << 20)
static __device__ __forceinline__ uint32_t w_blk(uint32_t off, uint32_t side) { return off | (((__popc((off >> 12) & 0xb3u) ^ side) & 1u) << 12); }
static __device__ __forceinline__ uint32_t w_h1(int c) { return W_UP | (1u << 13) | ((c >> 1) << 14) | ((c & 1) << 11); }
static __device__ __forceinline__ uint32_t w_ar(int s) { return ((s & 1) << 15) | ((s & 2) << 17); }
static __device__ __forceinline__ uint32_t w_mvx(int c, int s) { return W_2 | ((s & 1) << 20) | ((c >> 1) << 14) | ((c & 1) << 11); }
static __device__ __forceinline__ uint32_t w_mxa(int c, int s) { return W_2 | ((s & 1) << 20) | (1u << 13) | ((c >> 1) << 14) | ((c & 1) << 11); }
#define H1_V (1u << 13)

#define SPIN_LIMIT (1 << 18)

#define SM_X 0
#define SM_WOS 65536
#define SM_WVS 131072
#define SM_MEM 163840
#define SM_QKP 180224
#define SM_VP 184320
#define SM_CW 188416
#define SM_VST 196608
#define SM_VR 196608
#define SM_CQ 200704
#define SM_CV 208896
#define SM_XF 217088
#define SM_VL 221184
#define SM_OF 225280
#define SM_OX 227328
#define SM_PF 229376
#define SM_PX 230016
#define SM_RD 223232
#define SM_XS 231168
#define SM_BAR 231808
#define SM_Z 231936
#define SM_TS 232064
#define NTS 40
#define SM_TOTAL SM_TS
#define MB_F 0
#define MB_XE0 16
#define MB_XE1 112
#define MB_INIT 24
#define MB_MEM 32
#define MB_W 48
#define MB_XF 64
#define MB_VR 72
#define MB_X0 80
#define MB_WO 88
#define SM_SIDE (SM_BAR + 96)
#define MB_G 192
#define B_QK 1
#define B_V 2
#define B_P 3
#define B_O 4
#define B_O2 5
#define B_PUB 6
#define B_CQ 7
#define B_QK1 8
#define B_LD 9
#define B_PXF 10
#define B_CV 15
#define B_X2 11
#define B_PX 12
#define B_GO 14
#define B_G1 13

#ifdef PROF
__device__ unsigned int g_ts[NCTA][80][32];
#ifdef GT
#define TCLK() gt32()
#else
#define TCLK() clk32()
#endif
#ifndef TMASK
#define TMASK 0xffffffffu
#endif
#define TST(st, i, c, v) do { if ((TMASK >> (i)) & 1u) asm volatile("{\n.reg .pred q;\nsetp.eq.u32 q, %2, 0;\n@q st.global.u32 [%0], %1;\n}" :: "l"(&g_ts[cta][(st) + 1][i]), "r"((uint32_t)(v)), "r"((uint32_t)(c)) : "memory"); } while (0)
#define TS(i) TST(s, i, l16, TCLK())
#define TV(i, v) TST(s, i, l16, v)
#define TSF(i, w) TST(s, i, l16 | (w8 ^ (w)), TCLK())
#define TSP(i, w) TST(s - 1, i, l16 | (w8 ^ (w)), TCLK())
#define TVF(i, v) TV(i, v)
#else
#define TST(a, b, c, d)
#define TSF(i, w)
#define TSP(i, w)
#define TVF(i, v)
#define TS(i)
#define TV(i, v)
#endif

static __device__ __forceinline__ void bar_sync(int id, int n) { asm volatile("bar.sync %0, %1;" :: "r"(id), "r"(n) : "memory"); }
static __device__ __forceinline__ void bar_arrive(int id, int n) { asm volatile("bar.arrive %0, %1;" :: "r"(id), "r"(n) : "memory"); }
static __device__ __forceinline__ uint4 ldg_r4(const void* p) { uint4 v;
  asm volatile("ld.relaxed.gpu.global.v4.u32 {%0,%1,%2,%3}, [%4];" : "=r"(v.x), "=r"(v.y), "=r"(v.z), "=r"(v.w) : "l"(p) : "memory"); return v; }
static __device__ __forceinline__ uint32_t ldg_r1(const void* p) { uint32_t v;
  asm volatile("ld.relaxed.gpu.global.u32 %0, [%1];" : "=r"(v) : "l"(p) : "memory"); return v; }
template <int OFF> static __device__ __forceinline__ uint32_t ldg_r1o(const void* p) { uint32_t v;
  asm volatile("ld.relaxed.gpu.global.u32 %0, [%1+%2];" : "=r"(v) : "l"(p), "n"(OFF) : "memory"); return v; }
static __device__ __forceinline__ void stg_r4(void* p, uint32_t a, uint32_t b, uint32_t c, uint32_t d) {
  asm volatile("st.relaxed.gpu.global.v4.u32 [%0], {%1,%2,%3,%4};" :: "l"(p), "r"(a), "r"(b), "r"(c), "r"(d) : "memory"); }
static __device__ __forceinline__ void stg_r2(void* p, uint32_t a, uint32_t b) {
  asm volatile("st.relaxed.gpu.global.v2.u32 [%0], {%1,%2};" :: "l"(p), "r"(a), "r"(b) : "memory"); }
static __device__ __forceinline__ uint2 ldg_r2(const void* p) { uint2 v;
  asm volatile("ld.relaxed.gpu.global.v2.u32 {%0,%1}, [%2];" : "=r"(v.x), "=r"(v.y) : "l"(p) : "memory"); return v; }
static __device__ __forceinline__ void stg_4(void* p, const uint4& v) {
  asm volatile("st.global.v4.u32 [%0], {%1,%2,%3,%4};" :: "l"(p), "r"(v.x), "r"(v.y), "r"(v.z), "r"(v.w) : "memory"); }
static __device__ __forceinline__ uint32_t f2u(float v) { return __float_as_uint(v); }
static __device__ __forceinline__ void stg_2(void* p, uint32_t a, uint32_t b) {
  asm volatile("st.global.v2.u32 [%0], {%1,%2};" :: "l"(p), "r"(a), "r"(b) : "memory"); }
static __device__ __forceinline__ void stg_r1(void* p, uint32_t a) {
  asm volatile("st.relaxed.gpu.global.u32 [%0], %1;" :: "l"(p), "r"(a) : "memory"); }
static __device__ __forceinline__ void sts128(uint32_t a, uint32_t x, uint32_t y, uint32_t z, uint32_t w) {
  asm volatile("st.shared.v4.u32 [%0], {%1,%2,%3,%4};" :: "r"(a), "r"(x), "r"(y), "r"(z), "r"(w) : "memory"); }
static __device__ __forceinline__ void sts128f(uint32_t a, float x, float y, float z, float w) {
  asm volatile("st.shared.v4.f32 [%0], {%1,%2,%3,%4};" :: "r"(a), "f"(x), "f"(y), "f"(z), "f"(w) : "memory"); }
static __device__ __forceinline__ uint4 lds128(uint32_t a) { uint4 v;
  asm volatile("ld.shared.v4.u32 {%0,%1,%2,%3}, [%4];" : "=r"(v.x), "=r"(v.y), "=r"(v.z), "=r"(v.w) : "r"(a) : "memory"); return v; }
static __device__ __forceinline__ float4 lds128f(uint32_t a) { float4 v;
  asm volatile("ld.shared.v4.f32 {%0,%1,%2,%3}, [%4];" : "=f"(v.x), "=f"(v.y), "=f"(v.z), "=f"(v.w) : "r"(a) : "memory"); return v; }
static __device__ __forceinline__ void sts32(uint32_t a, uint32_t x) { asm volatile("st.shared.u32 [%0], %1;" :: "r"(a), "r"(x) : "memory"); }
static __device__ __forceinline__ void sts64f(uint32_t a, float x, float y) { asm volatile("st.shared.v2.f32 [%0], {%1,%2};" :: "r"(a), "f"(x), "f"(y) : "memory"); }
static __device__ __forceinline__ uint2 lds64(uint32_t a) { uint2 v;
  asm volatile("ld.shared.v2.u32 {%0,%1}, [%2];" : "=r"(v.x), "=r"(v.y) : "r"(a) : "memory"); return v; }
static __device__ __forceinline__ void st_async4(uint32_t ra, float x, float y, float z, float w, uint32_t rbar) {
  asm volatile("st.async.weak.shared::cluster.mbarrier::complete_tx::bytes.v4.f32 [%0], {%1,%2,%3,%4}, [%5];"
               :: "r"(ra), "f"(x), "f"(y), "f"(z), "f"(w), "r"(rbar) : "memory"); }
static __device__ __forceinline__ void stsm4t(uint32_t a, uint32_t x, uint32_t y, uint32_t z, uint32_t w) {
  asm volatile("stmatrix.sync.aligned.m8n8.x4.trans.shared.b16 [%0], {%1,%2,%3,%4};" :: "r"(a), "r"(x), "r"(y), "r"(z), "r"(w) : "memory"); }
static __device__ __forceinline__ void stsm2t(uint32_t a, uint32_t x, uint32_t y) {
  asm volatile("stmatrix.sync.aligned.m8n8.x2.trans.shared.b16 [%0], {%1,%2};" :: "r"(a), "r"(x), "r"(y) : "memory"); }
static __device__ __forceinline__ uint32_t hfma2(uint32_t a, uint32_t b, uint32_t c) { uint32_t d;
  asm("fma.rn.f16x2 %0, %1, %2, %3;" : "=r"(d) : "r"(a), "r"(b), "r"(c)); return d; }
static __device__ __forceinline__ uint32_t hmax2(uint32_t a, uint32_t b) { uint32_t d;
  asm("max.f16x2 %0, %1, %2;" : "=r"(d) : "r"(a), "r"(b)); return d; }
static __device__ __forceinline__ uint32_t shfl_x(uint32_t a, int m) { uint32_t d;
  asm volatile("shfl.sync.bfly.b32 %0, %1, %2, 0x1f, 0xffffffff;" : "=r"(d) : "r"(a), "r"(m)); return d; }
static __device__ __forceinline__ void h2f(float& lo, float& hi, uint32_t a) {
  asm volatile("{\n.reg .b16 l, h;\nmov.b32 {l, h}, %2;\ncvt.f32.f16 %0, l;\ncvt.f32.f16 %1, h;\n}" : "=f"(lo), "=f"(hi) : "r"(a)); }
static __device__ __forceinline__ uint4 ldsm4(uint32_t a) { uint4 v;
  asm volatile("ldmatrix.sync.aligned.m8n8.x4.shared.b16 {%0,%1,%2,%3}, [%4];" : "=r"(v.x), "=r"(v.y), "=r"(v.z), "=r"(v.w) : "r"(a) : "memory"); return v; }
static __device__ __forceinline__ uint4 ldsm4t(uint32_t a) { uint4 v;
  asm volatile("ldmatrix.sync.aligned.m8n8.x4.trans.shared.b16 {%0,%1,%2,%3}, [%4];" : "=r"(v.x), "=r"(v.y), "=r"(v.z), "=r"(v.w) : "r"(a) : "memory"); return v; }
static __device__ __forceinline__ uint32_t movm(uint32_t a) { uint32_t d;
  asm volatile("movmatrix.sync.aligned.m8n8.trans.b16 %0, %1;" : "=r"(d) : "r"(a)); return d; }
static __device__ __forceinline__ float u2f(uint32_t v) { return __uint_as_float(v); }
static __device__ __forceinline__ uint32_t nz(uint32_t w) { return w == 0u ? 0x8000u : w; }
static __device__ __forceinline__ uint32_t tagw(uint32_t w, uint32_t t) { uint32_t d;
  asm("lop3.b32 %0, %1, %2, 1, 0xd8;" : "=r"(d) : "r"(w), "r"(t)); return d; }
static __device__ __forceinline__ uint32_t pack_m2(float lo, float hi, uint32_t t) { return tagw(pack_bf16(lo, hi), t); }
static __device__ __forceinline__ uint32_t pack_f16(float lo, float hi) { uint32_t d;
  asm("cvt.rn.satfinite.f16x2.f32 %0, %1, %2;" : "=r"(d) : "f"(hi), "f"(lo)); return d; }
static __device__ __forceinline__ void sum_h4(float& lo, float& hi, uint32_t a, uint32_t b, uint32_t c, uint32_t d) {
  const float2 x = __half22float2(*reinterpret_cast<__half2*>(&a)), y = __half22float2(*reinterpret_cast<__half2*>(&b));
  const float2 z = __half22float2(*reinterpret_cast<__half2*>(&c)), w = __half22float2(*reinterpret_cast<__half2*>(&d));
  lo = (x.x + y.x) + (z.x + w.x); hi = (x.y + y.y) + (z.y + w.y);
}
static __device__ __forceinline__ void add_q3(float& lo, float& hi, uint32_t a, uint32_t b, uint32_t c) {
  uint32_t t;
  asm("{\n.reg .b32 u;\nmul.rn.f16x2 u, %1, %4;\nfma.rn.f16x2 u, %2, %4, u;\nfma.rn.f16x2 %0, %3, %4, u;\n}" : "=r"(t) : "r"(a), "r"(b), "r"(c), "r"(0x34003400u));
  const float2 x = __half22float2(*reinterpret_cast<__half2*>(&t));
  lo += x.x; hi += x.y;
}
static __device__ __forceinline__ uint32_t lds32(uint32_t a) { uint32_t v; asm volatile("ld.shared.u32 %0, [%1];" : "=r"(v) : "r"(a) : "memory"); return v; }
static __device__ __forceinline__ uint32_t addb2(uint32_t a, uint32_t b) { uint32_t d;
  asm("add.rn.bf16x2 %0, %1, %2;" : "=r"(d) : "r"(a), "r"(b)); return d; }
static __device__ __forceinline__ uint32_t mulb2(uint32_t a, uint32_t b) { uint32_t d;
  asm("mul.rn.bf16x2 %0, %1, %2;" : "=r"(d) : "r"(a), "r"(b)); return d; }
static __device__ __forceinline__ uint32_t x3(uint32_t a, uint32_t b, uint32_t t) { uint32_t d;
  asm("lop3.b32 %0, %1, %2, %3, 0x7e;" : "=r"(d) : "r"(a), "r"(b), "r"(t)); return d; }
static __device__ __forceinline__ uint32_t or3(uint32_t a, uint32_t b, uint32_t c) { uint32_t d;
  asm("lop3.b32 %0, %1, %2, %3, 0xfe;" : "=r"(d) : "r"(a), "r"(b), "r"(c)); return d; }
static __device__ __forceinline__ uint32_t bad4(const uint4& u, uint32_t t) { return x3(u.x, u.y, t) | x3(u.z, u.w, t); }
static __device__ __forceinline__ uint32_t bad8(const uint4& u, const uint4& v, uint32_t t) {
  return or3(x3(u.x, u.y, t), x3(u.z, u.w, t), x3(v.x, v.y, t)) | x3(v.z, v.w, t); }
static __device__ __forceinline__ float ex2(float x) { float y; asm("ex2.approx.ftz.f32 %0, %1;" : "=f"(y) : "f"(x)); return y; }
static __device__ __forceinline__ float rcpf(float x) { float y; asm("rcp.approx.ftz.f32 %0, %1;" : "=f"(y) : "f"(x)); return y; }
static __device__ __forceinline__ void mbar_wait(uint32_t bar, int parity) {
  asm volatile("{\n.reg .pred p, q;\n.reg .u32 n;\nmbarrier.try_wait.parity.shared::cta.b64 p, [%0], %1;\n@p bra W_DONE;\nmov.u32 n, 0;\n"
               "W_LOOP:\nmbarrier.try_wait.parity.shared::cta.b64 p, [%0], %1;\nadd.u32 n, n, 1;\nsetp.lt.and.u32 q, n, %2, !p;\n@q bra W_LOOP;\nW_DONE:\n}"
               :: "r"(bar), "r"(parity), "n"(SPIN_LIMIT) : "memory");
}
static __device__ __forceinline__ uint32_t mbar_test(uint32_t bar, int parity) { uint32_t ok;
  asm volatile("{\n.reg .pred p;\nmbarrier.test_wait.parity.shared::cta.b64 p, [%1], %2;\nselp.u32 %0, 1, 0, p;\n}" : "=r"(ok) : "r"(bar), "r"(parity) : "memory"); return ok; }
static __device__ __forceinline__ void mbar_arrive(uint32_t bar) {
  asm volatile("mbarrier.arrive.shared::cta.b64 _, [%0];" :: "r"(bar) : "memory"); }
static __device__ __forceinline__ void mbar_arrive_cluster_rlx(uint32_t raddr) {
  asm volatile("mbarrier.arrive.relaxed.cluster.shared::cluster.b64 _, [%0];" :: "r"(raddr) : "memory"); }
static __device__ __forceinline__ void tma_load_mc(uint32_t dst, const CUtensorMap* tm, int c1, int c2, uint32_t bar) {
#ifdef NOTMA
  asm volatile("mbarrier.complete_tx.relaxed.cta.shared::cta.b64 [%0], 32768;" :: "r"(bar) : "memory"); return;
#endif
  asm volatile("cp.async.bulk.tensor.3d.shared::cluster.global.mbarrier::complete_tx::bytes.multicast::cluster [%0], [%1, {%3, %4, %5}], [%2], %6;"
               :: "r"(dst), "l"(tm), "r"(bar), "r"(0), "r"(c1), "r"(c2), "h"((uint16_t)3) : "memory"); }
static __device__ __forceinline__ void cp16(uint32_t dst, const void* src) {
  asm volatile("cp.async.cg.shared.global [%0], [%1], 16;" :: "r"(dst), "l"(src) : "memory"); }
static __device__ __forceinline__ void mma_1688(float (&d)[4], uint32_t a0, uint32_t a1, uint32_t b0) {
  asm volatile("mma.sync.aligned.m16n8k8.row.col.f32.bf16.bf16.f32 {%0,%1,%2,%3}, {%4,%5}, {%6}, {%0,%1,%2,%3};"
               : "+f"(d[0]), "+f"(d[1]), "+f"(d[2]), "+f"(d[3]) : "r"(a0), "r"(a1), "r"(b0)); }
static __device__ __forceinline__ void mma4(float (&d)[4], uint32_t a0, uint32_t a1, uint32_t a2, uint32_t a3, uint32_t b0, uint32_t b1) {
  asm volatile("mma.sync.aligned.m16n8k16.row.col.f32.bf16.bf16.f32 {%0,%1,%2,%3}, {%4,%5,%6,%7}, {%8,%9}, {%0,%1,%2,%3};"
               : "+f"(d[0]), "+f"(d[1]), "+f"(d[2]), "+f"(d[3]) : "r"(a0), "r"(a1), "r"(a2), "r"(a3), "r"(b0), "r"(b1)); }
static __device__ __forceinline__ void mma4z(float (&d)[4], uint32_t a0, uint32_t a1, uint32_t a2, uint32_t a3, uint32_t b0, uint32_t b1) {
  asm volatile("mma.sync.aligned.m16n8k16.row.col.f32.bf16.bf16.f32 {%0,%1,%2,%3}, {%4,%5,%6,%7}, {%8,%9}, {%10,%10,%10,%10};"
               : "=f"(d[0]), "=f"(d[1]), "=f"(d[2]), "=f"(d[3]) : "r"(a0), "r"(a1), "r"(a2), "r"(a3), "r"(b0), "r"(b1), "f"(0.f)); }
static __device__ __forceinline__ void mma4h(float (&d)[4], uint32_t a0, uint32_t a1, uint32_t a2, uint32_t a3, uint32_t b) {
  asm volatile("mma.sync.aligned.m16n8k16.row.col.f32.f16.f16.f32 {%0,%1,%2,%3}, {%4,%5,%6,%7}, {%8,%8}, {%0,%1,%2,%3};"
               : "+f"(d[0]), "+f"(d[1]), "+f"(d[2]), "+f"(d[3]) : "r"(a0), "r"(a1), "r"(a2), "r"(a3), "r"(b)); }
static __device__ __forceinline__ void mma2h(float (&d)[4], uint32_t a0, uint32_t a1, uint32_t b) {
  asm volatile("mma.sync.aligned.m16n8k8.row.col.f32.f16.f16.f32 {%0,%1,%2,%3}, {%4,%5}, {%6}, {%0,%1,%2,%3};"
               : "+f"(d[0]), "+f"(d[1]), "+f"(d[2]), "+f"(d[3]) : "r"(a0), "r"(a1), "r"(b)); }
static __device__ __forceinline__ uint32_t clk32() { uint32_t t; asm volatile("mov.u32 %0, %%clock;" : "=r"(t)); return t; }
static __device__ __forceinline__ uint32_t gt32() { uint32_t t; asm volatile("mov.u32 %0, %%globaltimer_lo;" : "=r"(t)); return t; }
static __device__ __forceinline__ void spin(int clk) { if (clk > 0) { uint32_t t = clk32(); while (clk32() - t < (uint32_t)clk) {} } }
#define FENCE() asm volatile("griddepcontrol.launch_dependents;" ::: "memory")
#define OPAQUE_L(p) asm volatile("" : "+l"(p))
#define OPAQUE_R(p) asm volatile("" : "+r"(p))

template <int KK, int K1, int W0, int NW, int FIRST> struct XR {
  static __device__ __forceinline__ void run(float (&d)[16], const uint32_t (&w)[NW][4], uint32_t b16) {
#ifdef NOWG
    if (KK % NOWG == 0)
#endif
    wgmma_n32_ra<(KK >> 2) * 4096 + (KK & 3) * 32, !FIRST>(d, w[W0 + KK], b16);
    XR<KK + 1, K1, W0, NW, 0>::run(d, w, b16);
  }
};
template <int K1, int W0, int NW, int FIRST> struct XR<K1, K1, W0, NW, FIRST> { static __device__ __forceinline__ void run(float (&)[16], const uint32_t (&)[NW][4], uint32_t) {} };
template <int KK, int K0, int K1, int FIRST> struct XS {
  static __device__ __forceinline__ void run(float (&d)[16], uint32_t a16, uint32_t b16) {
#ifdef NOWG
    if (KK % NOWG == 0)
#endif
    wgmma_n32_ss_ta<(KK - K0) * 2048, (KK >> 2) * 4096 + (KK & 3) * 32, !FIRST>(d, a16, b16);
    XS<KK + 1, K0, K1, 0>::run(d, a16, b16);
  }
};
template <int K0, int K1, int FIRST> struct XS<K1, K0, K1, FIRST> { static __device__ __forceinline__ void run(float (&)[16], uint32_t, uint32_t) {} };

static __device__ bf16 g_h[8 * FF];
static __device__ unsigned int g_sbar;
struct SideParams { const bf16* x; const bf16* w_r; const bf16* w_gate; const bf16* w_up; const bf16* w_down; const bf16* gate_w; const bf16* Wo; };

static __device__ __forceinline__ void side_barrier(unsigned int target) {
  __syncthreads();
  if (threadIdx.x == 0) {
    __threadfence();
    atomicAdd(&g_sbar, 1u);
    int n = 0;
    while (*(volatile unsigned int*)&g_sbar < target) { if (++n > (1 << 22)) { g_err = 50; break; } }
    __threadfence();
  }
  __syncthreads();
}
static __device__ __forceinline__ uint4 ldg_nc(const void* p) { uint4 v;
  asm volatile("ld.global.nc.L1::no_allocate.v4.u32 {%0,%1,%2,%3}, [%4];" : "=r"(v.x), "=r"(v.y), "=r"(v.z), "=r"(v.w) : "l"(p)); return v; }
#ifndef SPD
#define SPD 3
#endif
static __device__ __forceinline__ void l2pf(const void* p) { asm volatile("prefetch.global.L2 [%0];" :: "l"(p)); }
static __device__ __forceinline__ void mm8(float (&acc)[8][4], const bf16* W, const bf16* Wn, int ldw, int nk16, uint32_t abase, int lane) {
  const int g = lane >> 2, t = lane & 3;
  const bf16* wp = W + (size_t)(2 * t) * ldw + g * 8;
#pragma unroll 1
  for (int k = 0; k < nk16; k += 4) {
    {
      const int kp = k + 4 * SPD;
      const bf16* pf = kp < nk16 ? W + (size_t)(kp * 16) * ldw : Wn ? Wn + (size_t)((kp - nk16) * 16) * ldw : nullptr;
      if (pf) { l2pf(pf + (size_t)lane * ldw); l2pf(pf + (size_t)(lane + 32) * ldw); }
    }
    uint4 r[4][4];
#pragma unroll
    for (int u = 0; u < 4; u++) {
      const bf16* q = wp + (size_t)(k + u) * 16 * ldw;
      r[u][0] = ldg_nc(q); r[u][1] = ldg_nc(q + ldw); r[u][2] = ldg_nc(q + 8 * ldw); r[u][3] = ldg_nc(q + 9 * ldw);
    }
#pragma unroll
    for (int u = 0; u < 4; u++) {
      uint32_t a0, a2;
      asm volatile("ld.shared.u32 %0, [%1];" : "=r"(a0) : "r"(abase + (k + u) * 32));
      asm volatile("ld.shared.u32 %0, [%1];" : "=r"(a2) : "r"(abase + (k + u) * 32 + 16));
      const uint32_t* p0 = reinterpret_cast<const uint32_t*>(&r[u][0]); const uint32_t* p1 = reinterpret_cast<const uint32_t*>(&r[u][1]);
      const uint32_t* p2 = reinterpret_cast<const uint32_t*>(&r[u][2]); const uint32_t* p3 = reinterpret_cast<const uint32_t*>(&r[u][3]);
#pragma unroll
      for (int i = 0; i < 8; i++) {
        const uint32_t sel = (i & 1) ? 0x7632u : 0x5410u;
        mma4(acc[i], a0, 0u, a2, 0u, __byte_perm(p0[i >> 1], p1[i >> 1], sel), __byte_perm(p2[i >> 1], p3[i >> 1], sel));
      }
    }
  }
}
static __device__ __noinline__ void side_work(const SideParams& P, unsigned char* smem, int q) {
  const int tid = threadIdx.x, lane = tid & 31, warp = tid >> 5, g = lane >> 2, t = lane & 3;
  const uint32_t sb = smem_u32(smem);
  unsigned int* cand = reinterpret_cast<unsigned int*>(smem);
  bf16* xs = reinterpret_cast<bf16*>(smem + 1024);
  float* part = reinterpret_cast<float*>(smem + 65536);
  {
    for (int i = tid; i < 256; i += 384) *reinterpret_cast<uint4*>(smem + 1024 + i * 16) = ldg_nc((i < 128 ? P.gate_w : P.w_r - DM) + i * 8);
    __syncthreads();
#pragma unroll 1
    for (int it = warp; it < 64; it += 12) {
      const bf16* xp = P.x + (size_t)(q * 512 + (it >> 1) * 16 + g) * DM + (it & 1) * 512 + t * 8;
      for (int a = it == warp ? 0 : 1; a < 2 && it + 12 * a < 64; a++)
#pragma unroll
        for (int i = 0; i < 4; i++) l2pf(P.x + (size_t)(q * 512 + (it >> 1) * 16 + a * 96 + i * 4 + (lane >> 3)) * DM + (it & 1) * 512 + (lane & 7) * 64);
      uint4 lo[16], hi[16];
#pragma unroll
      for (int i = 0; i < 16; i++) { lo[i] = ldg_nc(xp + i * 32); hi[i] = ldg_nc(xp + 8 * DM + i * 32); }
      float sg[4] = {0.f, 0.f, 0.f, 0.f}, sr[4] = {0.f, 0.f, 0.f, 0.f};
#pragma unroll
      for (int i = 0; i < 16; i++) {
        const uint4 gw = lds128(sb + 1024 + (it & 1) * 1024 + i * 64 + t * 16), wr = lds128(sb + 3072 + (it & 1) * 1024 + i * 64 + t * 16);
        mma4(sr, lo[i].x, hi[i].x, lo[i].y, hi[i].y, wr.x, wr.y); mma4(sr, lo[i].z, hi[i].z, lo[i].w, hi[i].w, wr.z, wr.w);
        mma4(sg, mulb2(lo[i].x, gw.x), mulb2(hi[i].x, gw.x), mulb2(lo[i].y, gw.y), mulb2(hi[i].y, gw.y), 0x3F803F80u, 0x3F803F80u);
        mma4(sg, mulb2(lo[i].z, gw.z), mulb2(hi[i].z, gw.z), mulb2(lo[i].w, gw.w), mulb2(hi[i].w, gw.w), 0x3F803F80u, 0x3F803F80u);
      }
      if (t == 0) {
        float* pp = part + (it & 1) * 1024 + (it >> 1) * 16 + g;
        pp[0] = sg[0]; pp[8] = sg[2]; pp[512] = sr[0]; pp[520] = sr[2];
      }
    }
    __syncthreads();
    for (int i = tid; i < 512; i += 384) {
      g_gate[q * 512 + i] = rbf(1.f / (1.f + expf(-rbf(part[i] + part[1024 + i]))));
      g_r[q * 512 + i] = rbf(part[512 + i] + part[1536 + i]);
    }
  }
#define GU(u) (((u) % 28) / 14 ? P.w_up : P.w_gate) + (size_t)((u) / 28) * 512 * FF + q * 896 + ((u) % 14) * 64
  for (int i = lane; i < 64 * SPD; i += 32) l2pf(GU(warp) + (size_t)i * FF);
  side_barrier(4);
  {
    unsigned int key[8];
#pragma unroll
    for (int i = 0; i < 8; i++) {
      const int tok = (warp & 7) * 256 + i * 32 + lane;
      const uint32_t b = __float_as_uint(__ldcg(&g_r[tok]) + 0.f) >> 16;
      key[i] = (((b & 0x8000u) ? (~b & 0xffffu) : (b | 0x8000u)) << 16) | (uint32_t)(2047 - tok);
    }
    for (int pass = 0; pass < 2; pass++) {
      if (pass == 0 ? warp < 8 : warp == 0) {
        for (int c = 0; c < 8; c++) {
          const unsigned int m = __reduce_max_sync(~0u, max(max(max(key[0], key[1]), max(key[2], key[3])), max(max(key[4], key[5]), max(key[6], key[7]))));
#pragma unroll
          for (int i = 0; i < 8; i++) if (key[i] == m) key[i] = 0u;
          if (lane == 0) cand[pass ? 128 + c : warp * 8 + c] = m;
        }
      }
      __syncthreads();
      if (pass == 0 && warp == 0) {
#pragma unroll
        for (int i = 0; i < 8; i++) key[i] = i < 2 ? cand[i * 32 + lane] : 0u;
      }
    }
    if (q == 0 && tid < 8) g_idx[tid] = 2047 - (int)(cand[128 + tid] & 0xffffu);
    for (int i = tid; i < 1024; i += 384) {
      const int c = i >> 7, tok = 2047 - (int)(cand[128 + c] & 0xffffu);
      *reinterpret_cast<uint4*>(xs + c * (FF + 8) + (i & 127) * 8) = ldg_nc(P.x + (size_t)tok * DM + (i & 127) * 8);
    }
    __syncthreads();
  }
#ifdef NOFFN
  return;
#endif
  const uint32_t abase = sb + 1024 + g * (FF + 8) * 2 + t * 4;
  for (int u = warp; u < 56; u += 12) {
    const int kh = u / 28, mat = (u % 28) / 14, cb = u % 14;
    float acc[8][4];
#pragma unroll
    for (int i = 0; i < 8; i++) acc[i][0] = acc[i][1] = acc[i][2] = acc[i][3] = 0.f;
    mm8(acc, GU(u), u + 12 < 56 ? GU(u + 12) : nullptr, FF, DM / 32, abase + kh * 1024, lane);
    float* pp = part + ((kh * 2 + mat) * 8 + g) * 896 + cb * 64 + 16 * t;
#pragma unroll
    for (int i = 0; i < 8; i++) { pp[i] = acc[i][0]; pp[8 + i] = acc[i][1]; }
  }
  for (int i = lane; i < 64 * SPD; i += 32) l2pf(P.w_down + (size_t)((warp >> 2) * 1216 + i) * DM + q * 256 + (warp & 3) * 64);
  __syncthreads();
  for (int i = tid; i < 8 * 896; i += 384) {
    const float ag = rbf(part[i] + part[16 * 896 + i]), au = rbf(part[8 * 896 + i] + part[24 * 896 + i]);
    g_h[(i / 896) * FF + q * 896 + i % 896] = __float2bfloat16(rbf(ag / (1.f + expf(-ag))) * au);
  }
  side_barrier(8);
  for (int i = tid; i < 8 * FF / 8; i += 384) {
    const int c = i / (FF / 8), o = i % (FF / 8);
    *reinterpret_cast<uint4*>(xs + c * (FF + 8) + o * 8) = __ldcg(reinterpret_cast<const uint4*>(g_h + c * FF + o * 8));
  }
  __syncthreads();
  {
    const int cb = warp & 3, kq = warp >> 2;
    float acc[8][4];
#pragma unroll
    for (int i = 0; i < 8; i++) acc[i][0] = acc[i][1] = acc[i][2] = acc[i][3] = 0.f;
    mm8(acc, P.w_down + (size_t)kq * 1216 * DM + q * 256 + cb * 64, nullptr, DM, kq == 2 ? 72 : 76, abase + kq * 1216 * 2, lane);
#pragma unroll
    for (int i = 0; i < 8; i++) { part[(kq * 8 + g) * 256 + cb * 64 + 16 * t + i] = acc[i][0]; part[(kq * 8 + g) * 256 + cb * 64 + 16 * t + 8 + i] = acc[i][1]; }
    __syncthreads();
    for (int i = tid; i < 2048; i += 384) {
      const int c = i >> 8, tok = 2047 - (int)(cand[128 + c] & 0xffffu);
      const float y = (part[i] + part[2048 + i]) + part[4096 + i];
      const float rs = rbf(1.f / (1.f + expf(-__ldcg(&g_r[tok]))));
      g_upd[c * DM + q * 256 + (i & 255)] = __float2bfloat16(rbf(y) * rs);
    }
  }
}
struct RecParams { const bf16* mem0; unsigned char* win; };
struct WMaps { CUtensorMap q, k, v; };
#ifndef RLX
#define RLX 1
#endif
#ifndef DLY_SIDE
#define DLY_SIDE 16000
#endif
#ifndef WSPL
#define WSPL 1
#endif

#ifndef DLY_S
#define DLY_S 210
#endif
#ifndef DLY_V
#define DLY_V 350
#endif
#ifndef DLY_M3
#define DLY_M3 632
#endif
#ifndef RF_FAT
#define RF_FAT 208
#endif
#ifndef RF_CTL
#define RF_CTL 88
#endif
#ifndef NCH
#define NCH 2
#endif
#ifndef WPF
#define WPF 7
#endif
#ifndef WRF
#define WRF 7
#endif
#ifndef VPF
#define VPF 2
#endif
#ifndef DLY_WO
#define DLY_WO 850
#endif
#ifndef XPF
#define XPF 4
#endif
#ifndef DLY_FA
#define DLY_FA 50
#endif
#ifndef DLY_XL
#define DLY_XL 300
#endif
#ifndef NPROBE
#define NPROBE 3
#endif
#ifndef PA
#define PA 1
#endif
#ifndef KU
#define KU 32
#endif
#ifndef KD
#define KD 4
#endif
#ifndef DLY_RR
#define DLY_RR 430
#endif
#ifndef GW
#define GW 0
#endif
#ifndef BI
#define BI 0
#endif
#ifndef BR
#define BR 8
#endif
#ifndef BG
#define BG 1
#endif
#ifndef VI
#define VI 1
#endif
#ifndef DLY_VI
#define DLY_VI 0
#endif
#ifndef F0W
#define F0W 0
#endif
#ifndef DLY_B
#define DLY_B 0
#endif
#ifndef BGT
#define BGT 0
#endif
#ifndef EG
#define EG 0
#endif
#ifndef W0I
#define W0I 0
#endif
#ifndef XH
#define XH 1
#endif
#ifndef F1L
#define F1L 1
#endif
#ifndef QB
#define QB 0
#endif
#ifndef LN
#define LN 0
#endif
#ifndef NSW
#define NSW 0
#endif
#ifndef EPI
#define EPI 0
#endif
#ifndef PXE
#define PXE 0
#endif
#ifndef GF
#define GF 12
#endif
#ifndef WNS
#define WNS -1
#endif
#ifndef DLY_NW
#define DLY_NW 160
#endif
#ifndef ETW
#define ETW 0
#endif
#ifndef KB
#define KB 6
#endif
#ifndef H16
#define H16 1
#endif
#ifndef DLY_N
#define DLY_N 0
#endif
#ifndef F1C
#define F1C 2
#endif
#ifndef KA
#define KA 0
#endif
#define KEEP() do { float kd[4]; mma4z(kd, 0u, 0u, 0u, 0u, 0u, 0u); } while (0)
#ifndef WKA
#define WKA 8
#endif
#ifndef WPA
#define WPA 4
#endif
#ifndef F0T
#define F0T 1
#endif
#ifndef DLY_K
#define DLY_K 1280
#endif
#ifndef DLY_KS
#define DLY_KS 900
#endif
#ifndef DLY_E
#define DLY_E 0
#endif
#ifndef DLY_PF
#define DLY_PF 10
#endif
#ifndef DLY_F0
#define DLY_F0 300
#endif
#ifndef DLY_XD
#define DLY_XD 200
#endif
#ifndef DLY_PX
#define DLY_PX 60
#endif
#ifndef DLY_TB
#define DLY_TB 700
#endif
#if 1
#define NTUNE 10
#define TUNE_NAMES {"OM3", "XL", "S", "NW", "WO", "PX", "V", "OK", "OKS", "ORR"}
__constant__ int g_tune[NTUNE] = {DLY_M3, DLY_XL, DLY_S, DLY_NW, DLY_WO, DLY_PX, DLY_V, DLY_K, DLY_KS, DLY_RR};
#undef DLY_M3
#define DLY_M3 g_tune[0]
#undef DLY_XL
#define DLY_XL g_tune[1]
#undef DLY_S
#define DLY_S g_tune[2]
#undef DLY_NW
#define DLY_NW g_tune[3]
#undef DLY_WO
#define DLY_WO g_tune[4]
#undef DLY_PX
#define DLY_PX g_tune[5]
#undef DLY_V
#define DLY_V g_tune[6]
#undef DLY_K
#define DLY_K g_tune[7]
#undef DLY_RR
#define DLY_RR g_tune[9]
#undef DLY_KS
#define DLY_KS g_tune[8]
#endif
#ifdef PROBE
__constant__ int g_probe[16];
#define PRB(i) spin(g_probe[i])
#else
#define PRB(i)
#endif
#ifdef PER
__device__ unsigned g_pclk[NCTA][64], g_per[NCTA][64], g_end[8] = {0, 0, 0, 0, 0, 0, 0, 100000};
#endif
#define ADD3(a, b, c) addb2(addb2(a, c), b)
#define STR2(x) #x
#define STR(x) STR2(x)

static __device__ __forceinline__ void cp16p(uint32_t dst, const void* src, uint32_t v) {
  asm volatile("{\n.reg .pred q;\nsetp.ne.u32 q, %2, 0;\n@q cp.async.cg.shared.global [%0], [%1], 16;\n}" :: "r"(dst), "l"(src), "r"(v) : "memory"); }
static __device__ __forceinline__ void red_bf2(void* p, uint32_t v) {
  asm volatile("red.relaxed.gpu.global.add.noftz.bf16x2 [%0], %1;" :: "l"(p), "r"(v) : "memory"); }
static __device__ __forceinline__ void red_bf2p(void* p, uint32_t v, uint32_t e) {
  asm volatile("{\n.reg .pred q;\nsetp.lt.u32 q, %2, 2;\n@q red.relaxed.gpu.global.add.noftz.bf16x2 [%0], %1;\n}" :: "l"(p), "r"(v), "r"(e) : "memory"); }
static __device__ __forceinline__ void red_bf2p4(void* p, uint32_t v, uint32_t e) {
  asm volatile("{\n.reg .pred q;\nsetp.lt.u32 q, %2, 4;\n@q red.relaxed.gpu.global.add.noftz.bf16x2 [%0], %1;\n}" :: "l"(p), "r"(v), "r"(e) : "memory"); }
static __device__ __forceinline__ void sts16(uint32_t a, uint32_t x) { asm volatile("{\n.reg .b16 h;\ncvt.u16.u32 h, %1;\nst.shared.u16 [%0], h;\n}" :: "r"(a), "r"(x) : "memory"); }
static __device__ __forceinline__ uint32_t cnt_word(uint32_t L) { return (L & 17u) | ((L & 6u) << 1) | ((L & 8u) >> 2); }
static __device__ __forceinline__ uint32_t cnt_line(uint32_t l) { return (l & 17u) | ((l & 12u) >> 1) | ((l & 2u) << 2); }
static __device__ __forceinline__ int m3_check(uint32_t sb, const unsigned char* p3, const unsigned char* pd, int dq, uint32_t l16, uint32_t mc, int hf, int s) {
  const uint32_t md = l16 + (sb + SM_MEM + hf * 8192), dd = l16 + (sb + SM_RD + hf * 256), dc = (l16 >> 2) + (sb + SM_RD + hf * 256);
  int n = 0;
  uint32_t c0 = 0, c1 = 0, d0 = 0, d1 = 0;
#pragma unroll 1
  do {
    if (n) {
      const int src = cnt_word(l16 >> 4);
      const uint32_t m0 = __ballot_sync(~0u, (__shfl_sync(~0u, c0, src) >> 16) != 0x4200u) >> (l16 >> 7), m1 = __ballot_sync(~0u, (__shfl_sync(~0u, c1, src) >> 16) != 0x4200u) >> (l16 >> 7);
      const uint32_t m2 = __ballot_sync(~0u, (d0 >> 16) != 0x4200u), m3 = __ballot_sync(~0u, (d1 >> 16) != 0x4200u);
#pragma unroll
      for (int i = 0; i < 8; i++) { cp16p(md + i * 512, p3 + i * 1024, m0 & (1u << (4 * i))); cp16p(md + 4096 + i * 512, p3 + dq + i * 1024, m1 & (1u << (4 * i))); }
      cp16p(dd, pd, l16 < 256u ? (((l16 & 128u) ? m3 : m2) >> ((l16 >> 2) & 28u)) & 15u : 0u);
      sts32(sb + SM_Z + 40, s);
      asm volatile("cp.async.commit_group;\ncp.async.wait_group 0;" ::: "memory");
      __syncwarp();
    }
    n++;
    mbar_wait(sb + SM_BAR + MB_G + hf * 8, s & 1);
    c0 = lds32(mc); c1 = lds32(mc + 4096); d0 = lds32(dc); d1 = lds32(dc + 128);
  } while (__any_sync(~0u, (x3(c0, c1, 0x42000000u) | x3(d0, d1, 0x42000000u)) >= 0x10000u) && n < SPIN_LIMIT);
  PRB(4);
  sts16(mc + 2, d0); sts16(mc + 4098, d1);
  mbar_arrive(sb + SM_BAR + MB_MEM + hf * 8);
  return n - 1;
}

__global__ void __cluster_dims__(2, 1, 1) __launch_bounds__(384, 1)
rec_kernel(const __grid_constant__ CUtensorMap tmx, const __grid_constant__ CUtensorMap tmw, const __grid_constant__ WMaps W, RecParams P, const __grid_constant__ SideParams SP) {
  extern __shared__ __align__(1024) unsigned char smem[];
  asm volatile("griddepcontrol.launch_dependents;");
  const uint32_t sb = smem_u32(smem);
  const int tid = threadIdx.x, lane = tid & 31, t128 = tid & 127;
  const int wg = __shfl_sync(~0u, tid >> 7, 0), wq = __shfl_sync(~0u, (tid >> 5) & 3, 0);
  const int r = blockIdx.x & 1, pp = blockIdx.x >> 1;
  const int mi = lane >> 3, r8 = lane & 7;
  const uint32_t xb16 = __shfl_sync(~0u, (((sb + SM_X + (tid >> 7) * 32768 + r * 16384) & 0x3FFFF) >> 4) | (1u << 16), 0);
  const uint32_t va16 = __shfl_sync(~0u, (((sb + SM_WVS + (tid >> 7) * 16384) & 0x3FFFF) >> 4) | (64u << 16), 0);
#ifdef PER
  const uint32_t tstart = gt32();
#endif

  if (tid == 0) {
    mbar_init(sb + SM_BAR + MB_F, BGT == 2 ? 8 : BGT == 1 ? 4 : 1); mbar_init(sb + SM_BAR + MB_F + 8, 1); mbar_init(sb + SM_BAR + MB_XE0, 2); mbar_init(sb + SM_BAR + MB_XE1, 2); mbar_init(sb + SM_BAR + MB_INIT, 2);
    mbar_init(sb + SM_BAR + MB_MEM, 32); mbar_init(sb + SM_BAR + MB_MEM + 8, 32); mbar_init(sb + SM_BAR + MB_W, 1); mbar_init(sb + SM_BAR + MB_W + 8, 1);
    mbar_init(sb + SM_BAR + MB_XF, 8); mbar_init(sb + SM_BAR + MB_X0, 1); mbar_init(sb + SM_BAR + MB_WO, 1); mbar_init(sb + SM_BAR + MB_VR, 5); mbar_init(sb + SM_BAR + MB_G, 32); mbar_init(sb + SM_BAR + MB_G + 8, 32);
    sts32(sb + SM_Z + 40, ~0u);
    asm volatile("fence.mbarrier_init.release.cluster;" ::: "memory");
  }
  if (tid == 32) {
    asm volatile("prefetch.tensormap [%0];" :: "l"(&W.q) : "memory"); asm volatile("prefetch.tensormap [%0];" :: "l"(&W.k) : "memory");
    asm volatile("prefetch.tensormap [%0];" :: "l"(&W.v) : "memory"); asm volatile("prefetch.tensormap [%0];" :: "l"(&tmx) : "memory");
  }
  if (tid >= 256 && tid < 320) {
    unsigned char* pl = P.win + r * W_2 + (W_UP | (1u << 19) | ((pp >> 5) << 14)) + (pp & 31) * 128 + wq * 4096;
    stg_r1(pl + lane * 4, 0u);
    uint32_t best = 1u << 30, acc = 0;
#pragma unroll 1
    for (int rep = 0; rep < NPROBE; rep++) {
      uint32_t v = 0, t1; const uint32_t t0 = clk32();
      if (lane == 0) asm volatile("atom.relaxed.gpu.global.add.u32 %0, [%1], 2;" : "=r"(v) : "l"(pl + acc) : "memory");
      acc = v >> 31;
      asm volatile("{\n.reg .u32 x;\nadd.u32 x, %1, 0;\nmov.u32 %0, %%clock;\n}" : "=r"(t1) : "r"(acc));
      best = min(best, t1 - t0 + acc);
    }
    if (lane == 0) sts32(sb + SM_SIDE + wq * 4, best);
    bar_sync(B_P, 64);
    if (wq == 0) {
      const uint2 bt = lds64(sb + SM_SIDE);
      if (lane < 8 && (r == 0 || pp == 0)) stg_r1(&g_side[(r ? 66 : pp) * 32 + lane], 2u | (bt.x < bt.y ? 1u : 0u));
      spin(DLY_TB);
      uint32_t a, b, c; int n = 0;
#pragma unroll 1
      do {
        a = ldg_r1(&g_side[lane * 32]); b = ldg_r1(&g_side[(32 + lane) * 32]); c = ldg_r1(&g_side[(64 + min(lane, 2)) * 32]);
      } while (!__all_sync(~0u, a & b & c & 2u) && ++n < SPIN_LIMIT);
      a = __ballot_sync(~0u, a & 1u); b = __ballot_sync(~0u, b & 1u); c = __ballot_sync(~0u, c & 1u);
      const uint32_t pol2 = (a ^ (c >> 2)) & 1u;
      c &= 3u;
      const unsigned long long ab = ((unsigned long long)b << 32) | a;
      const int sd = pp < 64 ? (int)(ab >> pp) & 1 : (int)(c >> (pp - 64)) & 1;
      const int n1 = __popcll(ab) + __popc(c), n0 = 66 - n1;
      const int below1 = pp < 64 ? __popcll(ab & ((1ull << pp) - 1)) : __popcll(ab) + (pp == 65 ? (int)(c & 1u) : 0);
      const int rk = sd ? below1 : pp - below1;
      const int k0 = (n0 & 1) ? n0 - 1 : n0 >= n1 ? n0 - 2 : n0, k1 = 64 - k0;
      const int role = rk >= (sd ? k1 : k0) ? 64 + ((n0 & 1) ? sd : rk - (sd ? k1 : k0)) : sd ? k0 + rk : rk;
      __syncwarp();
      if (lane == 0) sts128(sb + SM_SIDE, 2 * k0, 0u, pol2, role * 2 + r);
#ifdef PER
      if (lane == 0) { atomicMax(&g_end[6], gt32()); atomicMin(&g_end[7], max(bt.x, bt.y) - min(bt.x, bt.y)); }
#endif
    }
  }
  __syncthreads();
  const int cta = __shfl_sync(~0u, (int)lds32(sb + SM_SIDE + 12), 0), h = cta >> 2, j = cta & 3, p = j >> 1;
  const int sw = (cta >= __shfl_sync(~0u, (int)lds32(sb + SM_SIDE), 0) ? 1 : 0) ^ r ^ NSW;
  if (cta >= NCTA) {
    spin(DLY_SIDE);
#ifndef NOSIDE
    side_work(SP, smem, cta - NCTA);
#endif
#ifdef PER
    if (threadIdx.x == 0) atomicMax(&g_end[1], gt32());
#endif
    return;
  }
#ifdef PER
  if (threadIdx.x == 0) g_per[cta][63] = tstart;
#endif
  asm volatile("barrier.cluster.arrive.relaxed.aligned;" ::: "memory");
#define WLOAD(i0, i1) _Pragma("unroll 1") for (int u = i0; u < i1; u++) {        \
    const int g2 = u >> 2, i = u & 3, k = g2 * 512 + ((i * 128 + r * 256) & 511); \
    const uint32_t mb = sb + SM_BAR + MB_W + g2 * 8; \
    tma_load_2d(sb + g2 * 65536 + i * 8192, &W.q, h * DH + j * 32, k, mb); \
    tma_load_2d(sb + g2 * 65536 + 32768 + i * 8192, &W.k, h * DH + j * 32, k, mb); \
    if (i < 2) tma_load_2d(sb + (i ? SM_WVS : SM_VST) + g2 * 16384, &W.v, h * DH + p * 64, k, mb); }
  if (tid == 288) {
    mbar_expect_tx(sb + SM_BAR + MB_X0, 32768);
#pragma unroll 1
    for (int i = 0; i < 2; i++)
      asm volatile("cp.async.bulk.tensor.3d.shared::cluster.global.mbarrier::complete_tx::bytes [%0], [%1, {%3, %3, %4}], [%2];"
                   :: "r"(sb + SM_MEM + i * 16384), "l"(&tmx), "r"(sb + SM_BAR + MB_X0), "r"(0), "r"(i * 4) : "memory");
    mbar_expect_tx(sb + SM_BAR + MB_W, 98304); mbar_expect_tx(sb + SM_BAR + MB_W + 8, 98304);
    WLOAD(0, 4 + WSPL);
  }
  __syncwarp();
  asm volatile("barrier.cluster.wait.acquire.aligned;" ::: "memory");
#define SIDES() const uint4 sm2 = lds128(sb + SM_SIDE); const int nlo = sm2.x; const uint32_t me = cta >= nlo

#define XLOAD(t, sg) tma_load_mc(sb + SM_X + ((t) * 8 + r * 4) * 4096, &tmx, (sg) * SEG, (t) * 8 + r * 4, sb + SM_BAR + MB_F + (t) * 8)
#define F0LOAD() do { mbar_wait(sb + SM_BAR + MB_XE0, s & 1); \
    if (l16 == 0) XLOAD(0, s + 2); \
    __syncwarp(); } while (0)
  if (wg < 2) {
    asm volatile("setmaxnreg.inc.sync.aligned.u32 " STR(RF_FAT) ";");
    uint32_t w[32][4], wv[8][4];
    uint32_t lm = ((mi >> 1) * 8 + r8) * 128 + (((wq * 2 + (mi & 1)) ^ r8) << 4), l16 = lane * 16;
    lm = __shfl_sync(~0u, lm, lane); l16 = __shfl_sync(~0u, l16, lane);
    mbar_wait(sb + SM_BAR + MB_W + wg * 8, 0);
    {
      const uint32_t lq0 = sb + wg * 65536 + (wq >> 1) * 32768 + ((mi >> 1) * 8 + r8) * 64 + ((((wq & 1) * 2 + (mi & 1)) ^ (r8 >> 1)) << 4);
#pragma unroll
      for (int kk = 0; kk < 32; kk++) ldmatrix_x4_trans(w[kk], lq0 + kk * 1024);
    }
#pragma unroll
    for (int kk = 0; kk < 8; kk++) ldmatrix_x4_trans(wv[kk], sb + SM_VST + wg * 16384 + kk * 2048 + lm);
    if (wg == 0) bar_sync(B_V, 160);
    else bar_arrive(B_P, 224);
    const int w8 = wg * 4 + wq;
    const int cw = sw ^ wg, near = wg ^ 1 ^ NSW;
    const uint32_t xh16 = xb16 ^ 1024u;
    const uint32_t rsb = mapa(sb, r ^ 1);
#define MT (l16 + (sb + SM_MEM + wg * 8192))
#define WA (lm + (sb + SM_WVS + wg * 16384))
#define WOF(f) (lm + (sb + SM_WOS + wg * 32768 + ((f) & 1) * 16384 + ((f) >> 1) * 2048))
#define TH(base) (l16 + (sb + (base) + w8 * 512))
#define TQ(base) (l16 + (sb + (base) + wq * 512))
#define DUMP(base) _Pragma("unroll") for (int n = 0; n < 4; n++) sts128f(TQ((base) + n * 2048), d[4 * n], d[4 * n + 1], d[4 * n + 2], d[4 * n + 3])
#define INIT(base) _Pragma("unroll") for (int n = 0; n < 4; n++) { const float4 t = lds128f(TQ((base) + n * 2048)); d[4 * n] = t.x; d[4 * n + 1] = t.y; d[4 * n + 2] = t.z; d[4 * n + 3] = t.w; }
#define XQK(first, b0, b1) do { wg_fence(); XR<0, 16, 0, 32, first>::run(d, w, b0); XR<0, 16, 16, 32, 0>::run(d, w, b1); wg_commit(); wg_wait0(); } while (0)
#define XVS(first, b0) do { wg_fence(); XS<8, 8, 16, first>::run(d, va16, b0); XR<0, 8, 0, 8, 0>::run(d, wv, b0); wg_commit(); wg_wait0(); } while (0)
#define XVR(first, b0) do { wg_fence(); XR<0, 8, 0, 8, first>::run(d, wv, b0); XS<8, 8, 16, 0>::run(d, va16, b0); wg_commit(); wg_wait0(); } while (0)
#define XREL(mb) do { if (wq == 0 && l16 == 0) { mbar_arrive_cluster_rlx(rsb + SM_BAR + (mb)); mbar_arrive(sb + SM_BAR + (mb)); } } while (0)
#define XFOUT() do { \
          _Pragma("unroll") for (int hf = 0; hf < 2; hf++) \
            stsm4t(l16 + (sb + SM_XF + (wq * 2 + hf) * 512), pack_bf16(d[8 * hf], d[8 * hf + 1]), pack_bf16(d[8 * hf + 2], d[8 * hf + 3]), \
                   pack_bf16(d[8 * hf + 4], d[8 * hf + 5]), pack_bf16(d[8 * hf + 6], d[8 * hf + 7])); \
          __syncwarp(); \
          if (l16 < 32) mbar_arrive(sb + SM_BAR + MB_XF); } while (0)
#define ADDIN(base) _Pragma("unroll") for (int n = 0; n < 4; n++) { const float4 t = lds128f(TQ((base) + n * 2048)); d[4 * n] += t.x; d[4 * n + 1] += t.y; d[4 * n + 2] += t.z; d[4 * n + 3] += t.w; }
    if (wg == 0) {
      float d[16];
      const uint32_t x0 = (((sb + SM_MEM + r * 16384) & 0x3FFFF) >> 4) | (1u << 16), x1 = (((sb + SM_MEM + (r ^ 1) * 16384) & 0x3FFFF) >> 4) | (1u << 16);
      mbar_wait(sb + SM_BAR + MB_X0, 0);
      XQK(1, x0, x1);
      DUMP(SM_CQ);
      XVS(1, x0);
      bar_sync(B_CQ, 256);
      DUMP(SM_CV);
      bar_sync(B_X2, 384);
    } else {
      float d[16];
      bar_sync(B_CQ, 256);
      INIT(SM_CQ);
      bar_sync(B_X2, 384);
      mbar_wait(sb + SM_BAR + MB_F + 8, 0);
      XQK(0, xb16, xh16);
      XFOUT();
    }
    if (wg == 0) mbar_wait(sb + SM_BAR + MB_F, 0);
    for (int s = 0;; s++) {
      OPAQUE_R(lm); OPAQUE_R(l16);
      if (wg || s < NSEG - 1) {
        float d[16];
        const uint32_t cv = ((s ^ wg) & 1) ? SM_CV : SM_CW;
        PRB(2 + wg);
        spin(DLY_B);
        TSP(9, 1);

#if BI == 1
        wg_fence();
        XR<0, 1, 0, 8, 1>::run(d, wv, xb16); XS<8, 8, 9, 0>::run(d, va16, xb16); XR<1, 2, 0, 8, 0>::run(d, wv, xb16); XS<9, 8, 10, 0>::run(d, va16, xb16);
        XR<2, 3, 0, 8, 0>::run(d, wv, xb16); XS<10, 8, 11, 0>::run(d, va16, xb16); XR<3, 4, 0, 8, 0>::run(d, wv, xb16); XS<11, 8, 12, 0>::run(d, va16, xb16);
        XR<4, 5, 0, 8, 0>::run(d, wv, xb16); XS<12, 8, 13, 0>::run(d, va16, xb16); XR<5, 6, 0, 8, 0>::run(d, wv, xb16); XS<13, 8, 14, 0>::run(d, va16, xb16);
        XR<6, 7, 0, 8, 0>::run(d, wv, xb16); XS<14, 8, 15, 0>::run(d, va16, xb16); XR<7, 8, 0, 8, 0>::run(d, wv, xb16); XS<15, 8, 16, 0>::run(d, va16, xb16);
        wg_commit(); wg_wait0();
#elif BI == 4
        wg_fence(); XR<0, BR, 0, 8, 1>::run(d, wv, xb16);
        bar_sync(B_LD, 320);
        XR<BR, 8, 0, 8, 0>::run(d, wv, xb16); XS<8, 8, 16, 0>::run(d, va16, xb16); wg_commit(); wg_wait0();
#elif BI == 2
        if (wg) XVS(1, xb16); else XVR(1, xb16);
#elif BI == 3
        wg_fence(); XR<0, 8, 0, 8, 1>::run(d, wv, xb16); XR<8, 16, -8, 8, 0>::run(d, wv, xb16); wg_commit(); wg_wait0();
#else
        wg_fence(); XR<0, BR, 0, 8, 1>::run(d, wv, xb16); XS<8, 8, 16, BR == 0>::run(d, va16, xb16); XR<BR, 8, 0, 8, 0>::run(d, wv, xb16); wg_commit(); wg_wait0();
#endif
        OPAQUE_R(l16);
        if (wg == 0) {
          DUMP(cv);
          if (KB) { wg_fence(); XR<0, KB, 0, 32, 1>::run(d, w, xb16); wg_commit(); wg_wait0(); OPAQUE_R(l16); DUMP(SM_CQ); }
          TSP(5, 1);
        } else {
          XREL(MB_XE1);
          ADDIN(cv);
          uint32_t q[4], o[4];
#pragma unroll
          for (int i = 0; i < 4; i++) { const uint32_t a = pack_bf16(d[2 * i], d[2 * i + 1]), b = pack_bf16(d[8 + 2 * i], d[9 + 2 * i]); q[i] = r ? b : a; o[i] = r ? a : b; }
          st_async4(l16 + (rsb + SM_VR + wq * 512), u2f(o[0]), u2f(o[1]), u2f(o[2]), u2f(o[3]), rsb + SM_BAR + MB_VR);
          sts128(TQ(SM_VL), q[0], q[1], q[2], q[3]);
          __syncwarp();
          if (l16 == 0) mbar_arrive(sb + SM_BAR + MB_VR);
          TSP(28, 5);
        }
      }
      OPAQUE_R(lm); OPAQUE_R(l16);
      {
        uint32_t sa[4][4];
#pragma unroll
        for (int i = 0; i < VPF; i++) ldmatrix_x4_trans(sa[i], WA + i * 2048);
        float a[NCH][4], v[2][4]; uint4 c[4];
        FENCE();
        mbar_wait(sb + SM_BAR + MB_MEM + wg * 8, s & 1);
        TSF(0, 1);
        TSF(21, 5);
#if VI
#define QP(i) ((i) >= 12 ? (i) - 8 : (i) % 3 == 1 ? (i) / 3 : 8 + (i) - ((i) + 2) / 3)
#else
#define QP(i) ((i) < 8 ? 8 + (i) : (i) < 12 ? (i) - 4 : (i) - 12)
#endif
#pragma unroll
        for (int i = 0; i < 3; i++) c[i] = ldsm4t(MT + QP(i) * 512);
#pragma unroll
        for (int i = 0; i < 16; i++) {
          if (i + 3 < 16) c[(i + 3) & 3] = ldsm4t(MT + QP(i + 3) * 512);
          if (2 * i < NCH) mma4z(a[2 * i], w[2 * QP(i)][0], w[2 * QP(i)][1], w[2 * QP(i)][2], w[2 * QP(i)][3], c[i & 3].x, c[i & 3].y);
          else mma_16816(a[(2 * i) % NCH], w[2 * QP(i)], c[i & 3].x, c[i & 3].y);
          if (2 * i + 1 < NCH) mma4z(a[2 * i + 1], w[2 * QP(i) + 1][0], w[2 * QP(i) + 1][1], w[2 * QP(i) + 1][2], w[2 * QP(i) + 1][3], c[i & 3].z, c[i & 3].w);
          else mma_16816(a[(2 * i + 1) % NCH], w[2 * QP(i) + 1], c[i & 3].z, c[i & 3].w);
          if (VI && QP(i) == 0) {
            mma4z(v[0], wv[0][0], wv[0][1], wv[0][2], wv[0][3], c[i & 3].x, c[i & 3].y);
            mma4z(v[1], wv[1][0], wv[1][1], wv[1][2], wv[1][3], c[i & 3].z, c[i & 3].w);
          } else if (VI && QP(i) < 4) {
            mma_16816(v[0], wv[2 * (QP(i) & 3)], c[i & 3].x, c[i & 3].y);
            mma_16816(v[1], wv[2 * (QP(i) & 3) + 1], c[i & 3].z, c[i & 3].w);
          }
          FENCE();
        }
#if QB
        {
          const float f = wq < 2 ? 0.125f : 1.f;
          stsm2t(((l16 & 0x70u) | ((l16 & 0x80u) << 1)) + (sb + SM_QKP + wq * 512 + wg * 128),
                 pack_bf16(fmaf(a[0][0], f, a[1][0] * f), fmaf(a[0][1], f, a[1][1] * f)), pack_bf16(fmaf(a[0][2], f, a[1][2] * f), fmaf(a[0][3], f, a[1][3] * f)));
        }
#else
        {
          const float f = wq < 2 ? 0.125f : 1.f;
          const uint32_t qa = (((l16 & 0x30u) << 3) | ((l16 & 0x10u) << 2) | ((l16 >> 3) & 0x30u) | ((l16 >> 4) & 4u)) + (sb + SM_QKP + w8 * 512);
#pragma unroll
          for (int i = 0; i < 4; i++) sts32((qa ^ ((i & 1) << 6)) + (i >> 1) * 8, f2u(fmaf(a[0][i], f, a[1][i] * f)));
        }
#endif
        bar_arrive(B_QK, 288);
        bar_arrive(B_QK1, 288);
        FENCE();
#if VI
        spin(DLY_VI);
#pragma unroll
        for (int i = VPF; i < 4; i++) ldmatrix_x4_trans(sa[i], WA + i * 2048);
        FENCE();
#pragma unroll
        for (int i = 0; i < 4; i++) {
          mma_16816(v[0], sa[(2 * i) & 3], c[i].x, c[i].y);
          mma_16816(v[1], sa[(2 * i + 1) & 3], c[i].z, c[i].w);
          if (i < 2) { ldmatrix_x4_trans(sa[2 * i], WA + (4 + 2 * i) * 2048); ldmatrix_x4_trans(sa[2 * i + 1], WA + (5 + 2 * i) * 2048); }
          FENCE();
        }
#else
#pragma unroll
        for (int i = 0; i < 4; i++) {
          if (i == 0) {
            mma4z(v[0], wv[0][0], wv[0][1], wv[0][2], wv[0][3], c[0].x, c[0].y);
            mma4z(v[1], wv[1][0], wv[1][1], wv[1][2], wv[1][3], c[0].z, c[0].w);
          } else {
            mma_16816(v[0], wv[2 * i], c[i].x, c[i].y);
            mma_16816(v[1], wv[2 * i + 1], c[i].z, c[i].w);
          }
        }
        FENCE();

        c[0] = ldsm4t(MT + 4 * 512);
#pragma unroll
        for (int i = VPF; i < 2; i++) ldmatrix_x4_trans(sa[i], WA + i * 2048);
        c[1] = ldsm4t(MT + 5 * 512);
#pragma unroll
        for (int i = (VPF > 2 ? VPF : 2); i < 4; i++) ldmatrix_x4_trans(sa[i], WA + i * 2048);
        c[2] = ldsm4t(MT + 6 * 512);
        FENCE();
#pragma unroll
        for (int i = 0; i < 4; i++) {
          mma_16816(v[0], sa[(2 * i) & 3], c[i % 3].x, c[i % 3].y);
          mma_16816(v[1], sa[(2 * i + 1) & 3], c[i % 3].z, c[i % 3].w);
          if (i < 2) { ldmatrix_x4_trans(sa[2 * i], WA + (4 + 2 * i) * 2048); ldmatrix_x4_trans(sa[2 * i + 1], WA + (5 + 2 * i) * 2048); }
          if (i == 0) c[0] = ldsm4t(MT + 7 * 512);
          FENCE();
        }
#endif
        if (EG && s < NSEG - 1) bar_sync(B_PUB, 320);
        sts128f(TH(SM_VP), v[0][0] + v[1][0], v[0][1] + v[1][1], v[0][2] + v[1][2], v[0][3] + v[1][3]);
        bar_arrive(B_V, 320);
      }
      if (s == NSEG - 1) break;
      if (s == 0) mbar_wait(sb + SM_BAR + MB_WO, 0);
      OPAQUE_R(lm); OPAQUE_R(l16);
      {
        uint32_t wo[WPF][4];
        {
          float d[16];
          PRB(0);
          if (!F1L && wg) mbar_wait(sb + SM_BAR + MB_F + 8, (s + 1) & 1);
          if (KB && wg == 0) {
            INIT(SM_CQ);
#pragma unroll
            for (int f = 0; f < (W0I == 2 ? WPA : 0); f++) ldmatrix_x4_trans(wo[f], WOF(f));
            if (!EG) bar_sync(B_PUB, 320);
            wg_fence();
            XR<KB, KB + 1, 0, 32, 0>::run(d, w, xb16);
            TSF(26, 1);
            XR<KB + 1, 16, 0, 32, 0>::run(d, w, xb16);
            if (W0I == 3) wg_commit();
#pragma unroll
            for (int f = 0; f < (W0I & 1 ? WPA : 0); f++) ldmatrix_x4_trans(wo[f], WOF(f));
            if (W0I == 3) wg_fence();
            XR<0, 16, 16, 32, 0>::run(d, w, xh16);
            wg_commit(); wg_wait0();
            TSF(13, 1);
            XREL(MB_XE0);
#pragma unroll
            for (int f = 0; f < (W0I ? 0 : WPA); f++) ldmatrix_x4_trans(wo[f], WOF(f));
          } else {
          const uint32_t f1ok = EG ? 0u : F1L ? mbar_test(sb + SM_BAR + MB_F + 8, (s + 1) & 1) : 1u;
          if (!EG) bar_sync(B_PUB, 320);
          if (!f1ok) mbar_wait(sb + SM_BAR + MB_F + 8, (s + 1) & 1);
#pragma unroll
          for (int f = 0; f < (W0I == 2 ? WPA : 0); f++) ldmatrix_x4_trans(wo[f], WOF(f));
          wg_fence();
          XR<0, 1, 0, 32, 1>::run(d, w, xb16);
          TSF(7, 5);
          XR<1, WKA, 0, 32, 0>::run(d, w, xb16);
          if (W0I == 3) wg_commit();
#pragma unroll
          for (int f = 0; f < (W0I == 2 ? 0 : WPA); f++) ldmatrix_x4_trans(wo[f], WOF(f));
          if (W0I == 3) wg_fence();
          XR<WKA, 16, 0, 32, 0>::run(d, w, xb16); XR<0, 16, 16, 32, 0>::run(d, w, xh16);
          wg_commit(); wg_wait0();
          }
          TSF(31, 5);
          OPAQUE_R(l16);
          PRB(1);
#define XHALF(g) do { \
            _Pragma("unroll") for (int n = 0; n < 2; n++) sts128f(TQ(SM_CQ + ((g) * 2 + n) * 2048), d[8 - 8 * (g) + 4 * n], d[9 - 8 * (g) + 4 * n], d[10 - 8 * (g) + 4 * n], d[11 - 8 * (g) + 4 * n]); \
            if (F0W == 1 && (g) == 0 && wq == 0 && s < NSEG - 2) F0LOAD(); \
            bar_sync(B_CQ, 256); \
            const float4 t0 = lds128f(TQ(SM_CQ + (2 - 2 * (g)) * 2048)), t1 = lds128f(TQ(SM_CQ + (3 - 2 * (g)) * 2048)); \
            stsm4t(l16 + (sb + SM_XF + (wq * 2 + (g)) * 512), pack_bf16(d[8 * (g)] + t0.x, d[8 * (g) + 1] + t0.y), pack_bf16(d[8 * (g) + 2] + t0.z, d[8 * (g) + 3] + t0.w), \
                   pack_bf16(d[8 * (g) + 4] + t1.x, d[8 * (g) + 5] + t1.y), pack_bf16(d[8 * (g) + 6] + t1.z, d[8 * (g) + 7] + t1.w)); } while (0)
#if XH
          if (wg) { DUMP(SM_CQ); bar_arrive(B_CQ, 256); }
          else {
            bar_sync(B_CQ, 256);
#pragma unroll
            for (int hf = 0; hf < 2; hf++) {
              const float4 t0 = lds128f(TQ(SM_CQ + 2 * hf * 2048)), t1 = lds128f(TQ(SM_CQ + (2 * hf + 1) * 2048));
              stsm4t(l16 + (sb + SM_XF + (wq * 2 + hf) * 512), pack_bf16(d[8 * hf] + t0.x, d[8 * hf + 1] + t0.y), pack_bf16(d[8 * hf + 2] + t0.z, d[8 * hf + 3] + t0.w),
                     pack_bf16(d[8 * hf + 4] + t1.x, d[8 * hf + 5] + t1.y), pack_bf16(d[8 * hf + 6] + t1.z, d[8 * hf + 7] + t1.w));
            }
            __syncwarp();
            if (l16 < 32) mbar_arrive(sb + SM_BAR + MB_XF);
          }
#else
          if (wg == 0) { if (!KB) XREL(MB_XE0); XHALF(0); } else XHALF(1);
          __syncwarp();
          if (l16 == 0) mbar_arrive(sb + SM_BAR + MB_XF);
#endif
          TSF(3, 5);
        }
#pragma unroll
        for (int f = WPA; f < WPF; f++) ldmatrix_x4_trans(wo[f], WOF(f));
        unsigned char* pa = P.win + (w_ar(s) + (j * 32 + cw * 16 + wq * 2) * 256 + (l16 >> 2));
        uint32_t ce = (l16 >> 4) - 4 * (cw * 4 + wq);
        OPAQUE_L(pa); OPAQUE_R(ce);
        FENCE();
        if (XH) bar_sync(wg ? B_O : B_O2, 192); else bar_sync(B_O, LN ? 352 : 320);
        if (WNS < 0 && near) spin(DLY_NW);
        uint4 ob[2];
        ob[0] = ldsm4(l16 + (sb + SM_OF)); ob[1] = ldsm4(l16 + (sb + SM_OF + 512));
        float acc[2][4]; uint2 zi; uint32_t f0ok;
#pragma unroll
        for (int f = 0; f < 16; f++) {
          const int ks = f >> 1;
          const uint32_t b0 = (ks & 1) ? ob[(ks >> 1) & 1].z : ob[(ks >> 1) & 1].x, b1 = (ks & 1) ? ob[(ks >> 1) & 1].w : ob[(ks >> 1) & 1].y;
          if (f < 2) mma4z(acc[f], wo[f][0], wo[f][1], wo[f][2], wo[f][3], b0, b1);
          else mma_16816(acc[f % 2], wo[f < WPF ? f : 2 + (f - WPF) % (WPF - 2)], b0, b1);
          if (f - 1 >= 2 && f - 1 + (WPF - 2) < 16) {
            const int nf = f - 1 + (WPF - 2);
            ldmatrix_x4_trans(wo[2 + (nf - WPF) % (WPF - 2)], WOF(nf));
          }
          if (f == 4 || f == 8) ob[((f >> 2) - 1) & 1] = ldsm4(l16 + (sb + SM_OF + (1 + (f >> 2)) * 512));
          if (f == WNS && near) spin(DLY_NW);
          if (f == GF) f0ok = mbar_test(sb + SM_BAR + MB_F, (s + 1) & 1);
          if (LN && f == 12) zi = lds64(((l16 >> 1) & 24u) + (sb + SM_Z));
          if (f < 15) FENCE();
        }
        if (wg) { if (BGT == 2 && l16 == 0) mbar_arrive(sb + SM_BAR + MB_F); } else if (!BGT || f0ok) bar_arrive(B_CV, 256);
        PRB(7 + wg);
        if (LN) {
#pragma unroll
          for (int i = 0; i < 8; i++) acc[i >> 2][i & 3] *= u2f((i & 1) ? zi.y : zi.x);
        }
        red_bf2(pa, pack_bf16(acc[0][0], ce == 0 ? 1.f : acc[0][1])); red_bf2(pa + 256, pack_bf16(acc[0][2], ce == 1 ? 1.f : acc[0][3]));
        red_bf2(pa + 2048, pack_bf16(acc[1][0], ce == 2 ? 1.f : acc[1][1])); red_bf2(pa + 2304, pack_bf16(acc[1][2], ce == 3 ? 1.f : acc[1][3]));
        red_bf2p4(pa + (128 + (wq & 1) * 256), pack_bf16(ce == 0 ? acc[0][1] : ce == 1 ? acc[0][3] : ce == 2 ? acc[1][1] : acc[1][3], 1.f), ce);
        TSF(4, 1);
        TSF(2, 6);
        if (wg) bar_sync(B_CV, 256);
        else if (!f0ok) { mbar_wait(sb + SM_BAR + MB_F, (s + 1) & 1); if (BGT) bar_arrive(B_CV, 256); }
      }
    }
  } else {
    asm volatile("setmaxnreg.dec.sync.aligned.u32 " STR(RF_CTL) ";");
    const int g = lane >> 2, tq = lane & 3;
    if (wq == 0) {
      if (lane < 12) asm volatile("prefetch.global.L2 [%0];" :: "l"(SP.x + (size_t)(cta * 12 + lane) * 64));
      __syncwarp();
      {
        SIDES();
        const uint32_t o[6] = {w_blk(w_h1(cta), me), w_blk(w_h1(cta) ^ H1_V, me), w_blk(w_mvx(cta, 0), me ^ sm2.z), w_blk(w_mvx(cta, 1), me ^ sm2.z),
                               w_blk(w_mxa(cta, 0), me ^ sm2.z), w_blk(w_mxa(cta, 1), me ^ sm2.z)};
#pragma unroll
        for (int i = 0; i < 24; i++) stg_r4(P.win + (o[i >> 2] + (i & 3) * 512 + lane * 16), 0u, 0u, 0u, 0u);
#pragma unroll
        for (int i = 0; i < 6; i++) stg_r1(P.win + (w_ar(i >> 1) + cta * 256 + (i & 1) * 128 + lane * 4), 0u);
        __threadfence();
        __syncwarp();
      }
      {
        const uint32_t wv = movm(*reinterpret_cast<const uint32_t*>(P.mem0 + g * DM + cta * 8 + tq * 2));
        const bool sp = lane == cnt_word(cta & 31);
        stg_r1(P.win + (w_ar(-1) + cta * 256 + lane * 4), sp ? (wv & 0xffffu) | 0x42000000u : wv);
        if (sp) stg_r1(P.win + (w_ar(-1) + ((cta & ~9) + ((cta >> 1) & 1)) * 256 + 128 + lane * 4), (wv >> 16) | 0x42000000u);
      }
      bar_sync(B_V, 160);
      if (lane == 0) {
        fence_async_smem(); mbar_arrive_cluster_rlx(mapa(sb + SM_BAR + MB_INIT, 0)); mbar_arrive_cluster_rlx(mapa(sb + SM_BAR + MB_INIT, 1));
        mbar_wait(sb + SM_BAR + MB_INIT, 0);
        mbar_expect_tx(sb + SM_BAR + MB_F, 32768);
        for (int i = 0; i < (BGT == 2 ? 7 : BGT == 1 ? 3 : 0); i++) mbar_arrive(sb + SM_BAR + MB_F);
        mbar_expect_tx(sb + SM_BAR + MB_F + 8, 32768);
        XLOAD(1, 0); XLOAD(0, 1);
        WLOAD(4 + WSPL, 8);
      }
      __syncwarp();
#ifdef PER
      if (lane == 0) atomicMax(&g_end[5], gt32());
#endif
      bar_sync(B_X2, 384);
    } else {
      bar_sync(B_P, 224);
#ifdef PER
      if (t128 == 32) atomicMax(&g_end[4], gt32());
#endif
      if (t128 == 96) {
        fence_async_smem();
        mbar_expect_tx(sb + SM_BAR + MB_WO, 65536);
        for (int i = 0; i < 8; i++) tma_load_2d(sb + SM_WOS + i * 8192, &tmw, j * 256 + ((i >> 1) ^ (2 * sw)) * 64, h * DH + (i & 1) * 64, sb + SM_BAR + MB_WO);
      }
      __syncwarp();
      bar_sync(B_X2, 384);
    }
    SIDES();
    uint32_t l16 = __shfl_sync(~0u, lane * 16, lane);
    const uint32_t me2 = me ^ sm2.z;
    const float sc = 0.08838834764831845f * 1.4426950408889634f;
    uint32_t ls = l16 + sb;
#define PVM(o, zs, p0, p2) do { \
        FENCE(); \
        mma4z(zs, 0x3F803F80u, 0x3F803F80u, 0x3F803F80u, 0x3F803F80u, p0.x, p0.y); \
        _Pragma("unroll") for (int t = 0; t < 4; t++) mma4z(o[t], va[2 * t].x, va[2 * t].y, va[2 * t].z, va[2 * t].w, p0.x, p0.y); \
        FENCE(); \
        mma4(zs, 0x3F803F80u, 0x3F803F80u, 0x3F803F80u, 0x3F803F80u, p0.z, p0.w); \
        _Pragma("unroll") for (int t = 0; t < 2; t++) mma4(o[t], va[2 * t + 1].x, va[2 * t + 1].y, va[2 * t + 1].z, va[2 * t + 1].w, p0.z, p0.w); \
        FENCE(); \
        mma_1688(zs, 0x3F803F80u, 0x3F803F80u, p2); \
        _Pragma("unroll") for (int t = 2; t < 4; t++) mma4(o[t], va[2 * t + 1].x, va[2 * t + 1].y, va[2 * t + 1].z, va[2 * t + 1].w, p0.z, p0.w); \
        mma_1688(o[0], vm[0].x, vm[0].y, p2); mma_1688(o[1], vm[0].z, vm[0].w, p2); mma_1688(o[2], vm[1].x, vm[1].y, p2); mma_1688(o[3], vm[1].z, vm[1].w, p2); } while (0)
#define PVE(o, z, dst) do { \
        const float i0 = rcpf(z[0]), i1 = rcpf(z[1]); \
        _Pragma("unroll") for (int u = 0; u < 2; u++) \
          stsm4t(ls + (dst) + u * 1024, pack_bf16(o[2 * u][0] * i0, o[2 * u][1] * i1), pack_bf16(o[2 * u][2] * i0, o[2 * u][3] * i1), \
                 pack_bf16(o[2 * u + 1][0] * i0, o[2 * u + 1][1] * i1), pack_bf16(o[2 * u + 1][2] * i0, o[2 * u + 1][3] * i1)); } while (0)
#define SOFTMAX(pf, f) do { \
        float mx = fmaxf(fmaxf(fmaxf(sx[2], sx[3]), fmaxf(sx[4], sx[5])), fmaxf(fmaxf(sx[6], sx[7]), fmaxf(sx[8], sx[9]))); \
        mx = fmaxf(mx, fmaxf(sx[0], sx[1])); \
        mx = fmaxf(mx, __shfl_xor_sync(~0u, mx, 1)); \
        mx = fmaxf(mx, __shfl_xor_sync(~0u, mx, 2)); \
        mx *= -(f); \
        _Pragma("unroll") for (int i = 0; i < 10; i++) sx[i] = ex2(fmaf(sx[i], f, mx)); \
        sts128(ls + (pf), pack_bf16(sx[2], sx[3]), pack_bf16(sx[4], sx[5]), pack_bf16(sx[6], sx[7]), pack_bf16(sx[8], sx[9])); \
        sts32(ls - l12 + (pf) + 512, pack_bf16(sx[0], sx[1])); } while (0)
    const uint32_t lq = (l16 ^ ((l16 >> 1) & 64u)) + sb, l12 = (l16 >> 2) * 3;
#define M3PTR(sl) \
            const uint32_t tf = me ^ 1 ^ r, m3i = w_ar(sl) + (wq & 1) * 16384 + (l16 & 0x70u) + ((l16 & 0x180u) << 1); \
            const unsigned char* p0f = P.win + (m3i + r * 8192 + tf * 4096); const unsigned char* p0n = P.win + (m3i + r * 8192 + (tf ^ 1) * 4096); \
            const unsigned char* p1f = P.win + (m3i + (r ^ 1) * 8192 + (tf ^ 1) * 4096); const unsigned char* p1n = P.win + (m3i + (r ^ 1) * 8192 + tf * 4096); \
            const unsigned char* pd = P.win + (w_ar(sl) + (wq & 1) * 16384 + (((l16 >> 7) ^ r) & 1u) * 8192 + ((l16 & 64u) * 4 + (l16 & 48u) * 2 + (l16 & 16u)) * 16 + 128 + (l16 & 0x70u)); \
            uint32_t mf = ls + SM_MEM + (wq & 1) * 8192 + tf * 2048, mn = ls + SM_MEM + (wq & 1) * 8192 + (tf ^ 1) * 2048, nr = l16 < 256u ? 1u + (((l16 >> 6) ^ (l16 >> 7) ^ tf) & 1u) : 0u; \
            OPAQUE_L(p0f); OPAQUE_L(p0n); OPAQUE_L(p1f); OPAQUE_L(p1n); OPAQUE_L(pd); OPAQUE_R(mf); OPAQUE_R(mn); OPAQUE_R(nr); FENCE()
#define M3REQ(arr) \
            _Pragma("unroll") for (int i = 0; i < 4; i++) { cp16(mn + 4096 + i * 512, p1f + i * 1024); cp16(mf + i * 512, p0f + i * 1024); } \
            cp16p(ls + SM_RD + (wq & 1) * 256, pd, nr & 1u); \
            _Pragma("unroll") for (int i = 0; i < 4; i++) { cp16(mf + 4096 + i * 512, p1n + i * 1024); cp16(mn + i * 512, p0n + i * 1024); } \
            cp16p(ls + SM_RD + (wq & 1) * 256, pd, nr & 2u); \
            asm volatile("cp.async.mbarrier.arrive.noinc.shared::cta.b64 [%0];" :: "r"(sb + SM_BAR + MB_G + (wq & 1) * 8) : "memory"); \
            if (BI == 4 && (arr)) bar_arrive(B_LD, 320)
    if (wq < 2) { M3PTR(-1); M3REQ(1); }
#define ETA(k, first) ETAT(gt32() + (k), first)
#define ETAT(tm, first) do { unsigned char* pt = P.win + (w_ar(s) + 384 + (cta >> 5) * 8192 + ((cta >> 4) & 1) * 2048 + (l16 & 16u) * 256); \
          asm volatile("{\n.reg .pred q;\nsetp.lt.u32 q, %2, 32;\n@q red.relaxed.gpu.global.max.u32 [%0+4], %1;\n}" :: "l"(pt), "r"(tm), "r"(l16) : "memory"); \
          if (first) asm volatile("{\n.reg .pred q;\nsetp.lt.u32 q, %1, 32;\n@q red.relaxed.gpu.global.add.u32 [%0], 1;\n}" :: "l"(pt), "r"(l16) : "memory"); } while (0)
    if (wq == 1) {
      const uint32_t xin = w_blk(w_mxa(cta, 0), me2) + l16;
      const uint32_t lsq = sb + ((l16 & 0x70u) | ((l16 & 0x80u) << 1) | ((l16 & 0x100u) >> 1));
      mbar_wait(sb + SM_BAR + MB_MEM, 0); mbar_wait(sb + SM_BAR + MB_MEM + 8, 0);
      for (int s = 0; s < NSEG; s++) {
        const uint32_t t2 = ((s >> 1) & 1) ^ 1;
        mbar_wait(sb + SM_BAR + MB_XF, s & 1);
        PRB(10);
        {
        uint4 kx[4], qx[4];
#pragma unroll
        for (int i = 0; i < 4; i++) { kx[i] = ldsm4(ls + (SM_XF + (4 + i) * 512)); qx[i] = ldsm4(lsq + (SM_XF + i * 512)); }
        const uint32_t db = w_blk(w_mxa(h * 4, s), me2) + l16 - 512;
        {
          float S[2][4][4];
#pragma unroll
          for (int mt = 0; mt < 2; mt++) {
            const uint4 q0 = qx[mt];
            mma4z(S[mt][0], q0.x, q0.y, q0.z, q0.w, kx[0].x, kx[0].y); mma4z(S[mt][1], q0.x, q0.y, q0.z, q0.w, kx[0].z, kx[0].w);
            mma4z(S[mt][2], q0.x, q0.y, q0.z, q0.w, kx[1].x, kx[1].y); mma4z(S[mt][3], q0.x, q0.y, q0.z, q0.w, kx[1].z, kx[1].w);
          }
#pragma unroll
          for (int mt = 0; mt < 2; mt++) {
            const uint4 q1 = qx[2 + mt];
            mma4(S[mt][0], q1.x, q1.y, q1.z, q1.w, kx[2].x, kx[2].y); mma4(S[mt][1], q1.x, q1.y, q1.z, q1.w, kx[2].z, kx[2].w);
            mma4(S[mt][2], q1.x, q1.y, q1.z, q1.w, kx[3].x, kx[3].y); mma4(S[mt][3], q1.x, q1.y, q1.z, q1.w, kx[3].z, kx[3].w);
          }
          FENCE();
          if (BGT && s > 0 && l16 == 0) mbar_arrive(sb + SM_BAR + MB_F);
          FENCE();
#pragma unroll
          for (int u = 0; u < 4; u++) {
            const int mt = u >> 1, c = 2 * (u & 1);
            const uint32_t m0 = tagw(pack_f16(S[mt][0][c] * sc, S[mt][0][c + 1] * sc), t2), m1 = pack_f16(S[mt][1][c] * sc, S[mt][1][c + 1] * sc),
                           m2 = pack_f16(S[mt][2][c] * sc, S[mt][2][c + 1] * sc), m3 = pack_f16(S[mt][3][c] * sc, S[mt][3][c + 1] * sc);
            const int e = u ^ j;
            if (e) stg_r4(P.win + (db + mt * 16384 + (u & 1) * 2048 + e * 512), m0, m1, m2, m3);
            else sts128(ls + SM_XS, m0, m1, m2, m3);
          }
        }
        TS(15);
        float sx[10];
        const unsigned char* pa = P.win + (xin + ((s & 1) << 20));
        uint4 xv[3];
        if (s > 0) spin(DLY_XD);
#pragma unroll
        for (int i = 0; i < 3; i++) xv[i] = ldg_r4(pa + i * 512);
        FENCE();
        if (GW == 0 && s > 0) {
          M3PTR(s - 1);
          bar_sync(B_GO, 64);
          const uint32_t tg0 = lds32(sb + SM_Z + 32);
          while (tg0 - gt32() - 1u < 8192u) {}
          M3REQ(s < NSEG);
        }
        FENCE();
        int n = 0;
#pragma unroll 1
        while (__any_sync(~0u, (x3(xv[0].x, xv[1].x, t2) | (xv[2].x ^ t2)) & 1u) && ++n < SPIN_LIMIT) {
#pragma unroll
          for (int i = 0; i < 3; i++) xv[i] = ldg_r4(pa + i * 512);
        }
        {
          const uint4 v3 = lds128(ls + SM_XS);
          sum_h4(sx[2], sx[3], xv[0].x, xv[1].x, xv[2].x, v3.x); sum_h4(sx[4], sx[5], xv[0].y, xv[1].y, xv[2].y, v3.y);
          sum_h4(sx[6], sx[7], xv[0].z, xv[1].z, xv[2].z, v3.z); sum_h4(sx[8], sx[9], xv[0].w, xv[1].w, xv[2].w, v3.w);
          const int row = 8 * j + g - 2 * tq;
#pragma unroll
          for (int i = 0; i < 8; i++) if ((i >> 1) * 8 + (i & 1) > row) sx[2 + i] = -INFINITY;
        }
        float mx = fmaxf(fmaxf(fmaxf(sx[2], sx[3]), fmaxf(sx[4], sx[5])), fmaxf(fmaxf(sx[6], sx[7]), fmaxf(sx[8], sx[9])));
        sts32(ls - l12 + SM_XS + 512, f2u(mx));
        {
          if (l16 == 0) mbar_expect_tx(sb + SM_BAR + MB_VR, 2048);
          unsigned char* d = P.win + (w_blk(w_mvx(cta, s), me2) + l16);
          OPAQUE_L(d); FENCE();
          mbar_wait(sb + SM_BAR + MB_VR, s & 1);
          PRB(14);
#pragma unroll
          for (int t = 0; t < 4; t++) {
            const uint4 a0 = lds128(ls + (SM_VL + t * 512)), a1 = lds128(ls + (SM_VR + t * 512));
            stg_r4(d + t * 512, tagw(addb2(a0.x, a1.x), t2), addb2(a0.y, a1.y), addb2(a0.z, a1.z), addb2(a0.w, a1.w));
          }
          TS(23);
        }
        unsigned char* pm = P.win + (db + 2048 + j * 128 - l12);
        const unsigned char* py = pa + 1536 - l12;
        OPAQUE_L(pm); OPAQUE_L(py);
        if (s > 0) bar_sync(B_PXF, 96);
        FENCE();
        bar_sync(B_QK1, 288);
        uint32_t kb[2][2];
#pragma unroll
        for (int t = 0; t < 2; t++) {
#if QB
          const uint4 u = ldsm4(ls + (SM_QKP + (2 + t) * 512)); kb[t][0] = addb2(u.x, u.y); kb[t][1] = addb2(u.z, u.w);
#else
          const float4 u = lds128f(lq + (SM_QKP + (2 + t) * 512)), v4 = lds128f(lq + (SM_QKP + 2048 + (2 + t) * 512));
          kb[t][0] = pack_bf16(u.x + v4.x, u.y + v4.y); kb[t][1] = pack_bf16(u.z + v4.z, u.w + v4.w);
#endif
        }
        float S[2][4];
#pragma unroll
        for (int mt = 0; mt < 2; mt++) mma4z(S[mt], qx[mt].x, qx[mt].y, qx[mt].z, qx[mt].w, kb[0][0], kb[0][1]);
#pragma unroll
        for (int mt = 0; mt < 2; mt++) mma4(S[mt], qx[2 + mt].x, qx[2 + mt].y, qx[2 + mt].z, qx[2 + mt].w, kb[1][0], kb[1][1]);
        if (s < NSEG - 1) bar_arrive(B_PUB, 320);
        FENCE();
#pragma unroll
        for (int u = 0; u < 4; u++) stg_r1(pm + (u >> 1) * 16384 + (u & 1) * 2048, tagw(pack_f16(S[u >> 1][2 * (u & 1)] * sc, S[u >> 1][2 * (u & 1) + 1] * sc), t2));
        TS(30);
        spin(DLY_XL);
        uint32_t xy[4];
#pragma unroll
        for (int i = 0; i < 4; i++) xy[i] = ldg_r1(py + i * 128);
        FENCE();
        if (ETW == 1 && s < NSEG - 1) ETA(DLY_K, 1);
        FENCE();
        n = 0;
#pragma unroll 1
        while (__any_sync(~0u, (x3(xy[0], xy[1], t2) | x3(xy[2], xy[3], t2)) & 1u) && ++n < SPIN_LIMIT) {
#pragma unroll
          for (int i = 0; i < 4; i++) xy[i] = ldg_r1(py + i * 128);
        }
        sum_h4(sx[0], sx[1], xy[0], xy[1], xy[2], xy[3]);
        mx = fmaxf(mx, fmaxf(sx[0], sx[1]));
        mx = fmaxf(fmaxf(mx, __shfl_xor_sync(~0u, mx, 1)), fmaxf(__shfl_xor_sync(~0u, mx, 2), __shfl_xor_sync(~0u, mx, 3)));
#pragma unroll
        for (int i = 0; i < 10; i++) sx[i] = ex2(sx[i] - mx);
        sts128(ls + SM_PX, pack_bf16(sx[2], sx[3]), pack_bf16(sx[4], sx[5]), pack_bf16(sx[6], sx[7]), pack_bf16(sx[8], sx[9]));
        sts32(ls - l12 + SM_PX + 512, pack_bf16(sx[0], sx[1]));
        bar_arrive(B_PX, 96);
        TS(1);
        }
      }
    } else {
      const uint32_t ho = (wq & 1) * 512 + l16, hv = wq == 0 ? 0u : H1_V;
      uint32_t ow = w_blk(w_h1(cta) ^ hv, me) + ho, or0 = w_blk(w_h1(cta ^ 1) ^ hv, me) + ho, or1 = w_blk(w_h1((cta ^ 2) & ~1) ^ hv, me) + ho;
#define PTRS() OPAQUE_R(ow); OPAQUE_R(or0); OPAQUE_R(or1); \
      unsigned char* pw0 = P.win + ow; const unsigned char* pr0 = P.win + or0; const unsigned char* pr1 = P.win + or1; \
      OPAQUE_L(pw0); OPAQUE_L(pr0); OPAQUE_L(pr1); FENCE()
      if (wq == 0) {
        const uint32_t xcnt = me ? NCTA - nlo : nlo, xrank = (me ? cta - nlo : cta) + lane * xcnt;
        int ko = 0;
        mbar_wait(sb + SM_BAR + MB_XE1, 0);
        if (l16 == 0) { mbar_expect_tx(sb + SM_BAR + MB_F + 8, 32768); XLOAD(1, 1); }
        __syncwarp();
        for (int s = 0; s < NSEG; s++) {
          const uint32_t tg = (s & 1) ^ 1;
          mbar_wait(sb + SM_BAR + MB_XF, s & 1);
          uint4 xf[4];
#pragma unroll
          for (int i = 0; i < 4; i++) xf[i] = ldsm4(ls + (SM_XF + (4 + i) * 512));
          PTRS();
          unsigned char* pw1 = pw0 + 512 - l12; OPAQUE_L(pw1);
          if (KU) {
            const uint32_t f = lds32(sb + SM_Z + 40);
            ko = f == (uint32_t)s ? min(ko + KU, 256) : max(ko - KD, 0);
          }
          bar_sync(B_QK, 288);
          if (s == NSEG - 1) break;
          PRB(9);
#if QB
          const uint4 q0 = ldsm4(ls + SM_QKP), q1 = ldsm4(ls + (SM_QKP + 512)), k0 = ldsm4(ls + (SM_QKP + 1024)), k1 = ldsm4(ls + (SM_QKP + 1536));
          FENCE();
          float S[5][4];
          mma4z(S[1], q0.x, q0.y, q0.z, q0.w, xf[0].x, xf[0].y);
          mma4z(S[2], q0.x, q0.y, q0.z, q0.w, xf[0].z, xf[0].w);
          mma4z(S[3], q0.x, q0.y, q0.z, q0.w, xf[1].x, xf[1].y);
          mma4z(S[4], q0.x, q0.y, q0.z, q0.w, xf[1].z, xf[1].w);
          mma4z(S[0], q0.x, q0.y, q0.z, q0.w, addb2(k0.x, k0.y), addb2(k0.z, k0.w));
          mma4(S[1], q1.x, q1.y, q1.z, q1.w, xf[2].x, xf[2].y);
          mma4(S[2], q1.x, q1.y, q1.z, q1.w, xf[2].z, xf[2].w);
          mma4(S[3], q1.x, q1.y, q1.z, q1.w, xf[3].x, xf[3].y);
          mma4(S[4], q1.x, q1.y, q1.z, q1.w, xf[3].z, xf[3].w);
          mma4(S[0], q1.x, q1.y, q1.z, q1.w, addb2(k1.x, k1.y), addb2(k1.z, k1.w));
          bar_arrive(B_PUB, 320);
          uint32_t m[5];
#pragma unroll
          for (int i = 1; i < 6; i++) m[i % 5] = pack_f16(S[i % 5][0] + S[i % 5][2], S[i % 5][1] + S[i % 5][3]);
#else
          float4 u[4], v4[4];
#pragma unroll
          for (int t = 0; t < 4; t++) { u[t] = lds128f(lq + (SM_QKP + t * 512)); v4[t] = lds128f(lq + (SM_QKP + 2048 + t * 512)); }
          FENCE();
          uint32_t f[4][2];
#pragma unroll
          for (int t = 0; t < 4; t++) {
            f[t][0] = pack_bf16(u[t].x + v4[t].x, u[t].y + v4[t].y);
            f[t][1] = pack_bf16(u[t].z + v4[t].z, u[t].w + v4[t].w);
          }
          float S[5][4], T[5][4];
#pragma unroll
          for (int i = 0; i < 2; i++) {
            mma4z(S[1 + 2 * i], f[0][0], f[1][0], f[0][1], f[1][1], xf[i].x, xf[i].y); mma4z(T[1 + 2 * i], f[0][0], f[1][0], f[0][1], f[1][1], xf[2 + i].x, xf[2 + i].y);
            mma4z(S[2 + 2 * i], f[0][0], f[1][0], f[0][1], f[1][1], xf[i].z, xf[i].w); mma4z(T[2 + 2 * i], f[0][0], f[1][0], f[0][1], f[1][1], xf[2 + i].z, xf[2 + i].w);
          }
          mma4z(S[0], f[0][0], f[1][0], f[0][1], f[1][1], f[2][0], f[2][1]); mma4z(T[0], f[0][0], f[1][0], f[0][1], f[1][1], f[3][0], f[3][1]);
          bar_arrive(B_PUB, 320);
          FENCE();
          uint32_t m[5];
#pragma unroll
          for (int i = 1; i < 6; i++) m[i % 5] = pack_f16(S[i % 5][0] + T[i % 5][2], S[i % 5][1] + T[i % 5][3]);
#endif
          stg_r4(pw0, tagw(m[1], tg), m[2], m[3], m[4]);
          stg_r1(pw1, tagw(m[0], tg));
          TS(6);
          FENCE();
#pragma unroll
          for (int i = 0; i < 5; i++) { OPAQUE_R(m[i]); m[i] = hfma2(m[i], 0x34003400u, 0u); OPAQUE_R(m[i]); }
          const unsigned char* py0 = pr0 + 512 - l12; const unsigned char* py1 = pr1 + 512 - l12;
          OPAQUE_L(py0); OPAQUE_L(py1);
          const uint32_t ts = clk32(), te = gt32() + (DLY_K + ko);
          if (l16 == 0) mbar_expect_tx(sb + SM_BAR + MB_F, s < NSEG - 2 ? 32768 : 0);
          while (clk32() - ts < (uint32_t)DLY_S) {}
          {
            uint32_t t[5], x, x1, x2, x3_, bad; int n = 0;
#pragma unroll 1
            do {
              uint4 v[3]; uint32_t y[3];
              v[0] = ldg_r4(pr0); v[1] = ldg_r4(pr1); v[2] = ldg_r4(pr1 + 2048);
              y[0] = ldg_r1(py0); y[1] = ldg_r1(py1); y[2] = ldg_r1(py1 + 2048);
              if (n) ETA(DLY_KS, 0); else if (ETW == 0) ETAT(te, 1);
              n++;
              FENCE();
#define Q3(o, a, b, c) hfma2(c, 0x34003400u, hfma2(b, 0x34003400u, hfma2(a, 0x34003400u, o)))
              t[1] = Q3(m[1], v[0].x, v[1].x, v[2].x); t[2] = Q3(m[2], v[0].y, v[1].y, v[2].y); t[3] = Q3(m[3], v[0].z, v[1].z, v[2].z); t[4] = Q3(m[4], v[0].w, v[1].w, v[2].w);
              t[0] = Q3(m[0], y[0], y[1], y[2]);
              x = hmax2(hmax2(hmax2(t[1], t[2]), hmax2(t[3], t[4])), t[0]);
              x = hmax2(x, __byte_perm(x, 0u, 0x1032));
              x = f2u(__low2float(*reinterpret_cast<__half2*>(&x)) * (-32.f * sc));
              x1 = shfl_x(x, 1); x2 = shfl_x(x, 2); x3_ = shfl_x(x, 3);
              FENCE();
              bad = or3(x3(v[0].x, v[1].x, tg), x3(v[2].x, y[0], tg), x3(y[1], y[2], tg));
            } while (__any_sync(~0u, bad & 1u) && n < SPIN_LIMIT);
            float sx[10];
#pragma unroll
            for (int i = 0; i < 5; i++) h2f(sx[2 * i], sx[2 * i + 1], t[i]);
            FENCE();
            const float mx = fminf(fminf(u2f(x), u2f(x1)), fminf(u2f(x2), u2f(x3_)));
#pragma unroll
            for (int i = 2; i < 12; i++) sx[i % 10] = ex2(fmaf(sx[i % 10], 32.f * sc, mx));
#pragma unroll
            for (int i = 1; i < 6; i++) m[i % 5] = pack_bf16(sx[2 * (i % 5)], sx[2 * (i % 5) + 1]);
            sts128(ls + SM_PF, m[1], m[2], m[3], m[4]);
            sts32(ls - l12 + SM_PF + 512, m[0]);
            TV(19, n - 1);
          }
          TS(12);
          bar_sync(B_P, 96);
          if (LN) {
            const uint4 pa = lds128(ls + SM_PF); const uint32_t pb = lds32(ls - l12 + SM_PF + 512);
#define S2(w) (u2f((w) << 16) + u2f((w) & 0xffff0000u))
            float z = ((S2(pa.x) + S2(pa.y)) + (S2(pa.z) + S2(pa.w))) + S2(pb);
            z += __shfl_xor_sync(~0u, z, 1); z += __shfl_xor_sync(~0u, z, 2);
            sts32(sb + SM_Z + (l16 >> 6) * 4, f2u(rcpf(z)));
            bar_arrive(B_O, 352);
          }
          OPAQUE_R(l16);
          {
            const unsigned char* pe = P.win + w_blk(w_ar(s) + 384 + (l16 & 0x60u) * 256 + (l16 & 16u) * 128, me);
            const uint32_t tp = gt32() + DLY_M3;
            PRB(12);
            if (F0W == 0 && s < NSEG - 2) F0LOAD();
            if (PA) ETAT(tp, 0);
            uint32_t tg0; int n = 0;
#pragma unroll 1
            for (;;) {
              const uint2 e = ldg_r2(pe);
              tg0 = __reduce_max_sync(~0u, e.y);
              if (tg0 - tp >= 4096u) tg0 = tp;
              if ((!__any_sync(~0u, e.x != 16u) && (int)(tg0 - gt32()) < DLY_RR) || ++n >= SPIN_LIMIT) break;
            }
            sts32(sb + SM_Z + 32, tg0);
            bar_arrive(B_GO, GW ? 96 : 64);

            if (GW == 0) {
            M3PTR(s);
            while (tg0 - gt32() - 1u < 8192u) {}
            PRB(13);
            TS(16);
            M3REQ(s + 1 < NSEG);
            }
            TS(25);
          }
          if (F1C && s < NSEG - 2) {
            if (F1C == 1) spin(DLY_FA);
            mbar_wait(sb + SM_BAR + MB_XE1, (s + 1) & 1);
            if (l16 == 0) mbar_expect_tx(sb + SM_BAR + MB_F + 8, 32768);
            if (F1C == 2) { mbar_wait(sb + SM_BAR + MB_MEM, (s + 1) & 1); mbar_wait(sb + SM_BAR + MB_MEM + 8, (s + 1) & 1); }
            if (F1C == 3) { mbar_wait(sb + SM_BAR + MB_G, (s + 1) & 1); mbar_wait(sb + SM_BAR + MB_G + 8, (s + 1) & 1); }
            PRB(11);
            if (l16 == 0) XLOAD(1, s + 2);
            __syncwarp();
          }
          if (XPF && s + XPF < NSEG) {
            spin(DLY_PF);
            for (uint32_t i = xrank; i < 512; i += 32 * xcnt)
              asm volatile("prefetch.global.L2 [%0];" :: "l"(SP.x + (size_t)(s + XPF) * (SEG * DM) + i * 64));
            __syncwarp();
          }
          stg_2(P.win + (w_ar(s + 2) + cta * 256 + (l16 >> 1)), 0u, 0u);
        }
      } else {
        const int mt = wq - 2;
        const uint32_t lt = ls + mt * 1024;
        const uint32_t vi0 = w_blk(w_mvx(h * 4, 0), me2) + mt * 1024;
        const int m3d = r ? -8192 : 8192;
        float ox[4][4], zx[4];
#pragma unroll
        for (int i = 0; i < 16; i++) ox[i >> 2][i & 3] = zx[i & 3] = 1.f;
        for (int s = 0;; s++) {
          const uint32_t tg = (s & 1) ^ 1, t2 = ((s >> 1) & 1) ^ 1;
          {
            OPAQUE_R(l16);
            const uint32_t m3i = (mt * 2 + r) * 8192 + (l16 & 0x70u) + ((l16 & 0x180u) << 1);
            const uint32_t m3j = (mt * 2 + (r ^ (l16 >> 7 & 1))) * 8192 + ((l16 & 64u) * 4 + (l16 & 48u) * 2 + (l16 & 16u)) * 16 + 128 + (l16 & 0x70u);
            uint32_t m3c = sb + SM_MEM + mt * 8192 + cnt_line(l16 >> 4) * 128 + (l16 >> 2);
            const unsigned char* p3 = P.win + (m3i + w_ar(s - 1)); const unsigned char* pd = P.win + (m3j + w_ar(s - 1));
            OPAQUE_L(pd); OPAQUE_R(m3c);
#define XEPI() do {        \
              PVE(ox, zx, SM_OX + mt * 512); \
              __syncwarp(); \
              const uint32_t oa = sb + SM_OX + mt * 512 + ((l16 & 48u) << 3) + ((l16 >> 2) & 0x70u); \
              const uint4 a = lds128(oa), b = lds128(oa + 1024); \
              unsigned char* o = reinterpret_cast<unsigned char*>(g_ox + (size_t)((s - 1) * SEG + 8 * j) * (NH * DH) + h * DH + mt * 32) + ((l16 >> 6) * (NH * DH * 2) + (l16 & 48u)); \
              stg_4(o, a); stg_4(o + 128, b); \
              TST(s - 1, 18, l16 | mt, TCLK()); } while (0)
            if (s > 0) XEPI();
            if (s == NSEG) break;
            if (GW && s > 0) {
              M3PTR(s - 1);
              bar_sync(B_GO, 96);
              const uint32_t tg0 = lds32(sb + SM_Z + 32);
              while (tg0 - gt32() - 1u < 8192u) {}
              M3REQ(0);
            }
            FENCE();
            const int n = m3_check(sb, p3, pd, m3d, l16, m3c, mt, s);
            FENCE();
            if (ETW == 3 && s < NSEG - 1) ETA(DLY_K, mt);
            TST(s - 1, 14, l16 | mt, TCLK());
            TST(s, mt ? 22 : 17, l16, n);
#ifdef PER
            if (l16 == 0 && mt == 0 && s > 0) { g_per[cta][s - 1] = gt32(); g_pclk[cta][s - 1] = clk32(); }
#endif
          }
          uint4 va[8], vm[2], p0, q0; uint32_t p2, q2;
          const unsigned char* a0 = P.win + (vi0 + ((s & 1) << 20) + l16);
#define VALD() _Pragma("unroll") for (int i = 0; i < 4; i++) { va[i] = ldg_r4(a0 + (i >> 1) * 512 + (i & 1) * 2048); va[4 + i] = ldg_r4(a0 + 16384 + (i >> 1) * 512 + (i & 1) * 2048); }
          spin(DLY_WO);
          VALD();
          {
          PTRS();
          bar_sync(B_V, 320);
            const float4 u0 = lds128f(lt + SM_VP), w0 = lds128f(lt + SM_VP + 2048), u1 = lds128f(lt + SM_VP + 512), w1 = lds128f(lt + SM_VP + 2560);
            const uint32_t m0 = tagw(pack_bf16(u0.x + w0.x, u0.y + w0.y), tg), m1 = pack_bf16(u0.z + w0.z, u0.w + w0.w),
                           m2 = pack_bf16(u1.x + w1.x, u1.y + w1.y), m3 = pack_bf16(u1.z + w1.z, u1.w + w1.w);
            stg_r4(pw0, m0, m1, m2, m3);
            if (wq == 2) TS(10);
            FENCE();
            const uint32_t tv = clk32();
            if (ETW == 2 && wq == 3 && s < NSEG - 1) ETA(DLY_K, 1);
            while (clk32() - tv < (uint32_t)DLY_V) {}
            uint4 v[3]; int n = 0; uint32_t bada = 0;
#pragma unroll 1
            do {
              v[0] = ldg_r4(pr0); v[1] = ldg_r4(pr1); v[2] = ldg_r4(pr1 + 2048);
              if (n) {
                if (__any_sync(~0u, bada & 1u)) { VALD(); }
                if (s < NSEG - 1) ETA(DLY_KS - 192, 0);
              }
              n++;
              FENCE();
              bada = or3(x3(va[0].x, va[1].x, t2), x3(va[2].x, va[3].x, t2), x3(va[4].x, va[5].x, t2)) | x3(va[6].x, va[7].x, t2);
            } while (__any_sync(~0u, or3(bada, x3(v[0].x, v[1].x, tg), v[2].x ^ tg) & 1u) && n < SPIN_LIMIT);
            const uint4 A = make_uint4(addb2(m0, v[0].x), addb2(m1, v[0].y), addb2(m2, v[0].z), addb2(m3, v[0].w));
            const uint4 B = make_uint4(addb2(v[1].x, v[2].x), addb2(v[1].y, v[2].y), addb2(v[1].z, v[2].z), addb2(v[1].w, v[2].w));
            vm[0] = p ? B : A; vm[1] = p ? A : B;
            TST(s, 11, l16 | mt, TCLK()); TST(s, 29, l16 | (mt ^ 1), TCLK());
          }
          if (F0W == 2 && wq == 3 && s < NSEG - 2) F0LOAD();
          if (PXE) { bar_sync(B_PX, 96); q0 = lds128(ls + SM_PX); q2 = lds32(ls - l12 + SM_PX + 512); }
          FENCE();
          if (s < NSEG - 1) {
          PRB(5);
          bar_sync(B_P, 96);
          PRB(6);
          p0 = lds128(ls + SM_PF); p2 = lds32(ls - l12 + SM_PF + 512);
          float o[4][4], z[4];
#if LN
          FENCE();
#pragma unroll
          for (int t = 0; t < 4; t++) mma4z(o[t], va[2 * t].x, va[2 * t].y, va[2 * t].z, va[2 * t].w, p0.x, p0.y);
#pragma unroll
          for (int t = 0; t < 4; t++) mma4(o[t], va[2 * t + 1].x, va[2 * t + 1].y, va[2 * t + 1].z, va[2 * t + 1].w, p0.z, p0.w);
          mma_1688(o[0], vm[0].x, vm[0].y, p2); mma_1688(o[1], vm[0].z, vm[0].w, p2); mma_1688(o[2], vm[1].x, vm[1].y, p2); mma_1688(o[3], vm[1].z, vm[1].w, p2);
#pragma unroll
          for (int u = 0; u < 2; u++)
            stsm4t(ls + (SM_OF + mt * 512) + u * 1024, pack_bf16(o[2 * u][0], o[2 * u][1]), pack_bf16(o[2 * u][2], o[2 * u][3]),
                   pack_bf16(o[2 * u + 1][0], o[2 * u + 1][1]), pack_bf16(o[2 * u + 1][2], o[2 * u + 1][3]));
          bar_arrive(B_O, 352);
#else
#ifdef PROF
          uint32_t tq0, tq1;
          asm volatile("{\n.reg .u32 x;\nand.b32 x, %1, 0;\nmov.u32 %0, %%clock;\nadd.u32 %0, %0, x;\n}" : "=r"(tq0) : "r"(p0.x ^ p2));
#endif
          PVM(o, z, p0, p2);
#ifdef PROF
          FENCE();
          asm volatile("{\n.reg .pred q;\nsetp.eq.f32 q, %1, 0f7f7fffff;\n@q trap;\nmov.u32 %0, %%clock;\n}" : "=r"(tq1) : "f"(o[3][0]));
#endif
          PVE(o, z, SM_OF + mt * 512);
          if (XH) { bar_arrive(B_O, 192); bar_arrive(B_O2, 192); } else bar_arrive(B_O, 320);
          TST(s, 20, l16 | mt, tq1);
#endif
          }
          FENCE();
          TST(s, 8, l16 | mt, TCLK()); TST(s, 24, l16 | (mt ^ 1), TCLK());
          if (!PXE) { spin(DLY_PX); bar_sync(B_PX, 96); q0 = lds128(ls + SM_PX); q2 = lds32(ls - l12 + SM_PX + 512); }
          if (EPI < 4) PVM(ox, zx, q0, q2);
          FENCE();
          if (s < NSEG - 1) { bar_arrive(B_PXF, 96); if (BGT && l16 == 0) mbar_arrive(sb + SM_BAR + MB_F); }
        }
      }
    }
  }
#if RLX
  asm volatile("barrier.cluster.arrive.relaxed.aligned;\nbarrier.cluster.wait.aligned;" ::: "memory");
#else
  asm volatile("barrier.cluster.arrive.release.aligned;\nbarrier.cluster.wait.acquire.aligned;" ::: "memory");
#endif
#ifdef PER
  if (threadIdx.x == 0) atomicMax(&g_end[0], gt32());
#endif
}
#ifndef PW
#define PW 2
#endif
#ifndef G2_ST
#define G2_ST 6
#endif
#define G2_TB (G2_ST * 32768 + 1024)
#define G2_SMEM (G2_TB + 32768)
static __device__ __forceinline__ void wgmma_n128_ta(float (&d)[64], uint64_t da, uint64_t db) {
  asm volatile(
      "wgmma.mma_async.sync.aligned.m64n128k16.f32.bf16.bf16 "
      "{%0,%1,%2,%3,%4,%5,%6,%7,%8,%9,%10,%11,%12,%13,%14,%15,%16,%17,%18,%19,%20,%21,%22,%23,%24,%25,%26,%27,%28,%29,%30,%31,"
      "%32,%33,%34,%35,%36,%37,%38,%39,%40,%41,%42,%43,%44,%45,%46,%47,%48,%49,%50,%51,%52,%53,%54,%55,%56,%57,%58,%59,%60,%61,%62,%63}, "
      "%64, %65, 1, 1, 1, 1, 0;"
      : "+f"(d[0]), "+f"(d[1]), "+f"(d[2]), "+f"(d[3]), "+f"(d[4]), "+f"(d[5]), "+f"(d[6]), "+f"(d[7]), "+f"(d[8]), "+f"(d[9]), "+f"(d[10]), "+f"(d[11]),
        "+f"(d[12]), "+f"(d[13]), "+f"(d[14]), "+f"(d[15]), "+f"(d[16]), "+f"(d[17]), "+f"(d[18]), "+f"(d[19]), "+f"(d[20]), "+f"(d[21]), "+f"(d[22]), "+f"(d[23]),
        "+f"(d[24]), "+f"(d[25]), "+f"(d[26]), "+f"(d[27]), "+f"(d[28]), "+f"(d[29]), "+f"(d[30]), "+f"(d[31]), "+f"(d[32]), "+f"(d[33]), "+f"(d[34]), "+f"(d[35]),
        "+f"(d[36]), "+f"(d[37]), "+f"(d[38]), "+f"(d[39]), "+f"(d[40]), "+f"(d[41]), "+f"(d[42]), "+f"(d[43]), "+f"(d[44]), "+f"(d[45]), "+f"(d[46]), "+f"(d[47]),
        "+f"(d[48]), "+f"(d[49]), "+f"(d[50]), "+f"(d[51]), "+f"(d[52]), "+f"(d[53]), "+f"(d[54]), "+f"(d[55]), "+f"(d[56]), "+f"(d[57]), "+f"(d[58]), "+f"(d[59]),
        "+f"(d[60]), "+f"(d[61]), "+f"(d[62]), "+f"(d[63])
      : "l"(da), "l"(db));
}
__global__ void __cluster_dims__(2, 1, 1) __launch_bounds__(384, 1)
gemm2_kernel(const __grid_constant__ CUtensorMap tmo, const __grid_constant__ CUtensorMap tmw, const bf16* __restrict__ x, bf16* __restrict__ out, unsigned char* win) {
  extern __shared__ __align__(1024) unsigned char smem[];
  const uint32_t sb = smem_u32(smem), bars = sb + G2_ST * 32768;
  const int tid = threadIdx.x, lane = tid & 31, warp = tid >> 5;
  const int r = blockIdx.x & 1, n0 = (blockIdx.x & 7) * 128, m0 = (blockIdx.x >> 3) * 128;
  if (tid == 0) {
    for (int i = 0; i < G2_ST; i++) { mbar_init(bars + i * 8, 1); mbar_init(bars + 64 + i * 8, 4); }
    asm volatile("fence.mbarrier_init.release.cluster;" ::: "memory");
  }
  if (tid == 32) { asm volatile("prefetch.tensormap [%0];" :: "l"(&tmw) : "memory"); asm volatile("prefetch.tensormap [%0];" :: "l"(&tmo) : "memory"); }
  __syncthreads();
  asm volatile("barrier.cluster.arrive.relaxed.aligned;" ::: "memory");
#define LW(kt, st) do { tma_load_2d(sb + (st) * 32768, &tmw, n0, (kt) * 64, bars + (st) * 8); tma_load_2d(sb + (st) * 32768 + 8192, &tmw, n0 + 64, (kt) * 64, bars + (st) * 8); } while (0)
#define LO(kt, st) asm volatile("cp.async.bulk.tensor.2d.shared::cluster.global.mbarrier::complete_tx::bytes.multicast::cluster [%0], [%1, {%3, %4}], [%2], %5;" \
                     :: "r"(sb + (st) * 32768 + 16384 + r * 8192), "l"(&tmo), "r"(bars + (st) * 8), "r"((kt) * 64), "r"(m0 + r * 64), "h"((uint16_t)3) : "memory")
  if (tid == 256) for (int kt = 0; kt < G2_ST; kt++) { mbar_expect_tx(bars + kt * 8, 32768); if (kt < PW) LW(kt, kt); }
  __syncwarp();
  asm volatile("barrier.cluster.wait.acquire.aligned;" ::: "memory");
  if (warp == 8) {
    if (lane == 0) {
      asm volatile("griddepcontrol.wait;" ::: "memory");
      for (int kt = 0; kt < G2_ST; kt++) { LO(kt, kt); if (kt >= PW) LW(kt, kt); }
      for (int kt = G2_ST; kt < 64; kt++) {
        const int st = kt % G2_ST;
        mbar_wait(bars + 64 + st * 8, ((kt / G2_ST) - 1) & 1);
        mbar_expect_tx(bars + st * 8, 32768);
        LO(kt, st); LW(kt, st);
      }
    }
  } else if (warp > 8) {
    const int t = tid - 288, ch = t & 15;
    asm volatile("griddepcontrol.wait;" ::: "memory");
#ifdef PER
    if (t == 0) atomicMax(&g_end[3], gt32());
#endif
    int idx[8];
#pragma unroll
    for (int c = 0; c < 8; c++) idx[c] = g_idx[c];
    const int gi = blockIdx.x * 96 + t;
    if (gi < 67) g_side[gi * 32] = 0u;
    if (gi == 0) g_sbar = 0u;
#pragma unroll 4
    for (int row = t >> 4; row < 128; row += 6) {
      const int tok = m0 + row;
      const uint4 xv = *reinterpret_cast<const uint4*>(x + (size_t)tok * DM + n0 + ch * 8);
      const float g = g_gate[tok], omg = rbf(1.f - g);
      int sel = -1;
#pragma unroll
      for (int c = 0; c < 8; c++) if (idx[c] == tok) sel = c;
      uint4 uv = make_uint4(0u, 0u, 0u, 0u);
      if (sel >= 0) uv = *reinterpret_cast<const uint4*>(g_upd + sel * DM + n0 + ch * 8);
      const uint32_t x4[4] = {xv.x, xv.y, xv.z, xv.w}, u4[4] = {uv.x, uv.y, uv.z, uv.w};
      uint32_t o4[4];
#pragma unroll
      for (int e = 0; e < 4; e++) {
        const float b0 = rbf(u2f(x4[e] << 16) + u2f(u4[e] << 16)), b1 = rbf(u2f(x4[e] & 0xffff0000u) + u2f(u4[e] & 0xffff0000u));
        o4[e] = pack_bf16(omg * b0, omg * b1);
      }
      sts128(sb + G2_TB + row * 256 + ch * 16, o4[0], o4[1], o4[2], o4[3]);
      if (ch == 0) sts32(bars + 512 + row * 4, __float_as_uint(g));
    }
    bar_arrive(2, 352);
  } else {
    const int wg = warp >> 2;
    float d[64];
#pragma unroll
    for (int i = 0; i < 64; i++) d[i] = 0.f;
    const uint32_t e0 = mapa(bars + 64, 0), e1 = mapa(bars + 64, 1);
#ifdef PER
    if (threadIdx.x == 0) { mbar_wait(bars, 0); atomicMax(&g_end[4], gt32()); }
    __syncwarp();
#endif
    for (int kt = 0; kt < 64; kt++) {
      const int st = kt % G2_ST;
      mbar_wait(bars + st * 8, (kt / G2_ST) & 1);
      wg_fence();
#pragma unroll
      for (int kk = 0; kk < 4; kk++)
        wgmma_n128_ta(d, make_desc(sb + st * 32768 + wg * 8192 + kk * 2048, 1024, 1024), make_desc(sb + st * 32768 + 16384 + kk * 32, 16, 1024));
      wg_commit();
      asm volatile("wgmma.wait_group.sync.aligned 1;" ::: "memory");
      if (kt > 0 && (tid & 127) == 0) { const int ps = (kt - 1) % G2_ST; mbar_arrive_cluster_rlx(e0 + ps * 8); mbar_arrive_cluster_rlx(e1 + ps * 8); }
    }
    wg_wait0();
#ifdef PER
    if (threadIdx.x == 0) atomicMax(&g_end[5], gt32());
#endif
    bar_sync(1, 256);
#pragma unroll
    for (int jj = 0; jj < 8; jj++) {
      const uint32_t q0 = pack_bf16(d[8 * jj], d[8 * jj + 1]), q1 = pack_bf16(d[8 * jj + 2], d[8 * jj + 3]);
      const uint32_t q2 = pack_bf16(d[8 * jj + 4], d[8 * jj + 5]), q3 = pack_bf16(d[8 * jj + 6], d[8 * jj + 7]);
      stsm4t(sb + (jj * 16 + (lane >> 4) * 8 + (lane & 7)) * 272 + (warp * 16 + ((lane >> 3) & 1) * 8) * 2, q0, q1, q2, q3);
    }
    bar_sync(2, 352);
#pragma unroll
    for (int it = 0; it < 8; it++) {
      const int row = it * 16 + (tid >> 4), ch = tid & 15, tok = m0 + row;
      const uint4 av = lds128(sb + row * 272 + ch * 16), tv = lds128(sb + G2_TB + row * 256 + ch * 16);
      const float g = u2f(lds32(bars + 512 + row * 4));
      const uint32_t a4[4] = {av.x, av.y, av.z, av.w}, t4[4] = {tv.x, tv.y, tv.z, tv.w};
      uint32_t o4[4];
#pragma unroll
      for (int e = 0; e < 4; e++)
        o4[e] = pack_bf16(rbf(g * u2f(a4[e] << 16)) + u2f(t4[e] << 16), rbf(g * u2f(a4[e] & 0xffff0000u)) + u2f(t4[e] & 0xffff0000u));
      *reinterpret_cast<uint4*>(out + (size_t)tok * DM + n0 + ch * 8) = make_uint4(o4[0], o4[1], o4[2], o4[3]);
    }
  }
  asm volatile("barrier.cluster.arrive.relaxed.aligned;\nbarrier.cluster.wait.aligned;" ::: "memory");
#ifdef PER
  if (threadIdx.x == 0) atomicMax(&g_end[2], gt32());
#endif
}
#ifndef WPROM
#define WPROM CU_TENSOR_MAP_L2_PROMOTION_L2_128B
#endif
#ifndef PDL
#define PDL 1
#endif
typedef CUresult (*PFN_encodeTiled)(CUtensorMap*, CUtensorMapDataType, cuuint32_t, void*, const cuuint64_t*, const cuuint64_t*,
                                    const cuuint32_t*, const cuuint32_t*, CUtensorMapInterleave, CUtensorMapSwizzle,
                                    CUtensorMapL2promotion, CUtensorMapFloatOOBfill);

extern "C" void kernel_launch(void* const* d_in, const int* in_sizes, int n_in, void* d_out, int out_size) {
  const bf16* x = (const bf16*)d_in[0];
  const bf16* mem0 = (const bf16*)d_in[1];
  const bf16* Wq = (const bf16*)d_in[2];
  const bf16* Wk = (const bf16*)d_in[3];
  const bf16* Wv = (const bf16*)d_in[4];
  const bf16* Wo = (const bf16*)d_in[5];
  const bf16* w_r = (const bf16*)d_in[8];
  const bf16* w_gate = (const bf16*)d_in[9];
  const bf16* w_up = (const bf16*)d_in[10];
  const bf16* w_down = (const bf16*)d_in[11];
  const bf16* gate_w = (const bf16*)d_in[12];
  bf16* out = (bf16*)d_out;

  static PFN_encodeTiled encode = nullptr;
  if (!encode) {
    void* fn = nullptr; cudaDriverEntryPointQueryResult st;
    cudaGetDriverEntryPoint("cuTensorMapEncodeTiled", &fn, cudaEnableDefault, &st);
    encode = (PFN_encodeTiled)fn;
    cudaFuncSetAttribute(rec_kernel, cudaFuncAttributeMaxDynamicSharedMemorySize, SM_TOTAL);
    cudaFuncSetAttribute(gemm2_kernel, cudaFuncAttributeMaxDynamicSharedMemorySize, G2_SMEM);
  }
  CUtensorMap tmx;
  {
    cuuint64_t gd[3] = {64, S_TOK, DM / 64};
    cuuint64_t gs[2] = {DM * 2, 128};
    cuuint32_t bx[3] = {64, SEG, 4};
    cuuint32_t es[3] = {1, 1, 1};
    encode(&tmx, CU_TENSOR_MAP_DATA_TYPE_BFLOAT16, 3, (void*)x, gd, gs, bx, es, CU_TENSOR_MAP_INTERLEAVE_NONE,
           CU_TENSOR_MAP_SWIZZLE_128B, CU_TENSOR_MAP_L2_PROMOTION_L2_128B, CU_TENSOR_MAP_FLOAT_OOB_FILL_NONE);
  }
  bf16* ox;
  cudaGetSymbolAddress((void**)&ox, g_ox);
  CUtensorMap tmo, tmw;
  {
    cuuint64_t gd[2] = {NH * DH, S_TOK}; cuuint64_t gs[1] = {NH * DH * 2}; cuuint32_t bx[2] = {64, 64}; cuuint32_t es[2] = {1, 1};
    encode(&tmo, CU_TENSOR_MAP_DATA_TYPE_BFLOAT16, 2, (void*)ox, gd, gs, bx, es, CU_TENSOR_MAP_INTERLEAVE_NONE,
           CU_TENSOR_MAP_SWIZZLE_128B, CU_TENSOR_MAP_L2_PROMOTION_L2_128B, CU_TENSOR_MAP_FLOAT_OOB_FILL_NONE);
    cuuint64_t gd2[2] = {DM, NH * DH}; cuuint64_t gs2[1] = {DM * 2}; cuuint32_t bx2[2] = {64, 64};
    encode(&tmw, CU_TENSOR_MAP_DATA_TYPE_BFLOAT16, 2, (void*)Wo, gd2, gs2, bx2, es, CU_TENSOR_MAP_INTERLEAVE_NONE,
           CU_TENSOR_MAP_SWIZZLE_128B, CU_TENSOR_MAP_L2_PROMOTION_L2_128B, CU_TENSOR_MAP_FLOAT_OOB_FILL_NONE);
  }
  unsigned char* win;
  cudaGetSymbolAddress((void**)&win, g_win);
  win = (unsigned char*)(((uintptr_t)win + (2u << 20) - 1) & ~(uintptr_t)((2u << 20) - 1));
  WMaps W;
  {
    cuuint64_t gd[2] = {NH * DH, DM}; cuuint64_t gs[1] = {NH * DH * 2}; cuuint32_t b32[2] = {32, 128}, b64[2] = {64, 128}; cuuint32_t es[2] = {1, 1};
    encode(&W.q, CU_TENSOR_MAP_DATA_TYPE_BFLOAT16, 2, (void*)Wq, gd, gs, b32, es, CU_TENSOR_MAP_INTERLEAVE_NONE,
           CU_TENSOR_MAP_SWIZZLE_64B, WPROM, CU_TENSOR_MAP_FLOAT_OOB_FILL_NONE);
    encode(&W.k, CU_TENSOR_MAP_DATA_TYPE_BFLOAT16, 2, (void*)Wk, gd, gs, b32, es, CU_TENSOR_MAP_INTERLEAVE_NONE,
           CU_TENSOR_MAP_SWIZZLE_64B, WPROM, CU_TENSOR_MAP_FLOAT_OOB_FILL_NONE);
    encode(&W.v, CU_TENSOR_MAP_DATA_TYPE_BFLOAT16, 2, (void*)Wv, gd, gs, b64, es, CU_TENSOR_MAP_INTERLEAVE_NONE,
           CU_TENSOR_MAP_SWIZZLE_128B, WPROM, CU_TENSOR_MAP_FLOAT_OOB_FILL_NONE);
  }
  RecParams P{mem0, win};
  SideParams SP{x, w_r, w_gate, w_up, w_down, gate_w, Wo};
  rec_kernel<<<NCTA + 4, 384, SM_TOTAL, cudaStreamPerThread>>>(tmx, tmw, W, P, SP);
  {
    cudaLaunchConfig_t cfg = {};
    cfg.gridDim = dim3(NCTA); cfg.blockDim = dim3(384); cfg.dynamicSmemBytes = G2_SMEM; cfg.stream = cudaStreamPerThread;
    cudaLaunchAttribute at[1];
    at[0].id = cudaLaunchAttributeProgrammaticStreamSerialization; at[0].val.programmaticStreamSerializationAllowed = 1;
    cfg.attrs = at; cfg.numAttrs = PDL;
    cudaLaunchKernelEx(&cfg, gemm2_kernel, tmo, tmw, x, out, win);
  }
}
```

```cpp
#include <cuda_runtime.h>
#include <cuda_bf16.h>
#include <cuda_fp16.h>
#include <cuda.h>
#include <stdint.h>

typedef __nv_bfloat16 bf16;

#define S_TOK 2048
#define DM 1024
#define NH 32
#define DH 128
#define MM 8
#define SEG 32
#define NSEG 64
#define LL 40
#define FF 3584
#define NCTA 128

static __device__ bf16 g_ox[(size_t)S_TOK * NH * DH];
static __device__ float g_gate[S_TOK];
static __device__ float g_r[S_TOK];
static __device__ int g_idx[8];
static __device__ bf16 g_upd[8 * DM];

static __device__ __forceinline__ float rbf(float v) { return __bfloat162float(__float2bfloat16(v)); }
static __device__ __forceinline__ uint32_t smem_u32(const void* p) { return (uint32_t)__cvta_generic_to_shared(p); }
static __device__ __forceinline__ uint32_t pack_bf16(float lo, float hi) {
  __nv_bfloat162 v = __floats2bfloat162_rn(lo, hi);
  return *reinterpret_cast<uint32_t*>(&v);
}

static __device__ __forceinline__ void wg_fence() { asm volatile("wgmma.fence.sync.aligned;" ::: "memory"); }
static __device__ __forceinline__ void wg_commit() { asm volatile("wgmma.commit_group.sync.aligned;" ::: "memory"); }
static __device__ __forceinline__ void wg_wait0() { asm volatile("wgmma.wait_group.sync.aligned 0;" ::: "memory"); }
static __device__ __forceinline__ void wg_wait1() { asm volatile("wgmma.wait_group.sync.aligned 1;" ::: "memory"); }
static __device__ __forceinline__ void fence_async_smem() { asm volatile("fence.proxy.async.shared::cta;" ::: "memory"); }

static __device__ __forceinline__ uint64_t make_desc(uint32_t addr, uint32_t lbo, uint32_t sbo) {
  uint64_t d = 0;
  d |= (uint64_t)((addr & 0x3FFFF) >> 4);
  d |= (uint64_t)((lbo >> 4) & 0x3FFF) << 16;
  d |= (uint64_t)((sbo >> 4) & 0x3FFF) << 32;
  d |= (uint64_t)1 << 62;
  return d;
}

#define DESC_HI(sbo) (((sbo) >> 4) | (1u << 30))
template <int OFF, int SCALE>
static __device__ __forceinline__ void wgmma_n32_ra(float (&d)[16], const uint32_t (&a)[4], uint32_t base16) {
  asm volatile(
      "{\n.reg .b32 t;\n.reg .b64 dd;\nadd.u32 t, %20, %21;\nmov.b64 dd, {t, %22};\n"
      "wgmma.mma_async.sync.aligned.m64n32k16.f32.bf16.bf16 "
      "{%0,%1,%2,%3,%4,%5,%6,%7,%8,%9,%10,%11,%12,%13,%14,%15}, {%16,%17,%18,%19}, dd, %23, 1, 1, 0;\n}"
      : "+f"(d[0]), "+f"(d[1]), "+f"(d[2]), "+f"(d[3]), "+f"(d[4]), "+f"(d[5]), "+f"(d[6]), "+f"(d[7]),
        "+f"(d[8]), "+f"(d[9]), "+f"(d[10]), "+f"(d[11]), "+f"(d[12]), "+f"(d[13]), "+f"(d[14]), "+f"(d[15])
      : "r"(a[0]), "r"(a[1]), "r"(a[2]), "r"(a[3]), "r"(base16), "n"(OFF >> 4), "n"(DESC_HI(1024)), "n"(SCALE));
}
template <int AOFF, int BOFF, int SCALE>
static __device__ __forceinline__ void wgmma_n32_ss_ta(float (&d)[16], uint32_t abase16, uint32_t bbase16) {
  asm volatile(
      "{\n.reg .b32 t, u;\n.reg .b64 da, db;\nadd.u32 t, %16, %18;\nmov.b64 da, {t, %20};\nadd.u32 u, %17, %19;\nmov.b64 db, {u, %20};\n"
      "wgmma.mma_async.sync.aligned.m64n32k16.f32.bf16.bf16 "
      "{%0,%1,%2,%3,%4,%5,%6,%7,%8,%9,%10,%11,%12,%13,%14,%15}, da, db, %21, 1, 1, 1, 0;\n}"
      : "+f"(d[0]), "+f"(d[1]), "+f"(d[2]), "+f"(d[3]), "+f"(d[4]), "+f"(d[5]), "+f"(d[6]), "+f"(d[7]),
        "+f"(d[8]), "+f"(d[9]), "+f"(d[10]), "+f"(d[11]), "+f"(d[12]), "+f"(d[13]), "+f"(d[14]), "+f"(d[15])
      : "r"(abase16), "r"(bbase16), "n"(AOFF >> 4), "n"(BOFF >> 4), "n"(DESC_HI(1024)), "n"(SCALE));
}
static __device__ __forceinline__ void ldmatrix_x4_trans(uint32_t (&r)[4], uint32_t addr) {
  asm volatile("ldmatrix.sync.aligned.m8n8.x4.trans.shared.b16 {%0,%1,%2,%3}, [%4];"
               : "=r"(r[0]), "=r"(r[1]), "=r"(r[2]), "=r"(r[3]) : "r"(addr) : "memory");
}
static __device__ __forceinline__ void mma_16816(float (&d)[4], const uint32_t (&a)[4], uint32_t b0, uint32_t b1) {
  asm volatile("mma.sync.aligned.m16n8k16.row.col.f32.bf16.bf16.f32 {%0,%1,%2,%3}, {%4,%5,%6,%7}, {%8,%9}, {%0,%1,%2,%3};"
               : "+f"(d[0]), "+f"(d[1]), "+f"(d[2]), "+f"(d[3])
               : "r"(a[0]), "r"(a[1]), "r"(a[2]), "r"(a[3]), "r"(b0), "r"(b1));
}

static __device__ __forceinline__ uint32_t mapa(uint32_t addr, uint32_t rank) {
  uint32_t r; asm volatile("mapa.shared::cluster.u32 %0, %1, %2;" : "=r"(r) : "r"(addr), "r"(rank)); return r;
}

static __device__ __forceinline__ void mbar_init(uint32_t bar, int cnt) {
  asm volatile("mbarrier.init.shared::cta.b64 [%0], %1;" :: "r"(bar), "r"(cnt) : "memory");
}
static __device__ __forceinline__ void mbar_expect_tx(uint32_t bar, uint32_t bytes) {
  asm volatile("mbarrier.arrive.expect_tx.shared::cta.b64 _, [%0], %1;" :: "r"(bar), "r"(bytes) : "memory");
}
static __device__ __forceinline__ void tma_load_2d(uint32_t dst, const CUtensorMap* tm, int c0, int c1, uint32_t bar) {
  asm volatile("cp.async.bulk.tensor.2d.shared::cluster.global.mbarrier::complete_tx::bytes [%0], [%1, {%3, %4}], [%2];"
               :: "r"(dst), "l"(tm), "r"(bar), "r"(c0), "r"(c1) : "memory");
}

static __device__ unsigned char g_win[6 << 20];
static __device__ unsigned int g_side[67 * 32];
static __device__ unsigned int g_err;
#define W_UP (1u << 20)
#define W_2 (2u << 20)
static __device__ __forceinline__ uint32_t w_blk(uint32_t off, uint32_t side) { return off | (((__popc((off >> 12) & 0xb3u) ^ side) & 1u) << 12); }
static __device__ __forceinline__ uint32_t w_h1(int c) { return W_UP | (1u << 13) | ((c >> 1) << 14) | ((c & 1) << 11); }
#define W_DS 0x30000u
static __device__ __forceinline__ uint32_t w_ar(int s) { return ((s & 1) << 15) | ((s & 2) << 17); }
static __device__ __forceinline__ uint32_t w_mvx(int c, int s) { return W_2 | ((s & 1) << 20) | ((c >> 1) << 14) | ((c & 1) << 11); }
static __device__ __forceinline__ uint32_t w_mxa(int c, int s) { return W_2 | ((s & 1) << 20) | (1u << 13) | ((c >> 1) << 14) | ((c & 1) << 11); }
#define H1_V (1u << 13)

#define SPIN_LIMIT (1 << 18)

#define SM_X 0
#define SM_WOS 65536
#define SM_WVS 131072
#define SM_MEM 163840
#define SM_QKP 180224
#define SM_VP 184320
#define SM_CW 188416
#define SM_VST 196608
#define SM_VR 196608
#define SM_CQ 200704
#define SM_CV 208896
#define SM_XF 217088
#define SM_VL 221184
#define SM_OF 225280
#define SM_OX 227328
#define SM_PF 229376
#define SM_PX 230016
#define SM_RD 223232
#define SM_QA 230656
#define SM_XS 231168
#define SM_BAR 231808
#define SM_Z 231936
#define SM_TS 232064
#define NTS 40
#define SM_TOTAL SM_TS
#define MB_F 0
#define MB_XE0 16
#define MB_XE1 112
#define MB_INIT 24
#define MB_MEM 32
#define MB_W 48
#define MB_XF 64
#define MB_VR 72
#define MB_X0 80
#define MB_WO 88
#define SM_SIDE (SM_BAR + 96)
#define MB_G 192
#define B_QK 1
#define B_V 2
#define B_P 3
#define B_O 4
#define B_O2 5
#define B_PUB 6
#define B_CQ 7
#define B_QK1 8
#define B_LD 9
#define B_PXF 10
#define B_CV 15
#define B_X2 11
#define B_PX 12
#define B_GO 14
#define B_G1 13

#ifdef PROF
__device__ unsigned int g_ts[NCTA][80][32];
#ifdef GT
#define TCLK() gt32()
#else
#define TCLK() clk32()
#endif
#ifndef TMASK
#define TMASK 0xffffffffu
#endif
#define TST(st, i, c, v) do { if ((TMASK >> (i)) & 1u) asm volatile("{\n.reg .pred q;\nsetp.eq.u32 q, %2, 0;\n@q st.global.u32 [%0], %1;\n}" :: "l"(&g_ts[cta][(st) + 1][i]), "r"((uint32_t)(v)), "r"((uint32_t)(c)) : "memory"); } while (0)
#define TS(i) TST(s, i, l16, TCLK())
#define TV(i, v) TST(s, i, l16, v)
#define TSF(i, w) TST(s, i, l16 | (w8 ^ (w)), TCLK())
#define TSP(i, w) TST(s - 1, i, l16 | (w8 ^ (w)), TCLK())
#define TVF(i, v) TV(i, v)
#else
#define TST(a, b, c, d)
#define TSF(i, w)
#define TSP(i, w)
#define TVF(i, v)
#define TS(i)
#define TV(i, v)
#endif

static __device__ __forceinline__ void bar_sync(int id, int n) { asm volatile("bar.sync %0, %1;" :: "r"(id), "r"(n) : "memory"); }
static __device__ __forceinline__ void bar_arrive(int id, int n) { asm volatile("bar.arrive %0, %1;" :: "r"(id), "r"(n) : "memory"); }
static __device__ __forceinline__ uint4 ldg_r4(const void* p) { uint4 v;
  asm volatile("ld.relaxed.gpu.global.v4.u32 {%0,%1,%2,%3}, [%4];" : "=r"(v.x), "=r"(v.y), "=r"(v.z), "=r"(v.w) : "l"(p) : "memory"); return v; }
static __device__ __forceinline__ uint32_t ldg_r1(const void* p) { uint32_t v;
  asm volatile("ld.relaxed.gpu.global.u32 %0, [%1];" : "=r"(v) : "l"(p) : "memory"); return v; }
template <int OFF> static __device__ __forceinline__ uint32_t ldg_r1o(const void* p) { uint32_t v;
  asm volatile("ld.relaxed.gpu.global.u32 %0, [%1+%2];" : "=r"(v) : "l"(p), "n"(OFF) : "memory"); return v; }
static __device__ __forceinline__ void stg_r4(void* p, uint32_t a, uint32_t b, uint32_t c, uint32_t d) {
  asm volatile("st.relaxed.gpu.global.v4.u32 [%0], {%1,%2,%3,%4};" :: "l"(p), "r"(a), "r"(b), "r"(c), "r"(d) : "memory"); }
static __device__ __forceinline__ void stg_r2(void* p, uint32_t a, uint32_t b) {
  asm volatile("st.relaxed.gpu.global.v2.u32 [%0], {%1,%2};" :: "l"(p), "r"(a), "r"(b) : "memory"); }
static __device__ __forceinline__ uint2 ldg_r2(const void* p) { uint2 v;
  asm volatile("ld.relaxed.gpu.global.v2.u32 {%0,%1}, [%2];" : "=r"(v.x), "=r"(v.y) : "l"(p) : "memory"); return v; }
static __device__ __forceinline__ void stg_4(void* p, const uint4& v) {
  asm volatile("st.global.v4.u32 [%0], {%1,%2,%3,%4};" :: "l"(p), "r"(v.x), "r"(v.y), "r"(v.z), "r"(v.w) : "memory"); }
static __device__ __forceinline__ uint32_t f2u(float v) { return __float_as_uint(v); }
static __device__ __forceinline__ void stg_2(void* p, uint32_t a, uint32_t b) {
  asm volatile("st.global.v2.u32 [%0], {%1,%2};" :: "l"(p), "r"(a), "r"(b) : "memory"); }
static __device__ __forceinline__ void stg_r1(void* p, uint32_t a) {
  asm volatile("st.relaxed.gpu.global.u32 [%0], %1;" :: "l"(p), "r"(a) : "memory"); }
static __device__ __forceinline__ void sts128(uint32_t a, uint32_t x, uint32_t y, uint32_t z, uint32_t w) {
  asm volatile("st.shared.v4.u32 [%0], {%1,%2,%3,%4};" :: "r"(a), "r"(x), "r"(y), "r"(z), "r"(w) : "memory"); }
static __device__ __forceinline__ void sts128f(uint32_t a, float x, float y, float z, float w) {
  asm volatile("st.shared.v4.f32 [%0], {%1,%2,%3,%4};" :: "r"(a), "f"(x), "f"(y), "f"(z), "f"(w) : "memory"); }
static __device__ __forceinline__ uint4 lds128(uint32_t a) { uint4 v;
  asm volatile("ld.shared.v4.u32 {%0,%1,%2,%3}, [%4];" : "=r"(v.x), "=r"(v.y), "=r"(v.z), "=r"(v.w) : "r"(a) : "memory"); return v; }
static __device__ __forceinline__ float4 lds128f(uint32_t a) { float4 v;
  asm volatile("ld.shared.v4.f32 {%0,%1,%2,%3}, [%4];" : "=f"(v.x), "=f"(v.y), "=f"(v.z), "=f"(v.w) : "r"(a) : "memory"); return v; }
static __device__ __forceinline__ void sts32(uint32_t a, uint32_t x) { asm volatile("st.shared.u32 [%0], %1;" :: "r"(a), "r"(x) : "memory"); }
static __device__ __forceinline__ void sts64f(uint32_t a, float x, float y) { asm volatile("st.shared.v2.f32 [%0], {%1,%2};" :: "r"(a), "f"(x), "f"(y) : "memory"); }
static __device__ __forceinline__ uint2 lds64(uint32_t a) { uint2 v;
  asm volatile("ld.shared.v2.u32 {%0,%1}, [%2];" : "=r"(v.x), "=r"(v.y) : "r"(a) : "memory"); return v; }
static __device__ __forceinline__ void st_async4(uint32_t ra, float x, float y, float z, float w, uint32_t rbar) {
  asm volatile("st.async.weak.shared::cluster.mbarrier::complete_tx::bytes.v4.f32 [%0], {%1,%2,%3,%4}, [%5];"
               :: "r"(ra), "f"(x), "f"(y), "f"(z), "f"(w), "r"(rbar) : "memory"); }
static __device__ __forceinline__ void stsm4t(uint32_t a, uint32_t x, uint32_t y, uint32_t z, uint32_t w) {
  asm volatile("stmatrix.sync.aligned.m8n8.x4.trans.shared.b16 [%0], {%1,%2,%3,%4};" :: "r"(a), "r"(x), "r"(y), "r"(z), "r"(w) : "memory"); }
static __device__ __forceinline__ void stsm2t(uint32_t a, uint32_t x, uint32_t y) {
  asm volatile("stmatrix.sync.aligned.m8n8.x2.trans.shared.b16 [%0], {%1,%2};" :: "r"(a), "r"(x), "r"(y) : "memory"); }
static __device__ __forceinline__ uint32_t hfma2(uint32_t a, uint32_t b, uint32_t c) { uint32_t d;
  asm("fma.rn.f16x2 %0, %1, %2, %3;" : "=r"(d) : "r"(a), "r"(b), "r"(c)); return d; }
static __device__ __forceinline__ uint32_t hmax2(uint32_t a, uint32_t b) { uint32_t d;
  asm("max.f16x2 %0, %1, %2;" : "=r"(d) : "r"(a), "r"(b)); return d; }
static __device__ __forceinline__ uint32_t hadd2(uint32_t a, uint32_t b) { uint32_t d;
  asm("add.rn.f16x2 %0, %1, %2;" : "=r"(d) : "r"(a), "r"(b)); return d; }
static __device__ __forceinline__ uint32_t packv(float a, float b, float c, float d) { uint32_t r;
  asm volatile("{\n.reg .f32 x, y;\nadd.f32 x, %1, %2;\nadd.f32 y, %3, %4;\ncvt.rn.bf16x2.f32 %0, y, x;\n}" : "=r"(r) : "f"(a), "f"(b), "f"(c), "f"(d)); return r; }
static __device__ __forceinline__ float ex2v(float a, float b, float c) { float y;
  asm volatile("{\n.reg .f32 x;\nfma.rn.f32 x, %1, %2, %3;\nex2.approx.ftz.f32 %0, x;\n}" : "=f"(y) : "f"(a), "f"(b), "f"(c)); return y; }
static __device__ __forceinline__ uint32_t shfl_x(uint32_t a, int m) { uint32_t d;
  asm volatile("shfl.sync.bfly.b32 %0, %1, %2, 0x1f, 0xffffffff;" : "=r"(d) : "r"(a), "r"(m)); return d; }
static __device__ __forceinline__ void h2f(float& lo, float& hi, uint32_t a) {
  asm volatile("{\n.reg .b16 l, h;\nmov.b32 {l, h}, %2;\ncvt.f32.f16 %0, l;\ncvt.f32.f16 %1, h;\n}" : "=f"(lo), "=f"(hi) : "r"(a)); }
static __device__ __forceinline__ uint4 ldsm4(uint32_t a) { uint4 v;
  asm volatile("ldmatrix.sync.aligned.m8n8.x4.shared.b16 {%0,%1,%2,%3}, [%4];" : "=r"(v.x), "=r"(v.y), "=r"(v.z), "=r"(v.w) : "r"(a) : "memory"); return v; }
static __device__ __forceinline__ uint4 ldsm4t(uint32_t a) { uint4 v;
  asm volatile("ldmatrix.sync.aligned.m8n8.x4.trans.shared.b16 {%0,%1,%2,%3}, [%4];" : "=r"(v.x), "=r"(v.y), "=r"(v.z), "=r"(v.w) : "r"(a) : "memory"); return v; }
static __device__ __forceinline__ uint32_t movm(uint32_t a) { uint32_t d;
  asm volatile("movmatrix.sync.aligned.m8n8.trans.b16 %0, %1;" : "=r"(d) : "r"(a)); return d; }
static __device__ __forceinline__ float u2f(uint32_t v) { return __uint_as_float(v); }
static __device__ __forceinline__ uint32_t nz(uint32_t w) { return w == 0u ? 0x8000u : w; }
static __device__ __forceinline__ uint32_t tagw(uint32_t w, uint32_t t) { uint32_t d;
  asm("lop3.b32 %0, %1, %2, 1, 0xd8;" : "=r"(d) : "r"(w), "r"(t)); return d; }
static __device__ __forceinline__ uint32_t pack_m2(float lo, float hi, uint32_t t) { return tagw(pack_bf16(lo, hi), t); }
static __device__ __forceinline__ uint32_t pack_f16(float lo, float hi) { uint32_t d;
  asm("cvt.rn.satfinite.f16x2.f32 %0, %1, %2;" : "=r"(d) : "f"(hi), "f"(lo)); return d; }
static __device__ __forceinline__ void sum_h4(float& lo, float& hi, uint32_t a, uint32_t b, uint32_t c, uint32_t d) {
  const float2 x = __half22float2(*reinterpret_cast<__half2*>(&a)), y = __half22float2(*reinterpret_cast<__half2*>(&b));
  const float2 z = __half22float2(*reinterpret_cast<__half2*>(&c)), w = __half22float2(*reinterpret_cast<__half2*>(&d));
  lo = (x.x + y.x) + (z.x + w.x); hi = (x.y + y.y) + (z.y + w.y);
}
static __device__ __forceinline__ void add_q3(float& lo, float& hi, uint32_t a, uint32_t b, uint32_t c) {
  uint32_t t;
  asm("{\n.reg .b32 u;\nmul.rn.f16x2 u, %1, %4;\nfma.rn.f16x2 u, %2, %4, u;\nfma.rn.f16x2 %0, %3, %4, u;\n}" : "=r"(t) : "r"(a), "r"(b), "r"(c), "r"(0x34003400u));
  const float2 x = __half22float2(*reinterpret_cast<__half2*>(&t));
  lo += x.x; hi += x.y;
}
static __device__ __forceinline__ uint32_t lds32(uint32_t a) { uint32_t v; asm volatile("ld.shared.u32 %0, [%1];" : "=r"(v) : "r"(a) : "memory"); return v; }
static __device__ __forceinline__ uint32_t addb2(uint32_t a, uint32_t b) { uint32_t d;
  asm("add.rn.bf16x2 %0, %1, %2;" : "=r"(d) : "r"(a), "r"(b)); return d; }
static __device__ __forceinline__ uint32_t mulb2(uint32_t a, uint32_t b) { uint32_t d;
  asm("mul.rn.bf16x2 %0, %1, %2;" : "=r"(d) : "r"(a), "r"(b)); return d; }
static __device__ __forceinline__ uint32_t x3(uint32_t a, uint32_t b, uint32_t t) { uint32_t d;
  asm("lop3.b32 %0, %1, %2, %3, 0x7e;" : "=r"(d) : "r"(a), "r"(b), "r"(t)); return d; }
static __device__ __forceinline__ uint32_t or3(uint32_t a, uint32_t b, uint32_t c) { uint32_t d;
  asm("lop3.b32 %0, %1, %2, %3, 0xfe;" : "=r"(d) : "r"(a), "r"(b), "r"(c)); return d; }
static __device__ __forceinline__ uint32_t bad4(const uint4& u, uint32_t t) { return x3(u.x, u.y, t) | x3(u.z, u.w, t); }
static __device__ __forceinline__ uint32_t bad8(const uint4& u, const uint4& v, uint32_t t) {
  return or3(x3(u.x, u.y, t), x3(u.z, u.w, t), x3(v.x, v.y, t)) | x3(v.z, v.w, t); }
static __device__ __forceinline__ float ex2(float x) { float y; asm("ex2.approx.ftz.f32 %0, %1;" : "=f"(y) : "f"(x)); return y; }
static __device__ __forceinline__ float rcpf(float x) { float y; asm("rcp.approx.ftz.f32 %0, %1;" : "=f"(y) : "f"(x)); return y; }
static __device__ __forceinline__ void mbar_wait(uint32_t bar, int parity) {
  asm volatile("{\n.reg .pred p, q;\n.reg .u32 n;\nmbarrier.try_wait.parity.shared::cta.b64 p, [%0], %1;\n@p bra W_DONE;\nmov.u32 n, 0;\n"
               "W_LOOP:\nmbarrier.try_wait.parity.shared::cta.b64 p, [%0], %1;\nadd.u32 n, n, 1;\nsetp.lt.and.u32 q, n, %2, !p;\n@q bra W_LOOP;\nW_DONE:\n}"
               :: "r"(bar), "r"(parity), "n"(SPIN_LIMIT) : "memory");
}
static __device__ __forceinline__ uint32_t mbar_test(uint32_t bar, int parity) { uint32_t ok;
  asm volatile("{\n.reg .pred p;\nmbarrier.test_wait.parity.shared::cta.b64 p, [%1], %2;\nselp.u32 %0, 1, 0, p;\n}" : "=r"(ok) : "r"(bar), "r"(parity) : "memory"); return ok; }
static __device__ __forceinline__ void mbar_arrive(uint32_t bar) {
  asm volatile("mbarrier.arrive.shared::cta.b64 _, [%0];" :: "r"(bar) : "memory"); }
static __device__ __forceinline__ void mbar_arrive_cluster_rlx(uint32_t raddr) {
  asm volatile("mbarrier.arrive.relaxed.cluster.shared::cluster.b64 _, [%0];" :: "r"(raddr) : "memory"); }
static __device__ __forceinline__ void tma_load_mc(uint32_t dst, const CUtensorMap* tm, int c1, int c2, uint32_t bar) {
#ifdef NOTMA
  if ((NOTMA >> (c2 >> 3)) & 1) asm volatile("mbarrier.complete_tx.relaxed.cta.shared::cta.b64 [%0], 32768;" :: "r"(bar) : "memory"); else
#endif
  asm volatile("cp.async.bulk.tensor.3d.shared::cluster.global.mbarrier::complete_tx::bytes.multicast::cluster [%0], [%1, {%3, %4, %5}], [%2], %6;"
               :: "r"(dst), "l"(tm), "r"(bar), "r"(0), "r"(c1), "r"(c2), "h"((uint16_t)3) : "memory"); }
static __device__ __forceinline__ void cp16(uint32_t dst, const void* src) {
  asm volatile("cp.async.cg.shared.global [%0], [%1], 16;" :: "r"(dst), "l"(src) : "memory"); }
static __device__ __forceinline__ void mma_1688(float (&d)[4], uint32_t a0, uint32_t a1, uint32_t b0) {
  asm volatile("mma.sync.aligned.m16n8k8.row.col.f32.bf16.bf16.f32 {%0,%1,%2,%3}, {%4,%5}, {%6}, {%0,%1,%2,%3};"
               : "+f"(d[0]), "+f"(d[1]), "+f"(d[2]), "+f"(d[3]) : "r"(a0), "r"(a1), "r"(b0)); }
static __device__ __forceinline__ void mma4(float (&d)[4], uint32_t a0, uint32_t a1, uint32_t a2, uint32_t a3, uint32_t b0, uint32_t b1) {
  asm volatile("mma.sync.aligned.m16n8k16.row.col.f32.bf16.bf16.f32 {%0,%1,%2,%3}, {%4,%5,%6,%7}, {%8,%9}, {%0,%1,%2,%3};"
               : "+f"(d[0]), "+f"(d[1]), "+f"(d[2]), "+f"(d[3]) : "r"(a0), "r"(a1), "r"(a2), "r"(a3), "r"(b0), "r"(b1)); }
static __device__ __forceinline__ void mma4z(float (&d)[4], uint32_t a0, uint32_t a1, uint32_t a2, uint32_t a3, uint32_t b0, uint32_t b1) {
  asm volatile("mma.sync.aligned.m16n8k16.row.col.f32.bf16.bf16.f32 {%0,%1,%2,%3}, {%4,%5,%6,%7}, {%8,%9}, {%10,%10,%10,%10};"
               : "=f"(d[0]), "=f"(d[1]), "=f"(d[2]), "=f"(d[3]) : "r"(a0), "r"(a1), "r"(a2), "r"(a3), "r"(b0), "r"(b1), "f"(0.f)); }
static __device__ __forceinline__ void mma4h(float (&d)[4], uint32_t a0, uint32_t a1, uint32_t a2, uint32_t a3, uint32_t b) {
  asm volatile("mma.sync.aligned.m16n8k16.row.col.f32.f16.f16.f32 {%0,%1,%2,%3}, {%4,%5,%6,%7}, {%8,%8}, {%0,%1,%2,%3};"
               : "+f"(d[0]), "+f"(d[1]), "+f"(d[2]), "+f"(d[3]) : "r"(a0), "r"(a1), "r"(a2), "r"(a3), "r"(b)); }
static __device__ __forceinline__ void mma2h(float (&d)[4], uint32_t a0, uint32_t a1, uint32_t b) {
  asm volatile("mma.sync.aligned.m16n8k8.row.col.f32.f16.f16.f32 {%0,%1,%2,%3}, {%4,%5}, {%6}, {%0,%1,%2,%3};"
               : "+f"(d[0]), "+f"(d[1]), "+f"(d[2]), "+f"(d[3]) : "r"(a0), "r"(a1), "r"(b)); }
static __device__ __forceinline__ uint32_t clk32() { uint32_t t; asm volatile("mov.u32 %0, %%clock;" : "=r"(t)); return t; }
static __device__ __forceinline__ uint32_t gt32() { uint32_t t; asm volatile("mov.u32 %0, %%globaltimer_lo;" : "=r"(t)); return t; }
static __device__ __forceinline__ void spin(int clk) { if (clk > 0) { uint32_t t = clk32(); while (clk32() - t < (uint32_t)clk) {} } }
#define FENCE() asm volatile("griddepcontrol.launch_dependents;" ::: "memory")
#define OPAQUE_L(p) asm volatile("" : "+l"(p))
#define OPAQUE_R(p) asm volatile("" : "+r"(p))

template <int KK, int K1, int W0, int NW, int FIRST> struct XR {
  static __device__ __forceinline__ void run(float (&d)[16], const uint32_t (&w)[NW][4], uint32_t b16) {
#ifdef NOWG
    if (KK % NOWG == 0)
#endif
    wgmma_n32_ra<(KK >> 2) * 4096 + (KK & 3) * 32, !FIRST>(d, w[W0 + KK], b16);
    XR<KK + 1, K1, W0, NW, 0>::run(d, w, b16);
  }
};
template <int K1, int W0, int NW, int FIRST> struct XR<K1, K1, W0, NW, FIRST> { static __device__ __forceinline__ void run(float (&)[16], const uint32_t (&)[NW][4], uint32_t) {} };
template <int KK, int K0, int K1, int FIRST> struct XS {
  static __device__ __forceinline__ void run(float (&d)[16], uint32_t a16, uint32_t b16) {
#ifdef NOWG
    if (KK % NOWG == 0)
#endif
    wgmma_n32_ss_ta<(KK - K0) * 2048, (KK >> 2) * 4096 + (KK & 3) * 32, !FIRST>(d, a16, b16);
    XS<KK + 1, K0, K1, 0>::run(d, a16, b16);
  }
};
template <int K0, int K1, int FIRST> struct XS<K1, K0, K1, FIRST> { static __device__ __forceinline__ void run(float (&)[16], uint32_t, uint32_t) {} };

static __device__ bf16 g_h[8 * FF];
static __device__ unsigned int g_sbar;
struct SideParams { const bf16* x; const bf16* w_r; const bf16* w_gate; const bf16* w_up; const bf16* w_down; const bf16* gate_w; const bf16* Wo; };

static __device__ __forceinline__ void side_barrier(unsigned int target) {
  __syncthreads();
  if (threadIdx.x == 0) {
    __threadfence();
    atomicAdd(&g_sbar, 1u);
    int n = 0;
    while (*(volatile unsigned int*)&g_sbar < target) { if (++n > (1 << 22)) { g_err = 50; break; } }
    __threadfence();
  }
  __syncthreads();
}
static __device__ __forceinline__ uint4 ldg_nc(const void* p) { uint4 v;
  asm volatile("ld.global.nc.L1::no_allocate.v4.u32 {%0,%1,%2,%3}, [%4];" : "=r"(v.x), "=r"(v.y), "=r"(v.z), "=r"(v.w) : "l"(p)); return v; }
#ifndef SPD
#define SPD 3
#endif
static __device__ __forceinline__ void l2pf(const void* p) { asm volatile("prefetch.global.L2 [%0];" :: "l"(p)); }
static __device__ __forceinline__ void mm8(float (&acc)[8][4], const bf16* W, const bf16* Wn, int ldw, int nk16, uint32_t abase, int lane) {
  const int g = lane >> 2, t = lane & 3;
  const bf16* wp = W + (size_t)(2 * t) * ldw + g * 8;
#pragma unroll 1
  for (int k = 0; k < nk16; k += 4) {
    {
      const int kp = k + 4 * SPD;
      const bf16* pf = kp < nk16 ? W + (size_t)(kp * 16) * ldw : Wn ? Wn + (size_t)((kp - nk16) * 16) * ldw : nullptr;
      if (pf) { l2pf(pf + (size_t)lane * ldw); l2pf(pf + (size_t)(lane + 32) * ldw); }
    }
    uint4 r[4][4];
#pragma unroll
    for (int u = 0; u < 4; u++) {
      const bf16* q = wp + (size_t)(k + u) * 16 * ldw;
      r[u][0] = ldg_nc(q); r[u][1] = ldg_nc(q + ldw); r[u][2] = ldg_nc(q + 8 * ldw); r[u][3] = ldg_nc(q + 9 * ldw);
    }
#pragma unroll
    for (int u = 0; u < 4; u++) {
      uint32_t a0, a2;
      asm volatile("ld.shared.u32 %0, [%1];" : "=r"(a0) : "r"(abase + (k + u) * 32));
      asm volatile("ld.shared.u32 %0, [%1];" : "=r"(a2) : "r"(abase + (k + u) * 32 + 16));
      const uint32_t* p0 = reinterpret_cast<const uint32_t*>(&r[u][0]); const uint32_t* p1 = reinterpret_cast<const uint32_t*>(&r[u][1]);
      const uint32_t* p2 = reinterpret_cast<const uint32_t*>(&r[u][2]); const uint32_t* p3 = reinterpret_cast<const uint32_t*>(&r[u][3]);
#pragma unroll
      for (int i = 0; i < 8; i++) {
        const uint32_t sel = (i & 1) ? 0x7632u : 0x5410u;
        mma4(acc[i], a0, 0u, a2, 0u, __byte_perm(p0[i >> 1], p1[i >> 1], sel), __byte_perm(p2[i >> 1], p3[i >> 1], sel));
      }
    }
  }
}
static __device__ __noinline__ void side_work(const SideParams& P, unsigned char* smem, int q) {
  const int tid = threadIdx.x, lane = tid & 31, warp = tid >> 5, g = lane >> 2, t = lane & 3;
  const uint32_t sb = smem_u32(smem);
  unsigned int* cand = reinterpret_cast<unsigned int*>(smem);
  bf16* xs = reinterpret_cast<bf16*>(smem + 1024);
  float* part = reinterpret_cast<float*>(smem + 65536);
  {
    for (int i = tid; i < 256; i += 384) *reinterpret_cast<uint4*>(smem + 1024 + i * 16) = ldg_nc((i < 128 ? P.gate_w : P.w_r - DM) + i * 8);
    __syncthreads();
#pragma unroll 1
    for (int it = warp; it < 64; it += 12) {
      const bf16* xp = P.x + (size_t)(q * 512 + (it >> 1) * 16 + g) * DM + (it & 1) * 512 + t * 8;
      for (int a = it == warp ? 0 : 1; a < 2 && it + 12 * a < 64; a++)
#pragma unroll
        for (int i = 0; i < 4; i++) l2pf(P.x + (size_t)(q * 512 + (it >> 1) * 16 + a * 96 + i * 4 + (lane >> 3)) * DM + (it & 1) * 512 + (lane & 7) * 64);
      uint4 lo[16], hi[16];
#pragma unroll
      for (int i = 0; i < 16; i++) { lo[i] = ldg_nc(xp + i * 32); hi[i] = ldg_nc(xp + 8 * DM + i * 32); }
      float sg[4] = {0.f, 0.f, 0.f, 0.f}, sr[4] = {0.f, 0.f, 0.f, 0.f};
#pragma unroll
      for (int i = 0; i < 16; i++) {
        const uint4 gw = lds128(sb + 1024 + (it & 1) * 1024 + i * 64 + t * 16), wr = lds128(sb + 3072 + (it & 1) * 1024 + i * 64 + t * 16);
        mma4(sr, lo[i].x, hi[i].x, lo[i].y, hi[i].y, wr.x, wr.y); mma4(sr, lo[i].z, hi[i].z, lo[i].w, hi[i].w, wr.z, wr.w);
        mma4(sg, mulb2(lo[i].x, gw.x), mulb2(hi[i].x, gw.x), mulb2(lo[i].y, gw.y), mulb2(hi[i].y, gw.y), 0x3F803F80u, 0x3F803F80u);
        mma4(sg, mulb2(lo[i].z, gw.z), mulb2(hi[i].z, gw.z), mulb2(lo[i].w, gw.w), mulb2(hi[i].w, gw.w), 0x3F803F80u, 0x3F803F80u);
      }
      if (t == 0) {
        float* pp = part + (it & 1) * 1024 + (it >> 1) * 16 + g;
        pp[0] = sg[0]; pp[8] = sg[2]; pp[512] = sr[0]; pp[520] = sr[2];
      }
    }
    __syncthreads();
    for (int i = tid; i < 512; i += 384) {
      g_gate[q * 512 + i] = rbf(1.f / (1.f + expf(-rbf(part[i] + part[1024 + i]))));
      g_r[q * 512 + i] = rbf(part[512 + i] + part[1536 + i]);
    }
  }
#define GU(u) (((u) % 28) / 14 ? P.w_up : P.w_gate) + (size_t)((u) / 28) * 512 * FF + q * 896 + ((u) % 14) * 64
  for (int i = lane; i < 64 * SPD; i += 32) l2pf(GU(warp) + (size_t)i * FF);
  side_barrier(4);
  {
    unsigned int key[8];
#pragma unroll
    for (int i = 0; i < 8; i++) {
      const int tok = (warp & 7) * 256 + i * 32 + lane;
      const uint32_t b = __float_as_uint(__ldcg(&g_r[tok]) + 0.f) >> 16;
      key[i] = (((b & 0x8000u) ? (~b & 0xffffu) : (b | 0x8000u)) << 16) | (uint32_t)(2047 - tok);
    }
    for (int pass = 0; pass < 2; pass++) {
      if (pass == 0 ? warp < 8 : warp == 0) {
        for (int c = 0; c < 8; c++) {
          const unsigned int m = __reduce_max_sync(~0u, max(max(max(key[0], key[1]), max(key[2], key[3])), max(max(key[4], key[5]), max(key[6], key[7]))));
#pragma unroll
          for (int i = 0; i < 8; i++) if (key[i] == m) key[i] = 0u;
          if (lane == 0) cand[pass ? 128 + c : warp * 8 + c] = m;
        }
      }
      __syncthreads();
      if (pass == 0 && warp == 0) {
#pragma unroll
        for (int i = 0; i < 8; i++) key[i] = i < 2 ? cand[i * 32 + lane] : 0u;
      }
    }
    if (q == 0 && tid < 8) g_idx[tid] = 2047 - (int)(cand[128 + tid] & 0xffffu);
    for (int i = tid; i < 1024; i += 384) {
      const int c = i >> 7, tok = 2047 - (int)(cand[128 + c] & 0xffffu);
      *reinterpret_cast<uint4*>(xs + c * (FF + 8) + (i & 127) * 8) = ldg_nc(P.x + (size_t)tok * DM + (i & 127) * 8);
    }
    __syncthreads();
  }
#ifdef NOFFN
  return;
#endif
  const uint32_t abase = sb + 1024 + g * (FF + 8) * 2 + t * 4;
  for (int u = warp; u < 56; u += 12) {
    const int kh = u / 28, mat = (u % 28) / 14, cb = u % 14;
    float acc[8][4];
#pragma unroll
    for (int i = 0; i < 8; i++) acc[i][0] = acc[i][1] = acc[i][2] = acc[i][3] = 0.f;
    mm8(acc, GU(u), u + 12 < 56 ? GU(u + 12) : nullptr, FF, DM / 32, abase + kh * 1024, lane);
    float* pp = part + ((kh * 2 + mat) * 8 + g) * 896 + cb * 64 + 16 * t;
#pragma unroll
    for (int i = 0; i < 8; i++) { pp[i] = acc[i][0]; pp[8 + i] = acc[i][1]; }
  }
  for (int i = lane; i < 64 * SPD; i += 32) l2pf(P.w_down + (size_t)((warp >> 2) * 1216 + i) * DM + q * 256 + (warp & 3) * 64);
  __syncthreads();
  for (int i = tid; i < 8 * 896; i += 384) {
    const float ag = rbf(part[i] + part[16 * 896 + i]), au = rbf(part[8 * 896 + i] + part[24 * 896 + i]);
    g_h[(i / 896) * FF + q * 896 + i % 896] = __float2bfloat16(rbf(ag / (1.f + expf(-ag))) * au);
  }
  side_barrier(8);
  for (int i = tid; i < 8 * FF / 8; i += 384) {
    const int c = i / (FF / 8), o = i % (FF / 8);
    *reinterpret_cast<uint4*>(xs + c * (FF + 8) + o * 8) = __ldcg(reinterpret_cast<const uint4*>(g_h + c * FF + o * 8));
  }
  __syncthreads();
  {
    const int cb = warp & 3, kq = warp >> 2;
    float acc[8][4];
#pragma unroll
    for (int i = 0; i < 8; i++) acc[i][0] = acc[i][1] = acc[i][2] = acc[i][3] = 0.f;
    mm8(acc, P.w_down + (size_t)kq * 1216 * DM + q * 256 + cb * 64, nullptr, DM, kq == 2 ? 72 : 76, abase + kq * 1216 * 2, lane);
#pragma unroll
    for (int i = 0; i < 8; i++) { part[(kq * 8 + g) * 256 + cb * 64 + 16 * t + i] = acc[i][0]; part[(kq * 8 + g) * 256 + cb * 64 + 16 * t + 8 + i] = acc[i][1]; }
    __syncthreads();
    for (int i = tid; i < 2048; i += 384) {
      const int c = i >> 8, tok = 2047 - (int)(cand[128 + c] & 0xffffu);
      const float y = (part[i] + part[2048 + i]) + part[4096 + i];
      const float rs = rbf(1.f / (1.f + expf(-__ldcg(&g_r[tok]))));
      g_upd[c * DM + q * 256 + (i & 255)] = __float2bfloat16(rbf(y) * rs);
    }
  }
}
struct RecParams { const bf16* mem0; unsigned char* win; };
struct WMaps { CUtensorMap q, k, v; };
#ifndef RLX
#define RLX 1
#endif
#ifndef DLY_SIDE
#define DLY_SIDE 16000
#endif
#ifndef WSPL
#define WSPL 1
#endif

#ifndef DLY_S
#define DLY_S 270
#endif
#ifndef DLY_V
#define DLY_V 300
#endif
#ifndef DLY_M3
#define DLY_M3 560
#endif
#ifndef RF_FAT
#define RF_FAT 208
#endif
#ifndef RF_CTL
#define RF_CTL 88
#endif
#ifndef NCH
#define NCH 2
#endif
#ifndef WPF
#define WPF 7
#endif
#ifndef WRF
#define WRF 7
#endif
#ifndef VPF
#define VPF 2
#endif
#ifndef DLY_WO
#define DLY_WO 720
#endif
#ifndef XPF
#define XPF 4
#endif
#ifndef DLY_FA
#define DLY_FA 50
#endif
#ifndef DLY_XL
#define DLY_XL 400
#endif
#ifndef NPROBE
#define NPROBE 3
#endif
#ifndef O2P
#define O2P 2
#endif
#ifndef WS
#define WS 0
#endif
#ifndef NOB
#define NOB 2
#endif
#ifndef XG
#define XG 1
#endif
#ifndef VAL
#define VAL 0
#endif
#ifndef VE
#define VE 1
#endif
#ifndef PA
#define PA 1
#endif
#ifndef KU
#define KU 32
#endif
#ifndef KD
#define KD 4
#endif
#ifndef DLY_RR
#define DLY_RR 500
#endif
#ifndef GW
#define GW 0
#endif
#ifndef BI
#define BI 1
#endif
#ifndef BR
#define BR 8
#endif
#ifndef BG
#define BG 1
#endif
#ifndef VI
#define VI 1
#endif
#ifndef DLY_VI
#define DLY_VI 0
#endif
#ifndef F0W
#define F0W 0
#endif
#ifndef DLY_B
#define DLY_B 0
#endif
#ifndef BGT
#define BGT 0
#endif
#ifndef EG
#define EG 0
#endif
#ifndef W0I
#define W0I 0
#endif
#ifndef XH
#define XH 1
#endif
#ifndef F1L
#define F1L 1
#endif
#ifndef QB
#define QB 0
#endif
#ifndef LN
#define LN 0
#endif
#ifndef NSW
#define NSW 0
#endif
#ifndef EPI
#define EPI 0
#endif
#ifndef PXE
#define PXE 0
#endif
#ifndef GF
#define GF 12
#endif
#ifndef WNS
#define WNS -1
#endif
#ifndef DLY_NW
#define DLY_NW 0
#endif
#ifndef ETW
#define ETW 0
#endif
#ifndef KB
#define KB 8
#endif
#ifndef H16
#define H16 1
#endif
#ifndef DLY_N
#define DLY_N 0
#endif
#ifndef F1C
#define F1C 2
#endif
#ifndef KA
#define KA 0
#endif
#define KEEP() do { float kd[4]; mma4z(kd, 0u, 0u, 0u, 0u, 0u, 0u); } while (0)
#ifndef WKA
#define WKA 8
#endif
#ifndef WPA
#define WPA 4
#endif
#ifndef F0T
#define F0T 1
#endif
#ifndef DLY_K
#define DLY_K 1248
#endif
#ifndef DLY_KS
#define DLY_KS 850
#endif
#ifndef DLY_E
#define DLY_E 0
#endif
#ifndef DLY_PF
#define DLY_PF 10
#endif
#ifndef DLY_F0
#define DLY_F0 300
#endif
#ifndef DLY_XD
#define DLY_XD 200
#endif
#ifndef DLY_PX
#define DLY_PX 60
#endif
#ifndef DLY_TB
#define DLY_TB 700
#endif
#if 1
#define NTUNE 10
#define TUNE_NAMES {"OM3", "XL", "S", "NW", "WO", "PX", "V", "OK", "OKS", "ORR"}
__constant__ int g_tune[NTUNE] = {DLY_M3, DLY_XL, DLY_S, DLY_NW, DLY_WO, DLY_PX, DLY_V, DLY_K, DLY_KS, DLY_RR};
#undef DLY_M3
#define DLY_M3 g_tune[0]
#undef DLY_XL
#define DLY_XL g_tune[1]
#undef DLY_S
#define DLY_S g_tune[2]
#undef DLY_NW
#define DLY_NW g_tune[3]
#undef DLY_WO
#define DLY_WO g_tune[4]
#undef DLY_PX
#define DLY_PX g_tune[5]
#undef DLY_V
#define DLY_V g_tune[6]
#undef DLY_K
#define DLY_K g_tune[7]
#undef DLY_RR
#define DLY_RR g_tune[9]
#undef DLY_KS
#define DLY_KS g_tune[8]
#endif
#ifdef PROBE
__constant__ int g_probe[16];
#define PRB(i) spin(g_probe[i])
#else
#define PRB(i)
#endif
#ifdef PER
__device__ unsigned g_pclk[NCTA][64], g_per[NCTA][64], g_end[8] = {0, 0, 0, 0, 0, 0, 0, 100000};
#endif
#define ADD3(a, b, c) addb2(addb2(a, c), b)
#define STR2(x) #x
#define STR(x) STR2(x)

static __device__ __forceinline__ void cp16p(uint32_t dst, const void* src, uint32_t v) {
  asm volatile("{\n.reg .pred q;\nsetp.ne.u32 q, %2, 0;\n@q cp.async.cg.shared.global [%0], [%1], 16;\n}" :: "r"(dst), "l"(src), "r"(v) : "memory"); }
static __device__ __forceinline__ void red_bf2(void* p, uint32_t v) {
  asm volatile("red.relaxed.gpu.global.add.noftz.bf16x2 [%0], %1;" :: "l"(p), "r"(v) : "memory"); }
static __device__ __forceinline__ void red_bf2p(void* p, uint32_t v, uint32_t e) {
  asm volatile("{\n.reg .pred q;\nsetp.lt.u32 q, %2, 2;\n@q red.relaxed.gpu.global.add.noftz.bf16x2 [%0], %1;\n}" :: "l"(p), "r"(v), "r"(e) : "memory"); }
static __device__ __forceinline__ void red_bf2p4(void* p, uint32_t v, uint32_t e) {
  asm volatile("{\n.reg .pred q;\nsetp.lt.u32 q, %2, 4;\n@q red.relaxed.gpu.global.add.noftz.bf16x2 [%0], %1;\n}" :: "l"(p), "r"(v), "r"(e) : "memory"); }
static __device__ __forceinline__ void eta2(void* p, uint32_t t, uint32_t first, uint32_t l16) {
  asm volatile("{\n.reg .pred q;\nsetp.lt.u32 q, %3, 32;\n@q red.relaxed.gpu.global.max.u32 [%0+4], %1;\n@q red.relaxed.gpu.global.add.u32 [%0], %2;\n}" :: "l"(p), "r"(t), "r"(first), "r"(l16) : "memory"); }
static __device__ __forceinline__ void sts16(uint32_t a, uint32_t x) { asm volatile("{\n.reg .b16 h;\ncvt.u16.u32 h, %1;\nst.shared.u16 [%0], h;\n}" :: "r"(a), "r"(x) : "memory"); }
static __device__ __forceinline__ uint32_t cnt_word(uint32_t L) { return (L & 17u) | ((L & 6u) << 1) | ((L & 8u) >> 2); }
static __device__ __forceinline__ uint32_t cnt_line(uint32_t l) { return (l & 17u) | ((l & 12u) >> 1) | ((l & 2u) << 2); }
static __device__ __forceinline__ int m3_check(uint32_t sb, const unsigned char* p3, const unsigned char* pd, int dq, uint32_t l16, uint32_t mc, int hf, int s) {
  const uint32_t md = l16 + (sb + SM_MEM + hf * 8192), dd = l16 + (sb + SM_RD + hf * 256), dc = (l16 >> 2) + (sb + SM_RD + hf * 256);
  int n = 0;
  uint32_t c0 = 0, c1 = 0, d0 = 0, d1 = 0;
#pragma unroll 1
  do {
    if (n) {
      const int src = cnt_word(l16 >> 4);
      const uint32_t m0 = __ballot_sync(~0u, (__shfl_sync(~0u, c0, src) >> 16) != 0x4200u) >> (l16 >> 7), m1 = __ballot_sync(~0u, (__shfl_sync(~0u, c1, src) >> 16) != 0x4200u) >> (l16 >> 7);
      const uint32_t m2 = __ballot_sync(~0u, (d0 >> 16) != 0x4200u), m3 = __ballot_sync(~0u, (d1 >> 16) != 0x4200u);
#pragma unroll
      for (int i = 0; i < 8; i++) { cp16p(md + i * 512, p3 + i * 1024, m0 & (1u << (4 * i))); cp16p(md + 4096 + i * 512, p3 + dq + i * 1024, m1 & (1u << (4 * i))); }
      cp16p(dd, pd, l16 < 256u ? (((l16 & 128u) ? m3 : m2) >> ((l16 >> 2) & 28u)) & 15u : 0u);
      sts32(sb + SM_Z + 40, s);
      asm volatile("cp.async.commit_group;\ncp.async.wait_group 0;" ::: "memory");
      __syncwarp();
    }
    n++;
    mbar_wait(sb + SM_BAR + MB_G + hf * 8, s & 1);
    c0 = lds32(mc); c1 = lds32(mc + 4096); d0 = lds32(dc); d1 = lds32(dc + 128);
  } while (__any_sync(~0u, (x3(c0, c1, 0x42000000u) | x3(d0, d1, 0x42000000u)) >= 0x10000u) && n < SPIN_LIMIT);
  PRB(4);
  sts16(mc + 2, d0); sts16(mc + 4098, d1);
  mbar_arrive(sb + SM_BAR + MB_MEM + hf * 8);
  return n - 1;
}

__global__ void __cluster_dims__(2, 1, 1) __launch_bounds__(384, 1)
rec_kernel(const __grid_constant__ CUtensorMap tmx, const __grid_constant__ CUtensorMap tmw, const __grid_constant__ WMaps W, RecParams P, const __grid_constant__ SideParams SP) {
  extern __shared__ __align__(1024) unsigned char smem[];
  asm volatile("griddepcontrol.launch_dependents;");
  const uint32_t sb = smem_u32(smem);
  const int tid = threadIdx.x, lane = tid & 31, t128 = tid & 127;
  const int wg = __shfl_sync(~0u, tid >> 7, 0), wq = __shfl_sync(~0u, (tid >> 5) & 3, 0);
  const int r = blockIdx.x & 1, pp = blockIdx.x >> 1;
  const int mi = lane >> 3, r8 = lane & 7;
  const uint32_t xb16 = __shfl_sync(~0u, (((sb + SM_X + (tid >> 7) * 32768 + r * 16384) & 0x3FFFF) >> 4) | (1u << 16), 0);
  const uint32_t va16 = __shfl_sync(~0u, (((sb + SM_WVS + (tid >> 7) * 16384) & 0x3FFFF) >> 4) | (64u << 16), 0);
#ifdef PER
  const uint32_t tstart = gt32();
#endif

  if (tid == 0) {
    mbar_init(sb + SM_BAR + MB_F, BGT == 2 ? 8 : BGT == 1 ? 4 : 1); mbar_init(sb + SM_BAR + MB_F + 8, 1); mbar_init(sb + SM_BAR + MB_XE0, 2); mbar_init(sb + SM_BAR + MB_XE1, 2); mbar_init(sb + SM_BAR + MB_INIT, 2);
    mbar_init(sb + SM_BAR + MB_MEM, 32); mbar_init(sb + SM_BAR + MB_MEM + 8, 32); mbar_init(sb + SM_BAR + MB_W, 1); mbar_init(sb + SM_BAR + MB_W + 8, 1);
    mbar_init(sb + SM_BAR + MB_XF, 8); mbar_init(sb + SM_BAR + MB_X0, 1); mbar_init(sb + SM_BAR + MB_WO, 1); mbar_init(sb + SM_BAR + MB_VR, 5); mbar_init(sb + SM_BAR + MB_G, 32); mbar_init(sb + SM_BAR + MB_G + 8, 32);
    sts32(sb + SM_Z + 40, ~0u);
    asm volatile("fence.mbarrier_init.release.cluster;" ::: "memory");
  }
  if (tid >= 64 && tid < 96) {
    const uint32_t l16 = lane * 16, qa = ((l16 & 0x30u) << 3) | ((l16 & 0x10u) << 2) | ((l16 >> 3) & 0x30u) | ((l16 >> 4) & 4u);
    sts128(sb + SM_QA + l16, qa + (sb + SM_QKP), (qa ^ 64u) + (sb + SM_QKP), 0u, 0u);
  }
  if (tid == 32) {
    asm volatile("prefetch.tensormap [%0];" :: "l"(&W.q) : "memory"); asm volatile("prefetch.tensormap [%0];" :: "l"(&W.k) : "memory");
    asm volatile("prefetch.tensormap [%0];" :: "l"(&W.v) : "memory"); asm volatile("prefetch.tensormap [%0];" :: "l"(&tmx) : "memory");
  }
  if (tid >= 256 && tid < 320) {
    unsigned char* pl = P.win + r * W_2 + (W_UP | (1u << 19) | ((pp >> 5) << 14)) + (pp & 31) * 128 + wq * 4096;
    stg_r1(pl + lane * 4, 0u);
    uint32_t best = 1u << 30, acc = 0;
#pragma unroll 1
    for (int rep = 0; rep < NPROBE; rep++) {
      uint32_t v = 0, t1; const uint32_t t0 = clk32();
      if (lane == 0) asm volatile("atom.relaxed.gpu.global.add.u32 %0, [%1], 2;" : "=r"(v) : "l"(pl + acc) : "memory");
      acc = v >> 31;
      asm volatile("{\n.reg .u32 x;\nadd.u32 x, %1, 0;\nmov.u32 %0, %%clock;\n}" : "=r"(t1) : "r"(acc));
      best = min(best, t1 - t0 + acc);
    }
    if (lane == 0) sts32(sb + SM_SIDE + wq * 4, best);
    bar_sync(B_P, 64);
    if (wq == 0) {
      const uint2 bt = lds64(sb + SM_SIDE);
      if (lane < 8 && (r == 0 || pp == 0)) stg_r1(&g_side[(r ? 66 : pp) * 32 + lane], 2u | (bt.x < bt.y ? 1u : 0u));
      spin(DLY_TB);
      uint32_t a, b, c; int n = 0;
#pragma unroll 1
      do {
        a = ldg_r1(&g_side[lane * 32]); b = ldg_r1(&g_side[(32 + lane) * 32]); c = ldg_r1(&g_side[(64 + min(lane, 2)) * 32]);
      } while (!__all_sync(~0u, a & b & c & 2u) && ++n < SPIN_LIMIT);
      a = __ballot_sync(~0u, a & 1u); b = __ballot_sync(~0u, b & 1u); c = __ballot_sync(~0u, c & 1u);
      const uint32_t pol2 = (a ^ (c >> 2)) & 1u;
      c &= 3u;
      const unsigned long long ab = ((unsigned long long)b << 32) | a;
      const int sd = pp < 64 ? (int)(ab >> pp) & 1 : (int)(c >> (pp - 64)) & 1;
      const int n1 = __popcll(ab) + __popc(c), n0 = 66 - n1;
      const int below1 = pp < 64 ? __popcll(ab & ((1ull << pp) - 1)) : __popcll(ab) + (pp == 65 ? (int)(c & 1u) : 0);
      const int rk = sd ? below1 : pp - below1;
      const int k0 = (n0 & 1) ? n0 - 1 : n0 >= n1 ? n0 - 2 : n0, k1 = 64 - k0;
      const int role = rk >= (sd ? k1 : k0) ? 64 + ((n0 & 1) ? sd : rk - (sd ? k1 : k0)) : sd ? k0 + rk : rk;
      __syncwarp();
      if (lane == 0) sts128(sb + SM_SIDE, 2 * k0, 0u, pol2, role * 2 + r);
#ifdef PER
      if (lane == 0) { atomicMax(&g_end[6], gt32()); atomicMin(&g_end[7], max(bt.x, bt.y) - min(bt.x, bt.y)); }
#endif
    }
  }
  __syncthreads();
  const int cta = __shfl_sync(~0u, (int)lds32(sb + SM_SIDE + 12), 0), h = cta >> 2, j = cta & 3, p = j >> 1;
  const int sw = (cta >= __shfl_sync(~0u, (int)lds32(sb + SM_SIDE), 0) ? 1 : 0) ^ r ^ NSW;
  if (cta >= NCTA) {
    spin(DLY_SIDE);
#ifndef NOSIDE
    side_work(SP, smem, cta - NCTA);
#endif
#ifdef PER
    if (threadIdx.x == 0) atomicMax(&g_end[1], gt32());
#endif
    return;
  }
#ifdef PER
  if (threadIdx.x == 0) g_per[cta][63] = tstart;
#endif
  asm volatile("barrier.cluster.arrive.relaxed.aligned;" ::: "memory");
#define WLOAD(i0, i1) _Pragma("unroll 1") for (int u = i0; u < i1; u++) {        \
    const int g2 = u >> 2, i = u & 3, k = g2 * 512 + ((i * 128 + r * 256) & 511); \
    const uint32_t mb = sb + SM_BAR + MB_W + g2 * 8; \
    tma_load_2d(sb + g2 * 65536 + i * 8192, &W.q, h * DH + j * 32, k, mb); \
    tma_load_2d(sb + g2 * 65536 + 32768 + i * 8192, &W.k, h * DH + j * 32, k, mb); \
    if (i < 2) tma_load_2d(sb + (i ? SM_WVS : SM_VST) + g2 * 16384, &W.v, h * DH + p * 64, k, mb); }
  if (tid == 288) {
    mbar_expect_tx(sb + SM_BAR + MB_X0, 32768);
#pragma unroll 1
    for (int i = 0; i < 2; i++)
      asm volatile("cp.async.bulk.tensor.3d.shared::cluster.global.mbarrier::complete_tx::bytes [%0], [%1, {%3, %3, %4}], [%2];"
                   :: "r"(sb + SM_MEM + i * 16384), "l"(&tmx), "r"(sb + SM_BAR + MB_X0), "r"(0), "r"(i * 4) : "memory");
    mbar_expect_tx(sb + SM_BAR + MB_W, 98304); mbar_expect_tx(sb + SM_BAR + MB_W + 8, 98304);
    WLOAD(0, 4 + WSPL);
  }
  __syncwarp();
  asm volatile("barrier.cluster.wait.acquire.aligned;" ::: "memory");
#define SIDES() const uint4 sm2 = lds128(sb + SM_SIDE); const int nlo = sm2.x; const uint32_t me = cta >= nlo

#define XLOAD(t, sg) tma_load_mc(sb + SM_X + ((t) * 8 + r * 4) * 4096, &tmx, (sg) * SEG, (t) * 8 + r * 4, sb + SM_BAR + MB_F + (t) * 8)
#define F0LOAD() do { mbar_wait(sb + SM_BAR + MB_XE0, s & 1); \
    if (l16 == 0) XLOAD(0, s + 2); \
    __syncwarp(); } while (0)
  if (wg < 2) {
    asm volatile("setmaxnreg.inc.sync.aligned.u32 " STR(RF_FAT) ";");
    uint32_t w[32][4], wv[8][4];
    uint32_t lm = ((mi >> 1) * 8 + r8) * 128 + (((wq * 2 + (mi & 1)) ^ r8) << 4), l16 = lane * 16;
    lm = __shfl_sync(~0u, lm, lane); l16 = __shfl_sync(~0u, l16, lane);
    mbar_wait(sb + SM_BAR + MB_W + wg * 8, 0);
    {
      const uint32_t lq0 = sb + wg * 65536 + (wq >> 1) * 32768 + ((mi >> 1) * 8 + r8) * 64 + ((((wq & 1) * 2 + (mi & 1)) ^ (r8 >> 1)) << 4);
#pragma unroll
      for (int kk = 0; kk < 32; kk++) ldmatrix_x4_trans(w[kk], lq0 + kk * 1024);
      const uint32_t f = wq < 2 ? 0x3D003D00u : 0x3F803F80u;
#pragma unroll
      for (int kk = 0; kk < 128; kk++) w[kk >> 2][kk & 3] = mulb2(w[kk >> 2][kk & 3], f);
    }
#pragma unroll
    for (int kk = 0; kk < 8; kk++) ldmatrix_x4_trans(wv[kk], sb + SM_VST + wg * 16384 + kk * 2048 + lm);
    if (wg == 0) bar_sync(B_V, 160);
    else bar_arrive(B_P, 224);
    const int w8 = wg * 4 + wq;
    const int cw = sw ^ wg, near = wg ^ 1 ^ NSW;
    const uint32_t xh16 = xb16 ^ 1024u;
    const uint32_t rsb = mapa(sb, r ^ 1);
#define MT (l16 + (sb + SM_MEM + wg * 8192))
#define WA (lm + (sb + SM_WVS + wg * 16384))
#if WS
#define WOF(f) (lm + (sb + SM_WOS + wg * 32768 + (f) * 2048))
#else
#define WOF(f) (lm + (sb + SM_WOS + wg * 32768 + ((f) & 1) * 16384 + ((f) >> 1) * 2048))
#endif
#define TH(base) (l16 + (sb + (base) + w8 * 512))
#define TQ(base) (l16 + (sb + (base) + wq * 512))
#define DUMP(base) _Pragma("unroll") for (int n = 0; n < 4; n++) sts128f(TQ((base) + n * 2048), d[4 * n], d[4 * n + 1], d[4 * n + 2], d[4 * n + 3])
#define INIT(base) _Pragma("unroll") for (int n = 0; n < 4; n++) { const float4 t = lds128f(TQ((base) + n * 2048)); d[4 * n] = t.x; d[4 * n + 1] = t.y; d[4 * n + 2] = t.z; d[4 * n + 3] = t.w; }
#define XQK(first, b0, b1) do { wg_fence(); XR<0, 16, 0, 32, first>::run(d, w, b0); XR<0, 16, 16, 32, 0>::run(d, w, b1); wg_commit(); wg_wait0(); } while (0)
#define XVS(first, b0) do { wg_fence(); XS<8, 8, 16, first>::run(d, va16, b0); XR<0, 8, 0, 8, 0>::run(d, wv, b0); wg_commit(); wg_wait0(); } while (0)
#define XVR(first, b0) do { wg_fence(); XR<0, 8, 0, 8, first>::run(d, wv, b0); XS<8, 8, 16, 0>::run(d, va16, b0); wg_commit(); wg_wait0(); } while (0)
#define XREL(mb) do { if (wq == 0 && l16 == 0) { mbar_arrive_cluster_rlx(rsb + SM_BAR + (mb)); mbar_arrive(sb + SM_BAR + (mb)); } } while (0)
#define XFOUT() do { \
          _Pragma("unroll") for (int hf = 0; hf < 2; hf++) \
            stsm4t(l16 + (sb + SM_XF + (wq * 2 + hf) * 512), pack_bf16(d[8 * hf], d[8 * hf + 1]), pack_bf16(d[8 * hf + 2], d[8 * hf + 3]), \
                   pack_bf16(d[8 * hf + 4], d[8 * hf + 5]), pack_bf16(d[8 * hf + 6], d[8 * hf + 7])); \
          __syncwarp(); \
          if (l16 < 32) mbar_arrive(sb + SM_BAR + MB_XF); } while (0)
#define VDUMP(base) _Pragma("unroll") for (int n = 0; n < 2; n++) sts128(TQ((base) + n * 2048), pack_bf16(d[8 * n], d[8 * n + 1]), pack_bf16(d[8 * n + 2], d[8 * n + 3]), pack_bf16(d[8 * n + 4], d[8 * n + 5]), pack_bf16(d[8 * n + 6], d[8 * n + 7]))
#define ADDIN(base) _Pragma("unroll") for (int n = 0; n < 4; n++) { const float4 t = lds128f(TQ((base) + n * 2048)); d[4 * n] += t.x; d[4 * n + 1] += t.y; d[4 * n + 2] += t.z; d[4 * n + 3] += t.w; }
    if (wg == 0) {
      float d[16];
      const uint32_t x0 = (((sb + SM_MEM + r * 16384) & 0x3FFFF) >> 4) | (1u << 16), x1 = (((sb + SM_MEM + (r ^ 1) * 16384) & 0x3FFFF) >> 4) | (1u << 16);
      mbar_wait(sb + SM_BAR + MB_X0, 0);
      XQK(1, x0, x1);
      DUMP(SM_CQ);
      XVS(1, x0);
      VDUMP(SM_CV);
      bar_sync(B_CQ, 256);
      bar_sync(B_X2, 384);
    } else {
      float d[16];
      bar_sync(B_CQ, 256);
      INIT(SM_CQ);
      bar_sync(B_X2, 384);
      mbar_wait(sb + SM_BAR + MB_F + 8, 0);
      XQK(0, xb16, xh16);
      XFOUT();
    }
    if (wg == 0) mbar_wait(sb + SM_BAR + MB_F, 0);
    for (int s = -1;; s++) {
      if (s >= 0) {
        OPAQUE_R(lm); OPAQUE_R(l16);
        {
          uint32_t sa[4][4];
#pragma unroll
          for (int i = 0; i < VPF; i++) ldmatrix_x4_trans(sa[i], WA + i * 2048);
          float a[2][4], v[2][4]; uint4 c[4]; uint2 qa;
          FENCE();
          mbar_wait(sb + SM_BAR + MB_MEM + wg * 8, s & 1);
#define QP(i) ((i) >= 12 ? (i) - 8 : (i) % 3 == 1 ? (i) / 3 : 8 + (i) - ((i) + 2) / 3)
#pragma unroll
          for (int i = 0; i < 3; i++) c[i] = ldsm4t(MT + QP(i) * 512);
#pragma unroll
          for (int i = 0; i < 16; i++) {
            if (i + 3 < 16) c[(i + 3) & 3] = ldsm4t(MT + QP(i + 3) * 512);
            if (i == 13) qa = lds64(l16 + (sb + SM_QA));
            if (i == 0) {
              mma4z(a[0], w[2 * QP(i)][0], w[2 * QP(i)][1], w[2 * QP(i)][2], w[2 * QP(i)][3], c[i & 3].x, c[i & 3].y);
              mma4z(a[1], w[2 * QP(i) + 1][0], w[2 * QP(i) + 1][1], w[2 * QP(i) + 1][2], w[2 * QP(i) + 1][3], c[i & 3].z, c[i & 3].w);
            } else {
              mma_16816(a[0], w[2 * QP(i)], c[i & 3].x, c[i & 3].y);
              mma_16816(a[1], w[2 * QP(i) + 1], c[i & 3].z, c[i & 3].w);
            }
            if (QP(i) == 0) {
              mma4z(v[0], wv[0][0], wv[0][1], wv[0][2], wv[0][3], c[i & 3].x, c[i & 3].y);
              mma4z(v[1], wv[1][0], wv[1][1], wv[1][2], wv[1][3], c[i & 3].z, c[i & 3].w);
            } else if (QP(i) < 4) {
              mma_16816(v[0], wv[2 * (QP(i) & 3)], c[i & 3].x, c[i & 3].y);
              mma_16816(v[1], wv[2 * (QP(i) & 3) + 1], c[i & 3].z, c[i & 3].w);
            }
            if (VE && i == 12) {
              mma_16816(v[0], sa[0], c[0].x, c[0].y); mma_16816(v[1], sa[1], c[0].z, c[0].w);
            }
            if (VE && i == 13) { ldmatrix_x4_trans(sa[0], WA + 2 * 2048); ldmatrix_x4_trans(sa[1], WA + 3 * 2048); ldmatrix_x4_trans(sa[2], WA + 4 * 2048); }
            FENCE();
          }
#pragma unroll
          for (int i = 0; i < 4; i++) sts32(((i & 1) ? qa.y : qa.x) + (w8 * 512 + (i >> 1) * 8), f2u(a[0][i] + a[1][i]));
          bar_arrive(B_QK, 288);
          bar_arrive(B_QK1, 288);
          FENCE();
#if VE
          uint32_t sc2[4];
          ldmatrix_x4_trans(sa[3], WA + 5 * 2048); ldmatrix_x4_trans(sc2, WA + 6 * 2048);
          mma_16816(v[0], sa[0], c[1].x, c[1].y); mma_16816(v[1], sa[1], c[1].z, c[1].w);
          FENCE();
          ldmatrix_x4_trans(sa[0], WA + 7 * 2048);
          FENCE();
          mma_16816(v[0], sa[2], c[2].x, c[2].y); mma_16816(v[1], sa[3], c[2].z, c[2].w);
          mma_16816(v[0], sc2, c[3].x, c[3].y); mma_16816(v[1], sa[0], c[3].z, c[3].w);
          FENCE();
#else
#pragma unroll
          for (int i = VPF; i < 4; i++) ldmatrix_x4_trans(sa[i], WA + i * 2048);
          FENCE();
#pragma unroll
          for (int i = 0; i < 4; i++) {
            mma_16816(v[0], sa[(2 * i) & 3], c[i].x, c[i].y);
            mma_16816(v[1], sa[(2 * i + 1) & 3], c[i].z, c[i].w);
            if (i < 2) { ldmatrix_x4_trans(sa[2 * i], WA + (4 + 2 * i) * 2048); ldmatrix_x4_trans(sa[2 * i + 1], WA + (5 + 2 * i) * 2048); }
            FENCE();
          }
#endif
          sts128f(TH(SM_VP), v[0][0] + v[1][0], v[0][1] + v[1][1], v[0][2] + v[1][2], v[0][3] + v[1][3]);
          bar_arrive(B_V, 320);
        }
        if (s == NSEG - 1) break;
        OPAQUE_R(lm); OPAQUE_R(l16);
        uint32_t wo[WPF][4];
        {
          float d[16];
#define XOUT(g) _Pragma("unroll") for (int n = 0; n < 2; n++) sts128f(TQ(SM_CQ + ((g) * 2 + n) * 2048), d[8 - 8 * (g) + 4 * n], d[9 - 8 * (g) + 4 * n], d[10 - 8 * (g) + 4 * n], d[11 - 8 * (g) + 4 * n])
#define XIN(g) do { \
            const float4 t0 = lds128f(TQ(SM_CQ + (2 - 2 * (g)) * 2048)), t1 = lds128f(TQ(SM_CQ + (3 - 2 * (g)) * 2048)); \
            stsm4t(l16 + (sb + SM_XF + (wq * 2 + (g)) * 512), pack_bf16(d[8 * (g)] + t0.x, d[8 * (g) + 1] + t0.y), pack_bf16(d[8 * (g) + 2] + t0.z, d[8 * (g) + 3] + t0.w), \
                   pack_bf16(d[8 * (g) + 4] + t1.x, d[8 * (g) + 5] + t1.y), pack_bf16(d[8 * (g) + 6] + t1.z, d[8 * (g) + 7] + t1.w)); } while (0)
          if (wg == 0) {
            INIT(SM_CW);
            bar_sync(B_PUB, 320);
            wg_fence();
            XR<KB, 16, 0, 32, 0>::run(d, w, xb16); XR<0, 16, 16, 32, 0>::run(d, w, xh16);
            wg_commit(); wg_wait0();
            TSF(13, 1);
            OPAQUE_R(l16);
            XOUT(0);
            bar_arrive(B_G1, 256);
            XREL(MB_XE0);
#pragma unroll
            for (int f = 0; f < WPA; f++) ldmatrix_x4_trans(wo[f], WOF(f));
            bar_sync(B_CQ, 256);
            XIN(0);
          } else {
            const uint32_t ok = mbar_test(sb + SM_BAR + MB_F + 8, (s + 1) & 1);
            bar_sync(B_PUB, 320);
            if (!ok) mbar_wait(sb + SM_BAR + MB_F + 8, (s + 1) & 1);
            wg_fence();
            XR<0, 16, 0, 32, 1>::run(d, w, xb16); XR<0, 16, 16, 32, 0>::run(d, w, xh16);
            wg_commit();
#pragma unroll
            for (int f = 0; f < WPA; f++) ldmatrix_x4_trans(wo[f], WOF(f));
            wg_wait0();
            TSF(31, 5);
            OPAQUE_R(l16);
            XOUT(1);
            bar_arrive(B_CQ, 256);
            bar_sync(B_G1, 256);
            XIN(1);
          }
          __syncwarp();
          if (l16 == 0) mbar_arrive(sb + SM_BAR + MB_XF);
          TSF(3, 5);
        }
#pragma unroll
        for (int f = WPA; f < WPF; f++) ldmatrix_x4_trans(wo[f], WOF(f));
        unsigned char* pa = P.win + (w_ar(s) + (j * 32 + cw * 16 + wq * 2) * 256 + (l16 >> 2));
        uint32_t ce = (l16 >> 4) - 4 * (cw * 4 + wq);
        OPAQUE_L(pa); OPAQUE_R(ce);
        FENCE();
        bar_sync(wg ? B_O : B_O2, XG && !wg ? 224 : 192);
#if WS
        uint4 ob[NOB];
#pragma unroll
        for (int i = 0; i < NOB; i++) ob[i] = ldsm4(l16 + (sb + SM_OF + i * 512));
        float acc[2][4], dv; uint32_t f0ok;
#pragma unroll
        for (int f = 0; f < 16; f++) {
          const int ks = f & 7;
          const uint32_t b0 = (ks & 1) ? ob[(f >> 1) % NOB].z : ob[(f >> 1) % NOB].x, b1 = (ks & 1) ? ob[(f >> 1) % NOB].w : ob[(f >> 1) % NOB].y;
          const uint32_t (&a)[4] = wo[f < WPF ? f : 2 + (f - WPF) % (WPF - 2)];
          if (f == 8) {
            const float x0 = acc[0][0] + acc[1][0], x1 = acc[0][1] + acc[1][1], x2 = acc[0][2] + acc[1][2], x3_ = acc[0][3] + acc[1][3];
            red_bf2(pa, pack_bf16(x0, ce == 0 ? 1.f : x1)); red_bf2(pa + 256, pack_bf16(x2, ce == 1 ? 1.f : x3_));
            dv = ce == 0 ? x1 : x3_;
          }
          if (ks < 2) mma4z(acc[ks], a[0], a[1], a[2], a[3], b0, b1);
          else mma_16816(acc[ks & 1], a, b0, b1);
          if (NOB < 4 && (f & 1) == 0 && f >= 2 && (f >> 1) - 1 + NOB < 8) ob[((f >> 1) - 1) % NOB] = ldsm4(l16 + (sb + SM_OF + (((f >> 1) - 1 + NOB) & 3) * 512));
          if (f - 1 >= 2 && f - 1 + (WPF - 2) < 16) {
            const int nf = f - 1 + (WPF - 2);
            ldmatrix_x4_trans(wo[2 + (nf - WPF) % (WPF - 2)], WOF(nf));
          }
          if (f == GF) f0ok = mbar_test(sb + SM_BAR + MB_F, (s + 1) & 1);
          if (f < 15) FENCE();
        }
        if (!wg) bar_arrive(B_CV, 256);
        {
          const float x0 = acc[0][0] + acc[1][0], x1 = acc[0][1] + acc[1][1], x2 = acc[0][2] + acc[1][2], x3_ = acc[0][3] + acc[1][3];
          red_bf2(pa + 2048, pack_bf16(x0, ce == 2 ? 1.f : x1)); red_bf2(pa + 2304, pack_bf16(x2, ce == 3 ? 1.f : x3_));
          red_bf2p4(pa + (W_DS + (wq & 1) * 256), pack_bf16(ce == 2 ? x1 : ce == 3 ? x3_ : dv, 1.f), ce);
        }
#else
        uint4 ob[2];
        ob[0] = ldsm4(l16 + (sb + SM_OF)); ob[1] = ldsm4(l16 + (sb + SM_OF + 512));
        float acc[2][4]; uint32_t f0ok;
#pragma unroll
        for (int f = 0; f < 16; f++) {
          const int ks = f >> 1;
          const uint32_t b0 = (ks & 1) ? ob[(ks >> 1) & 1].z : ob[(ks >> 1) & 1].x, b1 = (ks & 1) ? ob[(ks >> 1) & 1].w : ob[(ks >> 1) & 1].y;
          if (f < 2) mma4z(acc[f], wo[f][0], wo[f][1], wo[f][2], wo[f][3], b0, b1);
          else mma_16816(acc[f % 2], wo[f < WPF ? f : 2 + (f - WPF) % (WPF - 2)], b0, b1);
          if (f - 1 >= 2 && f - 1 + (WPF - 2) < 16) {
            const int nf = f - 1 + (WPF - 2);
            ldmatrix_x4_trans(wo[2 + (nf - WPF) % (WPF - 2)], WOF(nf));
          }
          if (f == 4 || f == 8) ob[((f >> 2) - 1) & 1] = ldsm4(l16 + (sb + SM_OF + (1 + (f >> 2)) * 512));
          if (f == GF) f0ok = mbar_test(sb + SM_BAR + MB_F, (s + 1) & 1);
          if (f < 15) FENCE();
        }
        if (!wg) bar_arrive(B_CV, 256);
        red_bf2(pa, pack_bf16(acc[0][0], ce == 0 ? 1.f : acc[0][1])); red_bf2(pa + 256, pack_bf16(acc[0][2], ce == 1 ? 1.f : acc[0][3]));
        red_bf2(pa + 2048, pack_bf16(acc[1][0], ce == 2 ? 1.f : acc[1][1])); red_bf2(pa + 2304, pack_bf16(acc[1][2], ce == 3 ? 1.f : acc[1][3]));
        red_bf2p4(pa + (W_DS + (wq & 1) * 256), pack_bf16(ce == 0 ? acc[0][1] : ce == 1 ? acc[0][3] : ce == 2 ? acc[1][1] : acc[1][3], 1.f), ce);
#endif
        TSF(4, 1); TSF(2, 6);
        if (wg) bar_sync(B_CV, 256);
        else if (!f0ok) mbar_wait(sb + SM_BAR + MB_F, (s + 1) & 1);
      }
      OPAQUE_R(lm); OPAQUE_R(l16);
      {
        float d[16];
        const uint32_t cv = TQ(SM_CV + ((s ^ wg) & 1) * 4096);
        TSF(9, 1);
#if BI == 1
        wg_fence();
        XR<0, 1, 0, 8, 1>::run(d, wv, xb16); XS<8, 8, 9, 0>::run(d, va16, xb16); XR<1, 2, 0, 8, 0>::run(d, wv, xb16); XS<9, 8, 10, 0>::run(d, va16, xb16);
        XR<2, 3, 0, 8, 0>::run(d, wv, xb16); XS<10, 8, 11, 0>::run(d, va16, xb16); XR<3, 4, 0, 8, 0>::run(d, wv, xb16); XS<11, 8, 12, 0>::run(d, va16, xb16);
        XR<4, 5, 0, 8, 0>::run(d, wv, xb16); XS<12, 8, 13, 0>::run(d, va16, xb16); XR<5, 6, 0, 8, 0>::run(d, wv, xb16); XS<13, 8, 14, 0>::run(d, va16, xb16);
        XR<6, 7, 0, 8, 0>::run(d, wv, xb16); XS<14, 8, 15, 0>::run(d, va16, xb16); XR<7, 8, 0, 8, 0>::run(d, wv, xb16); XS<15, 8, 16, 0>::run(d, va16, xb16);
        wg_commit(); wg_wait0();
#elif BI == 3
        wg_fence(); XR<0, 8, 0, 8, 1>::run(d, wv, xb16); XR<8, 16, -8, 8, 0>::run(d, wv, xb16); wg_commit(); wg_wait0();
#elif BI == 6
        {
          uint32_t sv[2][4];
          ldmatrix_x4_trans(sv[0], WA); ldmatrix_x4_trans(sv[1], WA + 2048);
          wg_fence(); XR<0, 2, 0, 8, 1>::run(d, wv, xb16); wg_commit();
          wg_fence(); XR<8, 10, -8, 2, 0>::run(d, sv, xb16); wg_commit(); XR<2, 4, 0, 8, 0>::run(d, wv, xb16); wg_commit(); wg_wait1();
          ldmatrix_x4_trans(sv[0], WA + 2 * 2048); ldmatrix_x4_trans(sv[1], WA + 3 * 2048);
          wg_fence(); XR<10, 12, -10, 2, 0>::run(d, sv, xb16); wg_commit(); XR<4, 6, 0, 8, 0>::run(d, wv, xb16); wg_commit(); wg_wait1();
          ldmatrix_x4_trans(sv[0], WA + 4 * 2048); ldmatrix_x4_trans(sv[1], WA + 5 * 2048);
          wg_fence(); XR<12, 14, -12, 2, 0>::run(d, sv, xb16); wg_commit(); XR<6, 8, 0, 8, 0>::run(d, wv, xb16); wg_commit(); wg_wait1();
          ldmatrix_x4_trans(sv[0], WA + 6 * 2048); ldmatrix_x4_trans(sv[1], WA + 7 * 2048);
          wg_fence(); XR<14, 16, -14, 2, 0>::run(d, sv, xb16); wg_commit(); wg_wait0();
        }
#elif BI == 4
        wg_fence(); XR<0, BR, 0, 8, 1>::run(d, wv, xb16);
        bar_sync(B_LD, 320);
        XR<BR, 8, 0, 8, 0>::run(d, wv, xb16); XS<8, 8, 16, 0>::run(d, va16, xb16); wg_commit(); wg_wait0();
#elif BI == 5
        if (wg == 0) { wg_fence(); XR<0, KB, 0, 32, 1>::run(d, w, xb16); wg_commit(); wg_wait0(); OPAQUE_R(l16); DUMP(SM_CW); }
        wg_fence(); XR<0, BR, 0, 8, 1>::run(d, wv, xb16); XS<8, 8, 16, BR == 0>::run(d, va16, xb16); XR<BR, 8, 0, 8, 0>::run(d, wv, xb16); wg_commit(); wg_wait0();
#else
        wg_fence(); XR<0, BR, 0, 8, 1>::run(d, wv, xb16); XS<8, 8, 16, BR == 0>::run(d, va16, xb16); XR<BR, 8, 0, 8, 0>::run(d, wv, xb16); wg_commit(); wg_wait0();
#endif
        uint32_t q[8];
#pragma unroll
        for (int i = 0; i < 8; i++) q[i] = pack_bf16(d[2 * i], d[2 * i + 1]);
        if (wg == 0) {
          sts128(cv, q[0], q[1], q[2], q[3]); sts128(cv + 2048, q[4], q[5], q[6], q[7]);
          if (BI != 5) {
          wg_fence(); XR<0, KB, 0, 32, 1>::run(d, w, xb16); wg_commit(); wg_wait0();
          OPAQUE_R(l16);
          DUMP(SM_CW);
          }
          TSF(5, 1);
        } else {
          const uint4 o = lds128(cv + (r ^ 1) * 2048), k = lds128(cv + r * 2048);
          XREL(MB_XE1);
          st_async4(l16 + (rsb + SM_VR + wq * 512), u2f(addb2(r ? q[0] : q[4], o.x)), u2f(addb2(r ? q[1] : q[5], o.y)), u2f(addb2(r ? q[2] : q[6], o.z)), u2f(addb2(r ? q[3] : q[7], o.w)),
                    rsb + SM_BAR + MB_VR);
          sts128(TQ(SM_VL), addb2(r ? q[4] : q[0], k.x), addb2(r ? q[5] : q[1], k.y), addb2(r ? q[6] : q[2], k.z), addb2(r ? q[7] : q[3], k.w));
          __syncwarp();
          if (l16 == 0) mbar_arrive(sb + SM_BAR + MB_VR);
          TSF(28, 5);
        }
      }
    }
  } else {
    asm volatile("setmaxnreg.dec.sync.aligned.u32 " STR(RF_CTL) ";");
    const int g = lane >> 2, tq = lane & 3;
    if (wq == 0) {
      if (lane < 12) asm volatile("prefetch.global.L2 [%0];" :: "l"(SP.x + (size_t)(cta * 12 + lane) * 64));
      __syncwarp();
      {
        SIDES();
        const uint32_t o[6] = {w_blk(w_h1(cta), me), w_blk(w_h1(cta) ^ H1_V, me), w_blk(w_mvx(cta, 0), me ^ sm2.z), w_blk(w_mvx(cta, 1), me ^ sm2.z),
                               w_blk(w_mxa(cta, 0), me ^ sm2.z), w_blk(w_mxa(cta, 1), me ^ sm2.z)};
#pragma unroll
        for (int i = 0; i < 24; i++) stg_r4(P.win + (o[i >> 2] + (i & 3) * 512 + lane * 16), 0u, 0u, 0u, 0u);
#pragma unroll
        for (int i = 0; i < 6; i++) stg_r1(P.win + (w_ar(i >> 1) + cta * 256 + (i & 1) * W_DS + lane * 4), 0u);
        __threadfence();
        __syncwarp();
      }
      {
        const uint32_t wv = movm(*reinterpret_cast<const uint32_t*>(P.mem0 + g * DM + cta * 8 + tq * 2));
        const bool sp = lane == cnt_word(cta & 31);
        stg_r1(P.win + (w_ar(-1) + cta * 256 + lane * 4), sp ? (wv & 0xffffu) | 0x42000000u : wv);
        if (sp) stg_r1(P.win + (w_ar(-1) + ((cta & ~9) + ((cta >> 1) & 1)) * 256 + W_DS + lane * 4), (wv >> 16) | 0x42000000u);
      }
      bar_sync(B_V, 160);
      if (lane == 0) {
        fence_async_smem(); mbar_arrive_cluster_rlx(mapa(sb + SM_BAR + MB_INIT, 0)); mbar_arrive_cluster_rlx(mapa(sb + SM_BAR + MB_INIT, 1));
        mbar_wait(sb + SM_BAR + MB_INIT, 0);
        mbar_expect_tx(sb + SM_BAR + MB_F, 32768);
        for (int i = 0; i < (BGT == 2 ? 7 : BGT == 1 ? 3 : 0); i++) mbar_arrive(sb + SM_BAR + MB_F);
        mbar_expect_tx(sb + SM_BAR + MB_F + 8, 32768);
        XLOAD(1, 0); XLOAD(0, 1);
        WLOAD(4 + WSPL, 8);
      }
      __syncwarp();
#ifdef PER
      if (lane == 0) atomicMax(&g_end[5], gt32());
#endif
      bar_sync(B_X2, 384);
    } else {
      bar_sync(B_P, 224);
#ifdef PER
      if (t128 == 32) atomicMax(&g_end[4], gt32());
#endif
      if (t128 == 96) {
        fence_async_smem();
        mbar_expect_tx(sb + SM_BAR + MB_WO, 65536);
        for (int i = 0; i < 8; i++) tma_load_2d(sb + SM_WOS + i * 8192, &tmw, j * 256 + ((i >> 1) ^ (2 * sw)) * 64, h * DH + (i & 1) * 64, sb + SM_BAR + MB_WO);
      }
      __syncwarp();
      bar_sync(B_X2, 384);
    }
    SIDES();
    uint32_t l16 = __shfl_sync(~0u, lane * 16, lane);
    const uint32_t me2 = me ^ sm2.z;
    const float sc = 32.f * 0.08838834764831845f * 1.4426950408889634f;
    uint32_t ls = l16 + sb;
#define PVM(o, zs, p0, p2, M1, M2) do { \
        FENCE(); \
        mma4z(zs, 0x3F803F80u, 0x3F803F80u, 0x3F803F80u, 0x3F803F80u, p0.x, p0.y); \
        FENCE(); M1; \
        _Pragma("unroll") for (int t = 0; t < 4; t++) mma4z(o[t], va[2 * t].x, va[2 * t].y, va[2 * t].z, va[2 * t].w, p0.x, p0.y); \
        FENCE(); \
        mma4(zs, 0x3F803F80u, 0x3F803F80u, 0x3F803F80u, 0x3F803F80u, p0.z, p0.w); \
        _Pragma("unroll") for (int t = 0; t < 2; t++) mma4(o[t], va[2 * t + 1].x, va[2 * t + 1].y, va[2 * t + 1].z, va[2 * t + 1].w, p0.z, p0.w); \
        FENCE(); M2; \
        mma_1688(zs, 0x3F803F80u, 0x3F803F80u, p2); \
        _Pragma("unroll") for (int t = 2; t < 4; t++) mma4(o[t], va[2 * t + 1].x, va[2 * t + 1].y, va[2 * t + 1].z, va[2 * t + 1].w, p0.z, p0.w); \
        mma_1688(o[0], vm[0].x, vm[0].y, p2); mma_1688(o[1], vm[0].z, vm[0].w, p2); mma_1688(o[2], vm[1].x, vm[1].y, p2); mma_1688(o[3], vm[1].z, vm[1].w, p2); } while (0)
#define PVE(o, z, dst) do { \
        const float i0 = rcpf(z[0]), i1 = rcpf(z[1]); \
        _Pragma("unroll") for (int u = 0; u < 2; u++) \
          stsm4t(ls + (dst) + u * 1024, pack_bf16(o[2 * u][0] * i0, o[2 * u][1] * i1), pack_bf16(o[2 * u][2] * i0, o[2 * u][3] * i1), \
                 pack_bf16(o[2 * u + 1][0] * i0, o[2 * u + 1][1] * i1), pack_bf16(o[2 * u + 1][2] * i0, o[2 * u + 1][3] * i1)); } while (0)
#define SOFTMAX(pf, f) do { \
        float mx = fmaxf(fmaxf(fmaxf(sx[2], sx[3]), fmaxf(sx[4], sx[5])), fmaxf(fmaxf(sx[6], sx[7]), fmaxf(sx[8], sx[9]))); \
        mx = fmaxf(mx, fmaxf(sx[0], sx[1])); \
        mx = fmaxf(mx, __shfl_xor_sync(~0u, mx, 1)); \
        mx = fmaxf(mx, __shfl_xor_sync(~0u, mx, 2)); \
        mx *= -(f); \
        _Pragma("unroll") for (int i = 0; i < 10; i++) sx[i] = ex2(fmaf(sx[i], f, mx)); \
        sts128(ls + (pf), pack_bf16(sx[2], sx[3]), pack_bf16(sx[4], sx[5]), pack_bf16(sx[6], sx[7]), pack_bf16(sx[8], sx[9])); \
        sts32(ls - l12 + (pf) + 512, pack_bf16(sx[0], sx[1])); } while (0)
    const uint32_t lq = (l16 ^ ((l16 >> 1) & 64u)) + sb, l12 = (l16 >> 2) * 3;
#define M3PTR(sl) \
            const uint32_t tf = me ^ 1 ^ r, m3i = w_ar(sl) + (wq & 1) * 16384 + (l16 & 0x70u) + ((l16 & 0x180u) << 1); \
            const unsigned char* p0f = P.win + (m3i + r * 8192 + tf * 4096); const unsigned char* p0n = P.win + (m3i + r * 8192 + (tf ^ 1) * 4096); \
            const unsigned char* p1f = P.win + (m3i + (r ^ 1) * 8192 + (tf ^ 1) * 4096); const unsigned char* p1n = P.win + (m3i + (r ^ 1) * 8192 + tf * 4096); \
            const unsigned char* pd = P.win + (w_ar(sl) + (wq & 1) * 16384 + (((l16 >> 7) ^ r) & 1u) * 8192 + ((l16 & 64u) * 4 + (l16 & 48u) * 2 + (l16 & 16u)) * 16 + W_DS + (l16 & 0x70u)); \
            uint32_t mf = ls + SM_MEM + (wq & 1) * 8192 + tf * 2048, mn = ls + SM_MEM + (wq & 1) * 8192 + (tf ^ 1) * 2048, nr = l16 < 256u ? 1u + (((l16 >> 6) ^ (l16 >> 7) ^ tf) & 1u) : 0u; \
            OPAQUE_L(p0f); OPAQUE_L(p0n); OPAQUE_L(p1f); OPAQUE_L(p1n); OPAQUE_L(pd); OPAQUE_R(mf); OPAQUE_R(mn); OPAQUE_R(nr); FENCE()
#define M3REQ(arr) \
            _Pragma("unroll") for (int i = 0; i < 4; i++) { cp16(mn + 4096 + i * 512, p1f + i * 1024); cp16(mf + i * 512, p0f + i * 1024); } \
            cp16p(ls + SM_RD + (wq & 1) * 256, pd, nr & 1u); \
            _Pragma("unroll") for (int i = 0; i < 4; i++) { cp16(mf + 4096 + i * 512, p1n + i * 1024); cp16(mn + i * 512, p0n + i * 1024); } \
            cp16p(ls + SM_RD + (wq & 1) * 256, pd, nr & 2u); \
            asm volatile("cp.async.mbarrier.arrive.noinc.shared::cta.b64 [%0];" :: "r"(sb + SM_BAR + MB_G + (wq & 1) * 8) : "memory"); \
            if (BI == 4 && (arr)) bar_arrive(B_LD, 320)
    if (wq < 2) { M3PTR(-1); M3REQ(1); }
#define ETA(k, first) ETAT(gt32() + (k), first)
#define ETAT(tm, first) do { unsigned char* pt = P.win + (w_ar(s) + (W_DS + 256) + (cta >> 5) * 8192 + ((cta >> 4) & 1) * 2048 + (l16 & 16u) * 256); \
          asm volatile("{\n.reg .pred q;\nsetp.lt.u32 q, %2, 32;\n@q red.relaxed.gpu.global.max.u32 [%0+4], %1;\n}" :: "l"(pt), "r"(tm), "r"(l16) : "memory"); \
          if (first) asm volatile("{\n.reg .pred q;\nsetp.lt.u32 q, %1, 32;\n@q red.relaxed.gpu.global.add.u32 [%0], 1;\n}" :: "l"(pt), "r"(l16) : "memory"); } while (0)
    if (wq == 1) {
      const uint32_t xin = w_blk(w_mxa(cta, 0), me2) + l16;
      const uint32_t lsq = sb + ((l16 & 0x70u) | ((l16 & 0x80u) << 1) | ((l16 & 0x100u) >> 1));
      mbar_wait(sb + SM_BAR + MB_MEM, 0); mbar_wait(sb + SM_BAR + MB_MEM + 8, 0);
      for (int s = 0; s < NSEG; s++) {
        const uint32_t t2 = ((s >> 1) & 1) ^ 1;
        mbar_wait(sb + SM_BAR + MB_XF, s & 1);
        PRB(10);
        {
        uint4 kx[4], qx[4];
#pragma unroll
        for (int i = 0; i < 4; i++) { kx[i] = ldsm4(ls + (SM_XF + (4 + i) * 512)); qx[i] = ldsm4(lsq + (SM_XF + i * 512)); }
        const uint32_t db = w_blk(w_mxa(h * 4, s), me2) + l16 - 512;
        {
          float S[2][4][4];
#pragma unroll
          for (int mt = 0; mt < 2; mt++) {
            const uint4 q0 = qx[mt];
            mma4z(S[mt][0], q0.x, q0.y, q0.z, q0.w, kx[0].x, kx[0].y); mma4z(S[mt][1], q0.x, q0.y, q0.z, q0.w, kx[0].z, kx[0].w);
            mma4z(S[mt][2], q0.x, q0.y, q0.z, q0.w, kx[1].x, kx[1].y); mma4z(S[mt][3], q0.x, q0.y, q0.z, q0.w, kx[1].z, kx[1].w);
          }
#pragma unroll
          for (int mt = 0; mt < 2; mt++) {
            const uint4 q1 = qx[2 + mt];
            mma4(S[mt][0], q1.x, q1.y, q1.z, q1.w, kx[2].x, kx[2].y); mma4(S[mt][1], q1.x, q1.y, q1.z, q1.w, kx[2].z, kx[2].w);
            mma4(S[mt][2], q1.x, q1.y, q1.z, q1.w, kx[3].x, kx[3].y); mma4(S[mt][3], q1.x, q1.y, q1.z, q1.w, kx[3].z, kx[3].w);
          }
          FENCE();
          if (XG && s > 0) bar_arrive(B_O2, 224);
          FENCE();
#pragma unroll
          for (int u = 0; u < 4; u++) {
            const int mt = u >> 1, c = 2 * (u & 1);
            const uint32_t m0 = tagw(pack_f16(S[mt][0][c], S[mt][0][c + 1]), t2), m1 = pack_f16(S[mt][1][c], S[mt][1][c + 1]),
                           m2 = pack_f16(S[mt][2][c], S[mt][2][c + 1]), m3 = pack_f16(S[mt][3][c], S[mt][3][c + 1]);
            const int e = u ^ j;
            if (e) stg_r4(P.win + (db + mt * 16384 + (u & 1) * 2048 + e * 512), m0, m1, m2, m3);
            else sts128(ls + SM_XS, m0, m1, m2, m3);
          }
        }
        TS(15);
        float sx[10];
        const unsigned char* pa = P.win + (xin + ((s & 1) << 20));
        uint4 xv[3];
        if (s > 0) spin(DLY_XD);
#pragma unroll
        for (int i = 0; i < 3; i++) xv[i] = ldg_r4(pa + i * 512);
        FENCE();
        if (GW == 0 && s > 0) {
          M3PTR(s - 1);
          bar_sync(B_GO, 64);
          const uint32_t tg0 = lds32(sb + SM_Z + 32);
          while (tg0 - gt32() - 1u < 8192u) {}
          M3REQ(s < NSEG);
        }
        FENCE();
        int n = 0;
#pragma unroll 1
        while (__any_sync(~0u, (x3(xv[0].x, xv[1].x, t2) | (xv[2].x ^ t2)) & 1u) && ++n < SPIN_LIMIT) {
#pragma unroll
          for (int i = 0; i < 3; i++) xv[i] = ldg_r4(pa + i * 512);
        }
        {
          const uint4 v3 = lds128(ls + SM_XS);
          sum_h4(sx[2], sx[3], xv[0].x, xv[1].x, xv[2].x, v3.x); sum_h4(sx[4], sx[5], xv[0].y, xv[1].y, xv[2].y, v3.y);
          sum_h4(sx[6], sx[7], xv[0].z, xv[1].z, xv[2].z, v3.z); sum_h4(sx[8], sx[9], xv[0].w, xv[1].w, xv[2].w, v3.w);
          const int row = 8 * j + g - 2 * tq;
#pragma unroll
          for (int i = 0; i < 8; i++) if ((i >> 1) * 8 + (i & 1) > row) sx[2 + i] = -INFINITY;
        }
        float mx = fmaxf(fmaxf(fmaxf(sx[2], sx[3]), fmaxf(sx[4], sx[5])), fmaxf(fmaxf(sx[6], sx[7]), fmaxf(sx[8], sx[9])));
        sts32(ls - l12 + SM_XS + 512, f2u(mx));
        {
          if (l16 == 0) mbar_expect_tx(sb + SM_BAR + MB_VR, 2048);
          unsigned char* d = P.win + (w_blk(w_mvx(cta, s), me2) + l16);
          OPAQUE_L(d); FENCE();
          mbar_wait(sb + SM_BAR + MB_VR, s & 1);
          PRB(14);
#pragma unroll
          for (int t = 0; t < 4; t++) {
            const uint4 a0 = lds128(ls + (SM_VL + t * 512)), a1 = lds128(ls + (SM_VR + t * 512));
            stg_r4(d + t * 512, tagw(addb2(a0.x, a1.x), t2), addb2(a0.y, a1.y), addb2(a0.z, a1.z), addb2(a0.w, a1.w));
          }
          TS(23);
        }
        unsigned char* pm = P.win + (db + 2048 + j * 128 - l12);
        const unsigned char* py = pa + 1536 - l12;
        OPAQUE_L(pm); OPAQUE_L(py);
        if (s > 0) bar_sync(B_PXF, 96);
        FENCE();
        bar_sync(B_QK1, 288);
        uint32_t kb[2][2];
#pragma unroll
        for (int t = 0; t < 2; t++) {
          const float4 u = lds128f(lq + (SM_QKP + (2 + t) * 512)), v4 = lds128f(lq + (SM_QKP + 2048 + (2 + t) * 512));
          kb[t][0] = pack_bf16(u.x + v4.x, u.y + v4.y); kb[t][1] = pack_bf16(u.z + v4.z, u.w + v4.w);
        }
        float S[2][4];
#pragma unroll
        for (int mt = 0; mt < 2; mt++) mma4z(S[mt], qx[mt].x, qx[mt].y, qx[mt].z, qx[mt].w, kb[0][0], kb[0][1]);
#pragma unroll
        for (int mt = 0; mt < 2; mt++) mma4(S[mt], qx[2 + mt].x, qx[2 + mt].y, qx[2 + mt].z, qx[2 + mt].w, kb[1][0], kb[1][1]);
        if (s == 0) mbar_wait(sb + SM_BAR + MB_WO, 0);
        if (s < NSEG - 1) bar_arrive(B_PUB, 320);
        FENCE();
#pragma unroll
        for (int u = 0; u < 4; u++) stg_r1(pm + (u >> 1) * 16384 + (u & 1) * 2048, tagw(pack_f16(S[u >> 1][2 * (u & 1)], S[u >> 1][2 * (u & 1) + 1]), t2));
        TS(30);
        spin(DLY_XL);
        uint32_t xy[4];
#pragma unroll
        for (int i = 0; i < 4; i++) xy[i] = ldg_r1(py + i * 128);
        FENCE();
        if (ETW == 1 && s < NSEG - 1) ETA(DLY_K, 1);
        FENCE();
        n = 0;
#pragma unroll 1
        while (__any_sync(~0u, (x3(xy[0], xy[1], t2) | x3(xy[2], xy[3], t2)) & 1u) && ++n < SPIN_LIMIT) {
#pragma unroll
          for (int i = 0; i < 4; i++) xy[i] = ldg_r1(py + i * 128);
        }
        sum_h4(sx[0], sx[1], xy[0], xy[1], xy[2], xy[3]);
        mx = fmaxf(mx, fmaxf(sx[0], sx[1]));
        mx = fmaxf(fmaxf(mx, __shfl_xor_sync(~0u, mx, 1)), fmaxf(__shfl_xor_sync(~0u, mx, 2), __shfl_xor_sync(~0u, mx, 3)));
#pragma unroll
        for (int i = 0; i < 10; i++) sx[i] = ex2(fmaf(sx[i], sc, -sc * mx));
        sts128(ls + SM_PX, pack_bf16(sx[2], sx[3]), pack_bf16(sx[4], sx[5]), pack_bf16(sx[6], sx[7]), pack_bf16(sx[8], sx[9]));
        sts32(ls - l12 + SM_PX + 512, pack_bf16(sx[0], sx[1]));
        bar_arrive(B_PX, 96);
        TS(1);
        }
      }
    } else {
      const uint32_t ho = (wq & 1) * 512 + l16, hv = wq == 0 ? 0u : H1_V;
      uint32_t ow = w_blk(w_h1(cta) ^ hv, me) + ho, or0 = w_blk(w_h1(cta ^ 1) ^ hv, me) + ho, or1 = w_blk(w_h1((cta ^ 2) & ~1) ^ hv, me) + ho;
#define PTRS() OPAQUE_R(ow); OPAQUE_R(or0); OPAQUE_R(or1); \
      unsigned char* pw0 = P.win + ow; const unsigned char* pr0 = P.win + or0; const unsigned char* pr1 = P.win + or1; \
      OPAQUE_L(pw0); OPAQUE_L(pr0); OPAQUE_L(pr1); FENCE()
      if (wq == 0) {
        const uint32_t xcnt = me ? NCTA - nlo : nlo, xrank = (me ? cta - nlo : cta) + lane * xcnt;
        int kd = DLY_K;
        mbar_wait(sb + SM_BAR + MB_XE1, 0);
        if (l16 == 0) { mbar_expect_tx(sb + SM_BAR + MB_F + 8, 32768); XLOAD(1, 1); }
        __syncwarp();
        for (int s = 0; s < NSEG - 1; s++) {
          const uint32_t tg = (s & 1) ^ 1;
          mbar_wait(sb + SM_BAR + MB_XF, s & 1);
          uint4 xf[4];
#pragma unroll
          for (int i = 0; i < 4; i++) xf[i] = ldsm4(ls + (SM_XF + (4 + i) * 512));
          PTRS();
          unsigned char* pw1 = pw0 + 512 - l12; OPAQUE_L(pw1);
          bar_sync(B_QK, 288);
          PRB(9);
          float4 u[4], v4[4];
#pragma unroll
          for (int t = 0; t < 4; t++) { u[t] = lds128f(lq + (SM_QKP + t * 512)); v4[t] = lds128f(lq + (SM_QKP + 2048 + t * 512)); }
          FENCE();
          uint32_t f[4][2], m[5];
#pragma unroll
          for (int t = 0; t < 2; t++) { f[t][0] = pack_bf16(u[t].x + v4[t].x, u[t].y + v4[t].y); f[t][1] = pack_bf16(u[t].z + v4[t].z, u[t].w + v4[t].w); }
          float S[5][4], T[5][4];
          mma4z(S[1], f[0][0], f[1][0], f[0][1], f[1][1], xf[0].x, xf[0].y); mma4z(T[1], f[0][0], f[1][0], f[0][1], f[1][1], xf[2].x, xf[2].y);
          mma4z(S[2], f[0][0], f[1][0], f[0][1], f[1][1], xf[0].z, xf[0].w); mma4z(T[2], f[0][0], f[1][0], f[0][1], f[1][1], xf[2].z, xf[2].w);
          FENCE();
#pragma unroll
          for (int t = 2; t < 4; t++) { f[t][0] = packv(u[t].x, v4[t].x, u[t].y, v4[t].y); f[t][1] = packv(u[t].z, v4[t].z, u[t].w, v4[t].w); }
          mma4z(S[3], f[0][0], f[1][0], f[0][1], f[1][1], xf[1].x, xf[1].y); mma4z(T[3], f[0][0], f[1][0], f[0][1], f[1][1], xf[3].x, xf[3].y);
          mma4z(S[4], f[0][0], f[1][0], f[0][1], f[1][1], xf[1].z, xf[1].w); mma4z(T[4], f[0][0], f[1][0], f[0][1], f[1][1], xf[3].z, xf[3].w);
          FENCE();
          mma4z(S[0], f[0][0], f[1][0], f[0][1], f[1][1], f[2][0], f[2][1]); mma4z(T[0], f[0][0], f[1][0], f[0][1], f[1][1], f[3][0], f[3][1]);
          bar_arrive(B_PUB, 320);
          FENCE();
#pragma unroll
          for (int i = 1; i < 5; i++) m[i] = pack_f16(S[i][0] + T[i][2], S[i][1] + T[i][3]);
          stg_r4(pw0, tagw(m[1], tg), m[2], m[3], m[4]);
          m[0] = pack_f16(S[0][0] + T[0][2], S[0][1] + T[0][3]);
          stg_r1(pw1, tagw(m[0], tg));
          TS(6);
          FENCE();
          const uint32_t ts = clk32();
          uint32_t te = gt32() + kd;
          const unsigned char* py0 = pr0 + 512 - l12; const unsigned char* py1 = pr1 + 512 - l12;
          OPAQUE_L(py0); OPAQUE_L(py1);
          unsigned char* pt = P.win + (w_ar(s) + (W_DS + 256) + (cta >> 5) * 8192 + ((cta >> 4) & 1) * 2048 + (l16 & 16u) * 256);
          OPAQUE_L(pt);
          if (l16 == 0) mbar_expect_tx(sb + SM_BAR + MB_F, s < NSEG - 2 ? 32768 : 0);
          FENCE();
          while (clk32() - ts < (uint32_t)DLY_S) {}
          {
            float sx[10]; uint32_t x, x1, x2, x3_; int n = 0; bool bad;
#pragma unroll 1
            do {
              uint4 v[3]; uint32_t y[3], t[5];
              v[0] = ldg_r4(pr0); v[1] = ldg_r4(pr1); v[2] = ldg_r4(pr1 + 2048);
              y[0] = ldg_r1(py0); y[1] = ldg_r1(py1); y[2] = ldg_r1(py1 + 2048);
              if (n) te = gt32() + DLY_KS;
              eta2(pt, te, n == 0, l16);
              n++;
              FENCE();
#define Q3(o, a, b, c) hadd2(hadd2(o, a), hadd2(b, c))
              t[1] = Q3(m[1], v[0].x, v[1].x, v[2].x); t[2] = Q3(m[2], v[0].y, v[1].y, v[2].y); t[3] = Q3(m[3], v[0].z, v[1].z, v[2].z); t[4] = Q3(m[4], v[0].w, v[1].w, v[2].w);
              t[0] = Q3(m[0], y[0], y[1], y[2]);
              bad = __any_sync(~0u, or3(x3(v[0].x, v[1].x, tg), x3(v[2].x, y[0], tg), x3(y[1], y[2], tg)) & (n < SPIN_LIMIT ? 1u : 0u));
              x = hmax2(hmax2(hmax2(t[1], t[2]), hmax2(t[3], t[4])), t[0]);
              const float2 xm = __half22float2(*reinterpret_cast<__half2*>(&x));
              x = f2u(fmaxf(xm.x, xm.y) * -sc);
              x1 = shfl_x(x, 1); x2 = shfl_x(x, 2); x3_ = shfl_x(x, 3);
              FENCE();
#pragma unroll
              for (int i = 1; i < 6; i++) h2f(sx[2 * (i % 5)], sx[2 * (i % 5) + 1], t[i % 5]);
              FENCE();
            } while (bad);
            const float mx = fminf(fminf(u2f(x), u2f(x1)), fminf(u2f(x2), u2f(x3_)));
#pragma unroll
            for (int i = 2; i < 12; i++) sx[i % 10] = ex2v(sx[i % 10], sc, mx);
#pragma unroll
            for (int i = 1; i < 6; i++) m[i % 5] = pack_bf16(sx[2 * (i % 5)], sx[2 * (i % 5) + 1]);
            sts128(ls + SM_PF, m[1], m[2], m[3], m[4]);
            sts32(ls - l12 + SM_PF + 512, m[0]);
            TV(19, n - 1);
          }
          TS(12);
          bar_sync(B_P, 96);
          if (LN) {
            const uint4 pa = lds128(ls + SM_PF); const uint32_t pb = lds32(ls - l12 + SM_PF + 512);
#define S2(w) (u2f((w) << 16) + u2f((w) & 0xffff0000u))
            float z = ((S2(pa.x) + S2(pa.y)) + (S2(pa.z) + S2(pa.w))) + S2(pb);
            z += __shfl_xor_sync(~0u, z, 1); z += __shfl_xor_sync(~0u, z, 2);
            sts32(sb + SM_Z + (l16 >> 6) * 4, f2u(rcpf(z)));
            bar_arrive(B_O, 352);
          }
          OPAQUE_R(l16);
          {
            const unsigned char* pe = P.win + w_blk(w_ar(s) + (W_DS + 256) + (l16 & 0x60u) * 256 + (l16 & 16u) * 128, me);
            const uint32_t tp = gt32() + DLY_M3;
            PRB(12);
            if (F0W == 0 && s < NSEG - 2) F0LOAD();
            if (PA) ETAT(tp, 0);
            uint32_t tg0; int n = 0;
#pragma unroll 1
            for (;;) {
              const uint2 e = ldg_r2(pe);
              tg0 = __reduce_max_sync(~0u, e.y);
              if (tg0 - tp >= 4096u) tg0 = tp;
              if ((!__any_sync(~0u, e.x != 16u) && (int)(tg0 - gt32()) < DLY_RR) || ++n >= SPIN_LIMIT) break;
            }
            sts32(sb + SM_Z + 32, tg0);
            bar_arrive(B_GO, GW ? 96 : 64);

            if (GW == 0) {
            M3PTR(s);
            while (tg0 - gt32() - 1u < 8192u) {}
            PRB(13);
            TS(16);
            M3REQ(s + 1 < NSEG);
            }
            TS(25);
          }
          if (F1C && s < NSEG - 2) {
            if (F1C == 1) spin(DLY_FA);
            mbar_wait(sb + SM_BAR + MB_XE1, (s + 1) & 1);
            if (l16 == 0) mbar_expect_tx(sb + SM_BAR + MB_F + 8, 32768);
            if (F1C == 2) { mbar_wait(sb + SM_BAR + MB_MEM, (s + 1) & 1); mbar_wait(sb + SM_BAR + MB_MEM + 8, (s + 1) & 1); }
            if (F1C == 3) { mbar_wait(sb + SM_BAR + MB_G, (s + 1) & 1); mbar_wait(sb + SM_BAR + MB_G + 8, (s + 1) & 1); }
            PRB(11);
            if (l16 == 0) XLOAD(1, s + 2);
            __syncwarp();
          }
          if (XPF && s + XPF < NSEG) {
            spin(DLY_PF);
            for (uint32_t i = xrank; i < 512; i += 32 * xcnt)
              asm volatile("prefetch.global.L2 [%0];" :: "l"(SP.x + (size_t)(s + XPF) * (SEG * DM) + i * 64));
            __syncwarp();
          }
          stg_2(P.win + (w_ar(s + 2) + cta * 256 + (l16 >> 8) * W_DS + ((l16 >> 1) & 127u)), 0u, 0u);
          kd = lds32(sb + SM_Z + 40) == (uint32_t)(s + 1) ? min(kd + KU, DLY_K + 256) : max(kd - KD, DLY_K);
          kd = __shfl_sync(~0u, kd, l16 >> 4);
        }
        bar_sync(B_QK, 288);
      } else {
        const int mt = wq - 2;
        const uint32_t lt = ls + mt * 1024;
        const uint32_t vi0 = w_blk(w_mvx(h * 4, 0), me2) + mt * 1024;
        const int m3d = r ? -8192 : 8192;
#ifdef PROF
        const uint32_t epoch = gt32(); TST(-1, 30 + mt, l16, epoch);
#endif
        float ox[4][4], zx[4];
#pragma unroll
        for (int i = 0; i < 16; i++) ox[i >> 2][i & 3] = zx[i & 3] = 1.f;
        for (int s = 0;; s++) {
          const uint32_t tg = (s & 1) ^ 1, t2 = ((s >> 1) & 1) ^ 1;
          {
            OPAQUE_R(l16);
            const uint32_t m3i = (mt * 2 + r) * 8192 + (l16 & 0x70u) + ((l16 & 0x180u) << 1);
            const uint32_t m3j = (mt * 2 + (r ^ (l16 >> 7 & 1))) * 8192 + ((l16 & 64u) * 4 + (l16 & 48u) * 2 + (l16 & 16u)) * 16 + W_DS + (l16 & 0x70u);
            uint32_t m3c = sb + SM_MEM + mt * 8192 + cnt_line(l16 >> 4) * 128 + (l16 >> 2);
            const unsigned char* p3 = P.win + (m3i + w_ar(s - 1)); const unsigned char* pd = P.win + (m3j + w_ar(s - 1));
            OPAQUE_L(pd); OPAQUE_R(m3c);
#define XEPI() do {        \
              PVE(ox, zx, SM_OX + mt * 512); \
              __syncwarp(); \
              const uint32_t oa = sb + SM_OX + mt * 512 + ((l16 & 48u) << 3) + ((l16 >> 2) & 0x70u); \
              const uint4 a = lds128(oa), b = lds128(oa + 1024); \
              unsigned char* o = reinterpret_cast<unsigned char*>(g_ox + (size_t)((s - 1) * SEG + 8 * j) * (NH * DH) + h * DH + mt * 32) + ((l16 >> 6) * (NH * DH * 2) + (l16 & 48u)); \
              stg_4(o, a); stg_4(o + 128, b); \
              TST(s - 1, 18, l16 | mt, TCLK()); } while (0)
            if (s > 0) XEPI();
            if (s == NSEG) break;
            if (GW && s > 0) {
              M3PTR(s - 1);
              bar_sync(B_GO, 96);
              const uint32_t tg0 = lds32(sb + SM_Z + 32);
              while (tg0 - gt32() - 1u < 8192u) {}
              M3REQ(0);
            }
            FENCE();
            const int n = m3_check(sb, p3, pd, m3d, l16, m3c, mt, s);
            FENCE();
            if (ETW == 3 && s < NSEG - 1) ETA(DLY_K, mt);
            TST(s, mt ? 21 : 0, l16, TCLK());
            TST(s, mt ? 22 : 17, l16, n);
#ifdef PER
            if (l16 == 0 && mt == 0 && s > 0) { g_per[cta][s - 1] = gt32(); g_pclk[cta][s - 1] = clk32(); }
#endif
          }
          uint4 va[8], vm[2], p0, q0; uint32_t p2, q2;
          const unsigned char* a0 = P.win + (vi0 + ((s & 1) << 20) + l16);
#define VALD() _Pragma("unroll") for (int i = 0; i < 4; i++) { va[i] = ldg_r4(a0 + (i >> 1) * 512 + (i & 1) * 2048); va[4 + i] = ldg_r4(a0 + 16384 + (i >> 1) * 512 + (i & 1) * 2048); }
          if (!VAL) { spin(DLY_WO); VALD(); }
          {
          PTRS();
          bar_sync(B_V, 320);
            const float4 u0 = lds128f(lt + SM_VP), w0 = lds128f(lt + SM_VP + 2048), u1 = lds128f(lt + SM_VP + 512), w1 = lds128f(lt + SM_VP + 2560);
            const uint32_t m0 = tagw(pack_bf16(u0.x + w0.x, u0.y + w0.y), tg), m1 = pack_bf16(u0.z + w0.z, u0.w + w0.w),
                           m2 = pack_bf16(u1.x + w1.x, u1.y + w1.y), m3 = pack_bf16(u1.z + w1.z, u1.w + w1.w);
            stg_r4(pw0, m0, m1, m2, m3);
            if (wq == 2) TS(10);
            FENCE();
            const uint32_t tv = clk32();
            if (VAL) { VALD(); }
            if (ETW == 2 && wq == 3 && s < NSEG - 1) ETA(DLY_K, 1);
            while (clk32() - tv < (uint32_t)DLY_V) {}
            uint4 v[3]; int n = 0; uint32_t bada = 0;
#pragma unroll 1
            do {
              v[0] = ldg_r4(pr0); v[1] = ldg_r4(pr1); v[2] = ldg_r4(pr1 + 2048);
              if (n) {
                TST(s, __any_sync(~0u, bada & 1u) ? 26 : 24, l16, epoch);
                if (__any_sync(~0u, bada & 1u)) { VALD(); }
                if (s < NSEG - 1) ETA(DLY_KS - 192, 0);
              }
              n++;
              FENCE();
              bada = or3(x3(va[0].x, va[1].x, t2), x3(va[2].x, va[3].x, t2), x3(va[4].x, va[5].x, t2)) | x3(va[6].x, va[7].x, t2);
            } while (__any_sync(~0u, or3(bada, x3(v[0].x, v[1].x, tg), v[2].x ^ tg) & 1u) && n < SPIN_LIMIT);
            const uint4 A = make_uint4(addb2(m0, v[0].x), addb2(m1, v[0].y), addb2(m2, v[0].z), addb2(m3, v[0].w));
            const uint4 B = make_uint4(addb2(v[1].x, v[2].x), addb2(v[1].y, v[2].y), addb2(v[1].z, v[2].z), addb2(v[1].w, v[2].w));
            vm[0] = p ? B : A; vm[1] = p ? A : B;
            TST(s, 11, l16 | mt, TCLK()); TST(s, 29, l16 | (mt ^ 1), TCLK());
          }
          if (F0W == 2 && wq == 3 && s < NSEG - 2) F0LOAD();
          if (PXE) { bar_sync(B_PX, 96); q0 = lds128(ls + SM_PX); q2 = lds32(ls - l12 + SM_PX + 512); }
          FENCE();
          if (s < NSEG - 1) {
          PRB(5);
          bar_sync(B_P, 96);
          PRB(6);
          p0 = lds128(ls + SM_PF); p2 = lds32(ls - l12 + SM_PF + 512);
          float o[4][4], z[4];
#if LN
          FENCE();
#pragma unroll
          for (int t = 0; t < 4; t++) mma4z(o[t], va[2 * t].x, va[2 * t].y, va[2 * t].z, va[2 * t].w, p0.x, p0.y);
#pragma unroll
          for (int t = 0; t < 4; t++) mma4(o[t], va[2 * t + 1].x, va[2 * t + 1].y, va[2 * t + 1].z, va[2 * t + 1].w, p0.z, p0.w);
          mma_1688(o[0], vm[0].x, vm[0].y, p2); mma_1688(o[1], vm[0].z, vm[0].w, p2); mma_1688(o[2], vm[1].x, vm[1].y, p2); mma_1688(o[3], vm[1].z, vm[1].w, p2);
#pragma unroll
          for (int u = 0; u < 2; u++)
            stsm4t(ls + (SM_OF + mt * 512) + u * 1024, pack_bf16(o[2 * u][0], o[2 * u][1]), pack_bf16(o[2 * u][2], o[2 * u][3]),
                   pack_bf16(o[2 * u + 1][0], o[2 * u + 1][1]), pack_bf16(o[2 * u + 1][2], o[2 * u + 1][3]));
          bar_arrive(B_O, 352);
#else
#ifdef PROF
          uint32_t tq0, tq1;
          asm volatile("{\n.reg .u32 x;\nand.b32 x, %1, 0;\nmov.u32 %0, %%clock;\nadd.u32 %0, %0, x;\n}" : "=r"(tq0) : "r"(p0.x ^ p2));
#endif
          PVM(o, z, p0, p2, , );
#ifdef PROF
          FENCE();
          asm volatile("{\n.reg .pred q;\nsetp.eq.f32 q, %1, 0f7f7fffff;\n@q trap;\nmov.u32 %0, %%clock;\n}" : "=r"(tq1) : "f"(o[3][0]));
#endif
          PVE(o, z, SM_OF + mt * 512);
          bar_arrive(B_O, 192);
          TST(s, 20, l16 | mt, tq1);
#endif
          }
          FENCE();
          TST(s, 8, l16 | mt, TCLK());
          if (!PXE) { bar_sync(B_PX, 96); q0 = lds128(ls + SM_PX); q2 = lds32(ls - l12 + SM_PX + 512); }
          if (O2P == 0 && s < NSEG - 1) bar_arrive(B_O2, XG ? 224 : 192);
          PVM(ox, zx, q0, q2, if (O2P == 1 && s < NSEG - 1) bar_arrive(B_O2, XG ? 224 : 192), if (O2P == 2 && s < NSEG - 1) bar_arrive(B_O2, XG ? 224 : 192));
          FENCE();
          if (s < NSEG - 1) { if (O2P == 3) bar_arrive(B_O2, XG ? 224 : 192); bar_arrive(B_PXF, 96); }
        }
      }
    }
  }
#if RLX
  asm volatile("barrier.cluster.arrive.relaxed.aligned;\nbarrier.cluster.wait.aligned;" ::: "memory");
#else
  asm volatile("barrier.cluster.arrive.release.aligned;\nbarrier.cluster.wait.acquire.aligned;" ::: "memory");
#endif
#ifdef PER
  if (threadIdx.x == 0) atomicMax(&g_end[0], gt32());
#endif
}
#ifndef PW
#define PW 2
#endif
#ifndef G2_ST
#define G2_ST 6
#endif
#define G2_TB (G2_ST * 32768 + 1024)
#define G2_SMEM (G2_TB + 32768)
static __device__ __forceinline__ void wgmma_n128_ta(float (&d)[64], uint64_t da, uint64_t db) {
  asm volatile(
      "wgmma.mma_async.sync.aligned.m64n128k16.f32.bf16.bf16 "
      "{%0,%1,%2,%3,%4,%5,%6,%7,%8,%9,%10,%11,%12,%13,%14,%15,%16,%17,%18,%19,%20,%21,%22,%23,%24,%25,%26,%27,%28,%29,%30,%31,"
      "%32,%33,%34,%35,%36,%37,%38,%39,%40,%41,%42,%43,%44,%45,%46,%47,%48,%49,%50,%51,%52,%53,%54,%55,%56,%57,%58,%59,%60,%61,%62,%63}, "
      "%64, %65, 1, 1, 1, 1, 0;"
      : "+f"(d[0]), "+f"(d[1]), "+f"(d[2]), "+f"(d[3]), "+f"(d[4]), "+f"(d[5]), "+f"(d[6]), "+f"(d[7]), "+f"(d[8]), "+f"(d[9]), "+f"(d[10]), "+f"(d[11]),
        "+f"(d[12]), "+f"(d[13]), "+f"(d[14]), "+f"(d[15]), "+f"(d[16]), "+f"(d[17]), "+f"(d[18]), "+f"(d[19]), "+f"(d[20]), "+f"(d[21]), "+f"(d[22]), "+f"(d[23]),
        "+f"(d[24]), "+f"(d[25]), "+f"(d[26]), "+f"(d[27]), "+f"(d[28]), "+f"(d[29]), "+f"(d[30]), "+f"(d[31]), "+f"(d[32]), "+f"(d[33]), "+f"(d[34]), "+f"(d[35]),
        "+f"(d[36]), "+f"(d[37]), "+f"(d[38]), "+f"(d[39]), "+f"(d[40]), "+f"(d[41]), "+f"(d[42]), "+f"(d[43]), "+f"(d[44]), "+f"(d[45]), "+f"(d[46]), "+f"(d[47]),
        "+f"(d[48]), "+f"(d[49]), "+f"(d[50]), "+f"(d[51]), "+f"(d[52]), "+f"(d[53]), "+f"(d[54]), "+f"(d[55]), "+f"(d[56]), "+f"(d[57]), "+f"(d[58]), "+f"(d[59]),
        "+f"(d[60]), "+f"(d[61]), "+f"(d[62]), "+f"(d[63])
      : "l"(da), "l"(db));
}
__global__ void __cluster_dims__(2, 1, 1) __launch_bounds__(384, 1)
gemm2_kernel(const __grid_constant__ CUtensorMap tmo, const __grid_constant__ CUtensorMap tmw, const bf16* __restrict__ x, bf16* __restrict__ out, unsigned char* win) {
  extern __shared__ __align__(1024) unsigned char smem[];
  const uint32_t sb = smem_u32(smem), bars = sb + G2_ST * 32768;
  const int tid = threadIdx.x, lane = tid & 31, warp = tid >> 5;
  const int r = blockIdx.x & 1, n0 = (blockIdx.x & 7) * 128, m0 = (blockIdx.x >> 3) * 128;
  if (tid == 0) {
    for (int i = 0; i < G2_ST; i++) { mbar_init(bars + i * 8, 1); mbar_init(bars + 64 + i * 8, 4); }
    asm volatile("fence.mbarrier_init.release.cluster;" ::: "memory");
  }
  if (tid == 32) { asm volatile("prefetch.tensormap [%0];" :: "l"(&tmw) : "memory"); asm volatile("prefetch.tensormap [%0];" :: "l"(&tmo) : "memory"); }
  __syncthreads();
  asm volatile("barrier.cluster.arrive.relaxed.aligned;" ::: "memory");
#define LW(kt, st) do { tma_load_2d(sb + (st) * 32768, &tmw, n0, (kt) * 64, bars + (st) * 8); tma_load_2d(sb + (st) * 32768 + 8192, &tmw, n0 + 64, (kt) * 64, bars + (st) * 8); } while (0)
#define LO(kt, st) asm volatile("cp.async.bulk.tensor.2d.shared::cluster.global.mbarrier::complete_tx::bytes.multicast::cluster [%0], [%1, {%3, %4}], [%2], %5;" \
                     :: "r"(sb + (st) * 32768 + 16384 + r * 8192), "l"(&tmo), "r"(bars + (st) * 8), "r"((kt) * 64), "r"(m0 + r * 64), "h"((uint16_t)3) : "memory")
  if (tid == 256) for (int kt = 0; kt < G2_ST; kt++) { mbar_expect_tx(bars + kt * 8, 32768); if (kt < PW) LW(kt, kt); }
  __syncwarp();
  asm volatile("barrier.cluster.wait.acquire.aligned;" ::: "memory");
  if (warp == 8) {
    if (lane == 0) {
      asm volatile("griddepcontrol.wait;" ::: "memory");
      for (int kt = 0; kt < G2_ST; kt++) { LO(kt, kt); if (kt >= PW) LW(kt, kt); }
      for (int kt = G2_ST; kt < 64; kt++) {
        const int st = kt % G2_ST;
        mbar_wait(bars + 64 + st * 8, ((kt / G2_ST) - 1) & 1);
        mbar_expect_tx(bars + st * 8, 32768);
        LO(kt, st); LW(kt, st);
      }
    }
  } else if (warp > 8) {
    const int t = tid - 288, ch = t & 15;
    asm volatile("griddepcontrol.wait;" ::: "memory");
#ifdef PER
    if (t == 0) atomicMax(&g_end[3], gt32());
#endif
    int idx[8];
#pragma unroll
    for (int c = 0; c < 8; c++) idx[c] = g_idx[c];
    const int gi = blockIdx.x * 96 + t;
    if (gi < 67) g_side[gi * 32] = 0u;
    if (gi == 0) g_sbar = 0u;
#pragma unroll 4
    for (int row = t >> 4; row < 128; row += 6) {
      const int tok = m0 + row;
      const uint4 xv = *reinterpret_cast<const uint4*>(x + (size_t)tok * DM + n0 + ch * 8);
      const float g = g_gate[tok], omg = rbf(1.f - g);
      int sel = -1;
#pragma unroll
      for (int c = 0; c < 8; c++) if (idx[c] == tok) sel = c;
      uint4 uv = make_uint4(0u, 0u, 0u, 0u);
      if (sel >= 0) uv = *reinterpret_cast<const uint4*>(g_upd + sel * DM + n0 + ch * 8);
      const uint32_t x4[4] = {xv.x, xv.y, xv.z, xv.w}, u4[4] = {uv.x, uv.y, uv.z, uv.w};
      uint32_t o4[4];
#pragma unroll
      for (int e = 0; e < 4; e++) {
        const float b0 = rbf(u2f(x4[e] << 16) + u2f(u4[e] << 16)), b1 = rbf(u2f(x4[e] & 0xffff0000u) + u2f(u4[e] & 0xffff0000u));
        o4[e] = pack_bf16(omg * b0, omg * b1);
      }
      sts128(sb + G2_TB + row * 256 + ch * 16, o4[0], o4[1], o4[2], o4[3]);
      if (ch == 0) sts32(bars + 512 + row * 4, __float_as_uint(g));
    }
    bar_arrive(2, 352);
  } else {
    const int wg = warp >> 2;
    float d[64];
#pragma unroll
    for (int i = 0; i < 64; i++) d[i] = 0.f;
    const uint32_t e0 = mapa(bars + 64, 0), e1 = mapa(bars + 64, 1);
#ifdef PER
    if (threadIdx.x == 0) { mbar_wait(bars, 0); atomicMax(&g_end[4], gt32()); }
    __syncwarp();
#endif
    for (int kt = 0; kt < 64; kt++) {
      const int st = kt % G2_ST;
      mbar_wait(bars + st * 8, (kt / G2_ST) & 1);
      wg_fence();
#pragma unroll
      for (int kk = 0; kk < 4; kk++)
        wgmma_n128_ta(d, make_desc(sb + st * 32768 + wg * 8192 + kk * 2048, 1024, 1024), make_desc(sb + st * 32768 + 16384 + kk * 32, 16, 1024));
      wg_commit();
      asm volatile("wgmma.wait_group.sync.aligned 1;" ::: "memory");
      if (kt > 0 && (tid & 127) == 0) { const int ps = (kt - 1) % G2_ST; mbar_arrive_cluster_rlx(e0 + ps * 8); mbar_arrive_cluster_rlx(e1 + ps * 8); }
    }
    wg_wait0();
#ifdef PER
    if (threadIdx.x == 0) atomicMax(&g_end[5], gt32());
#endif
    bar_sync(1, 256);
#pragma unroll
    for (int jj = 0; jj < 8; jj++) {
      const uint32_t q0 = pack_bf16(d[8 * jj], d[8 * jj + 1]), q1 = pack_bf16(d[8 * jj + 2], d[8 * jj + 3]);
      const uint32_t q2 = pack_bf16(d[8 * jj + 4], d[8 * jj + 5]), q3 = pack_bf16(d[8 * jj + 6], d[8 * jj + 7]);
      stsm4t(sb + (jj * 16 + (lane >> 4) * 8 + (lane & 7)) * 272 + (warp * 16 + ((lane >> 3) & 1) * 8) * 2, q0, q1, q2, q3);
    }
    bar_sync(2, 352);
#pragma unroll
    for (int it = 0; it < 8; it++) {
      const int row = it * 16 + (tid >> 4), ch = tid & 15, tok = m0 + row;
      const uint4 av = lds128(sb + row * 272 + ch * 16), tv = lds128(sb + G2_TB + row * 256 + ch * 16);
      const float g = u2f(lds32(bars + 512 + row * 4));
      const uint32_t a4[4] = {av.x, av.y, av.z, av.w}, t4[4] = {tv.x, tv.y, tv.z, tv.w};
      uint32_t o4[4];
#pragma unroll
      for (int e = 0; e < 4; e++)
        o4[e] = pack_bf16(rbf(g * u2f(a4[e] << 16)) + u2f(t4[e] << 16), rbf(g * u2f(a4[e] & 0xffff0000u)) + u2f(t4[e] & 0xffff0000u));
      *reinterpret_cast<uint4*>(out + (size_t)tok * DM + n0 + ch * 8) = make_uint4(o4[0], o4[1], o4[2], o4[3]);
    }
  }
  asm volatile("barrier.cluster.arrive.relaxed.aligned;\nbarrier.cluster.wait.aligned;" ::: "memory");
#ifdef PER
  if (threadIdx.x == 0) atomicMax(&g_end[2], gt32());
#endif
}
#ifndef WPROM
#define WPROM CU_TENSOR_MAP_L2_PROMOTION_L2_128B
#endif
#ifndef PDL
#define PDL 1
#endif
typedef CUresult (*PFN_encodeTiled)(CUtensorMap*, CUtensorMapDataType, cuuint32_t, void*, const cuuint64_t*, const cuuint64_t*,
                                    const cuuint32_t*, const cuuint32_t*, CUtensorMapInterleave, CUtensorMapSwizzle,
                                    CUtensorMapL2promotion, CUtensorMapFloatOOBfill);

extern "C" void kernel_launch(void* const* d_in, const int* in_sizes, int n_in, void* d_out, int out_size) {
  const bf16* x = (const bf16*)d_in[0];
  const bf16* mem0 = (const bf16*)d_in[1];
  const bf16* Wq = (const bf16*)d_in[2];
  const bf16* Wk = (const bf16*)d_in[3];
  const bf16* Wv = (const bf16*)d_in[4];
  const bf16* Wo = (const bf16*)d_in[5];
  const bf16* w_r = (const bf16*)d_in[8];
  const bf16* w_gate = (const bf16*)d_in[9];
  const bf16* w_up = (const bf16*)d_in[10];
  const bf16* w_down = (const bf16*)d_in[11];
  const bf16* gate_w = (const bf16*)d_in[12];
  bf16* out = (bf16*)d_out;

  static PFN_encodeTiled encode = nullptr;
  if (!encode) {
    void* fn = nullptr; cudaDriverEntryPointQueryResult st;
    cudaGetDriverEntryPoint("cuTensorMapEncodeTiled", &fn, cudaEnableDefault, &st);
    encode = (PFN_encodeTiled)fn;
    cudaFuncSetAttribute(rec_kernel, cudaFuncAttributeMaxDynamicSharedMemorySize, SM_TOTAL);
    cudaFuncSetAttribute(gemm2_kernel, cudaFuncAttributeMaxDynamicSharedMemorySize, G2_SMEM);
  }
  CUtensorMap tmx;
  {
    cuuint64_t gd[3] = {64, S_TOK, DM / 64};
    cuuint64_t gs[2] = {DM * 2, 128};
    cuuint32_t bx[3] = {64, SEG, 4};
    cuuint32_t es[3] = {1, 1, 1};
    encode(&tmx, CU_TENSOR_MAP_DATA_TYPE_BFLOAT16, 3, (void*)x, gd, gs, bx, es, CU_TENSOR_MAP_INTERLEAVE_NONE,
           CU_TENSOR_MAP_SWIZZLE_128B, CU_TENSOR_MAP_L2_PROMOTION_L2_128B, CU_TENSOR_MAP_FLOAT_OOB_FILL_NONE);
  }
  bf16* ox;
  cudaGetSymbolAddress((void**)&ox, g_ox);
  CUtensorMap tmo, tmw;
  {
    cuuint64_t gd[2] = {NH * DH, S_TOK}; cuuint64_t gs[1] = {NH * DH * 2}; cuuint32_t bx[2] = {64, 64}; cuuint32_t es[2] = {1, 1};
    encode(&tmo, CU_TENSOR_MAP_DATA_TYPE_BFLOAT16, 2, (void*)ox, gd, gs, bx, es, CU_TENSOR_MAP_INTERLEAVE_NONE,
           CU_TENSOR_MAP_SWIZZLE_128B, CU_TENSOR_MAP_L2_PROMOTION_L2_128B, CU_TENSOR_MAP_FLOAT_OOB_FILL_NONE);
    cuuint64_t gd2[2] = {DM, NH * DH}; cuuint64_t gs2[1] = {DM * 2}; cuuint32_t bx2[2] = {64, 64};
    encode(&tmw, CU_TENSOR_MAP_DATA_TYPE_BFLOAT16, 2, (void*)Wo, gd2, gs2, bx2, es, CU_TENSOR_MAP_INTERLEAVE_NONE,
           CU_TENSOR_MAP_SWIZZLE_128B, CU_TENSOR_MAP_L2_PROMOTION_L2_128B, CU_TENSOR_MAP_FLOAT_OOB_FILL_NONE);
  }
  unsigned char* win;
  cudaGetSymbolAddress((void**)&win, g_win);
  win = (unsigned char*)(((uintptr_t)win + (2u << 20) - 1) & ~(uintptr_t)((2u << 20) - 1));
  WMaps W;
  {
    cuuint64_t gd[2] = {NH * DH, DM}; cuuint64_t gs[1] = {NH * DH * 2}; cuuint32_t b32[2] = {32, 128}, b64[2] = {64, 128}; cuuint32_t es[2] = {1, 1};
    encode(&W.q, CU_TENSOR_MAP_DATA_TYPE_BFLOAT16, 2, (void*)Wq, gd, gs, b32, es, CU_TENSOR_MAP_INTERLEAVE_NONE,
           CU_TENSOR_MAP_SWIZZLE_64B, WPROM, CU_TENSOR_MAP_FLOAT_OOB_FILL_NONE);
    encode(&W.k, CU_TENSOR_MAP_DATA_TYPE_BFLOAT16, 2, (void*)Wk, gd, gs, b32, es, CU_TENSOR_MAP_INTERLEAVE_NONE,
           CU_TENSOR_MAP_SWIZZLE_64B, WPROM, CU_TENSOR_MAP_FLOAT_OOB_FILL_NONE);
    encode(&W.v, CU_TENSOR_MAP_DATA_TYPE_BFLOAT16, 2, (void*)Wv, gd, gs, b64, es, CU_TENSOR_MAP_INTERLEAVE_NONE,
           CU_TENSOR_MAP_SWIZZLE_128B, WPROM, CU_TENSOR_MAP_FLOAT_OOB_FILL_NONE);
  }
  RecParams P{mem0, win};
  SideParams SP{x, w_r, w_gate, w_up, w_down, gate_w, Wo};
  rec_kernel<<<NCTA + 4, 384, SM_TOTAL, cudaStreamPerThread>>>(tmx, tmw, W, P, SP);
  {
    cudaLaunchConfig_t cfg = {};
    cfg.gridDim = dim3(NCTA); cfg.blockDim = dim3(384); cfg.dynamicSmemBytes = G2_SMEM; cfg.stream = cudaStreamPerThread;
    cudaLaunchAttribute at[1];
    at[0].id = cudaLaunchAttributeProgrammaticStreamSerialization; at[0].val.programmaticStreamSerializationAllowed = 1;
    cfg.attrs = at; cfg.numAttrs = PDL;
    cudaLaunchKernelEx(&cfg, gemm2_kernel, tmo, tmw, x, out, win);
  }
}
```

```cpp
#include <cuda_runtime.h>
#include <cuda_bf16.h>
#include <cuda_fp16.h>
#include <cuda.h>
#include <stdint.h>

typedef __nv_bfloat16 bf16;

#define S_TOK 2048
#define DM 1024
#define NH 32
#define DH 128
#define MM 8
#define SEG 32
#define NSEG 64
#define LL 40
#define FF 3584
#define NCTA 128

static __device__ bf16 g_ox[(size_t)S_TOK * NH * DH];
static __device__ float g_gate[S_TOK];
static __device__ float g_r[S_TOK];
static __device__ int g_idx[8];
static __device__ bf16 g_upd[8 * DM];

static __device__ __forceinline__ float rbf(float v) { return __bfloat162float(__float2bfloat16(v)); }
static __device__ __forceinline__ uint32_t smem_u32(const void* p) { return (uint32_t)__cvta_generic_to_shared(p); }
static __device__ __forceinline__ uint32_t pack_bf16(float lo, float hi) {
  __nv_bfloat162 v = __floats2bfloat162_rn(lo, hi);
  return *reinterpret_cast<uint32_t*>(&v);
}

static __device__ __forceinline__ void wg_fence() { asm volatile("wgmma.fence.sync.aligned;" ::: "memory"); }
static __device__ __forceinline__ void wg_commit() { asm volatile("wgmma.commit_group.sync.aligned;" ::: "memory"); }
static __device__ __forceinline__ void wg_wait0() { asm volatile("wgmma.wait_group.sync.aligned 0;" ::: "memory"); }
static __device__ __forceinline__ void wg_wait1() { asm volatile("wgmma.wait_group.sync.aligned 1;" ::: "memory"); }
static __device__ __forceinline__ void fence_async_smem() { asm volatile("fence.proxy.async.shared::cta;" ::: "memory"); }

static __device__ __forceinline__ uint64_t make_desc(uint32_t addr, uint32_t lbo, uint32_t sbo) {
  uint64_t d = 0;
  d |= (uint64_t)((addr & 0x3FFFF) >> 4);
  d |= (uint64_t)((lbo >> 4) & 0x3FFF) << 16;
  d |= (uint64_t)((sbo >> 4) & 0x3FFF) << 32;
  d |= (uint64_t)1 << 62;
  return d;
}

#define DESC_HI(sbo) (((sbo) >> 4) | (1u << 30))
template <int OFF, int SCALE>
static __device__ __forceinline__ void wgmma_n32_ra(float (&d)[16], const uint32_t (&a)[4], uint32_t base16) {
  asm volatile(
      "{\n.reg .b32 t;\n.reg .b64 dd;\nadd.u32 t, %20, %21;\nmov.b64 dd, {t, %22};\n"
      "wgmma.mma_async.sync.aligned.m64n32k16.f32.bf16.bf16 "
      "{%0,%1,%2,%3,%4,%5,%6,%7,%8,%9,%10,%11,%12,%13,%14,%15}, {%16,%17,%18,%19}, dd, %23, 1, 1, 0;\n}"
      : "+f"(d[0]), "+f"(d[1]), "+f"(d[2]), "+f"(d[3]), "+f"(d[4]), "+f"(d[5]), "+f"(d[6]), "+f"(d[7]),
        "+f"(d[8]), "+f"(d[9]), "+f"(d[10]), "+f"(d[11]), "+f"(d[12]), "+f"(d[13]), "+f"(d[14]), "+f"(d[15])
      : "r"(a[0]), "r"(a[1]), "r"(a[2]), "r"(a[3]), "r"(base16), "n"(OFF >> 4), "n"(DESC_HI(1024)), "n"(SCALE));
}
template <int AOFF, int BOFF, int SCALE>
static __device__ __forceinline__ void wgmma_n32_ss_ta(float (&d)[16], uint32_t abase16, uint32_t bbase16) {
  asm volatile(
      "{\n.reg .b32 t, u;\n.reg .b64 da, db;\nadd.u32 t, %16, %18;\nmov.b64 da, {t, %20};\nadd.u32 u, %17, %19;\nmov.b64 db, {u, %20};\n"
      "wgmma.mma_async.sync.aligned.m64n32k16.f32.bf16.bf16 "
      "{%0,%1,%2,%3,%4,%5,%6,%7,%8,%9,%10,%11,%12,%13,%14,%15}, da, db, %21, 1, 1, 1, 0;\n}"
      : "+f"(d[0]), "+f"(d[1]), "+f"(d[2]), "+f"(d[3]), "+f"(d[4]), "+f"(d[5]), "+f"(d[6]), "+f"(d[7]),
        "+f"(d[8]), "+f"(d[9]), "+f"(d[10]), "+f"(d[11]), "+f"(d[12]), "+f"(d[13]), "+f"(d[14]), "+f"(d[15])
      : "r"(abase16), "r"(bbase16), "n"(AOFF >> 4), "n"(BOFF >> 4), "n"(DESC_HI(1024)), "n"(SCALE));
}
static __device__ __forceinline__ void ldmatrix_x4_trans(uint32_t (&r)[4], uint32_t addr) {
  asm volatile("ldmatrix.sync.aligned.m8n8.x4.trans.shared.b16 {%0,%1,%2,%3}, [%4];"
               : "=r"(r[0]), "=r"(r[1]), "=r"(r[2]), "=r"(r[3]) : "r"(addr) : "memory");
}
static __device__ __forceinline__ void mma_16816(float (&d)[4], const uint32_t (&a)[4], uint32_t b0, uint32_t b1) {
  asm volatile("mma.sync.aligned.m16n8k16.row.col.f32.bf16.bf16.f32 {%0,%1,%2,%3}, {%4,%5,%6,%7}, {%8,%9}, {%0,%1,%2,%3};"
               : "+f"(d[0]), "+f"(d[1]), "+f"(d[2]), "+f"(d[3])
               : "r"(a[0]), "r"(a[1]), "r"(a[2]), "r"(a[3]), "r"(b0), "r"(b1));
}

static __device__ __forceinline__ uint32_t mapa(uint32_t addr, uint32_t rank) {
  uint32_t r; asm volatile("mapa.shared::cluster.u32 %0, %1, %2;" : "=r"(r) : "r"(addr), "r"(rank)); return r;
}

static __device__ __forceinline__ void mbar_init(uint32_t bar, int cnt) {
  asm volatile("mbarrier.init.shared::cta.b64 [%0], %1;" :: "r"(bar), "r"(cnt) : "memory");
}
static __device__ __forceinline__ void mbar_expect_tx(uint32_t bar, uint32_t bytes) {
  asm volatile("mbarrier.arrive.expect_tx.shared::cta.b64 _, [%0], %1;" :: "r"(bar), "r"(bytes) : "memory");
}
static __device__ __forceinline__ void tma_load_2d(uint32_t dst, const CUtensorMap* tm, int c0, int c1, uint32_t bar) {
  asm volatile("cp.async.bulk.tensor.2d.shared::cluster.global.mbarrier::complete_tx::bytes [%0], [%1, {%3, %4}], [%2];"
               :: "r"(dst), "l"(tm), "r"(bar), "r"(c0), "r"(c1) : "memory");
}

static __device__ unsigned char g_win[6 << 20];
static __device__ unsigned int g_side[67 * 32];
static __device__ unsigned int g_err;
#define W_UP (1u << 20)
#define W_2 (2u << 20)
static __device__ __forceinline__ uint32_t w_blk(uint32_t off, uint32_t side) { return off | (((__popc((off >> 12) & 0xb3u) ^ side) & 1u) << 12); }
static __device__ __forceinline__ uint32_t w_h1(int c) { return W_UP | (1u << 13) | ((c >> 1) << 14) | ((c & 1) << 11); }
#define W_DS 0x30000u
static __device__ __forceinline__ uint32_t w_ar(int s) { return ((s & 1) << 15) | ((s & 2) << 17); }
static __device__ __forceinline__ uint32_t w_mvx(int c, int s) { return W_2 | ((s & 1) << 20) | ((c >> 1) << 14) | ((c & 1) << 11); }
static __device__ __forceinline__ uint32_t w_mxa(int c, int s) { return W_2 | ((s & 1) << 20) | (1u << 13) | ((c >> 1) << 14) | ((c & 1) << 11); }
#define H1_V (1u << 13)

#define SPIN_LIMIT (1 << 18)

#define SM_X 0
#define SM_WOS 65536
#define SM_WVS 131072
#define SM_MEM 163840
#define SM_QKP 180224
#define SM_VP 184320
#define SM_CW 188416
#define SM_VST 196608
#define SM_VR 196608
#define SM_CQ 200704
#define SM_CV 208896
#define SM_XF 217088
#define SM_VL 221184
#define SM_OF 225280
#define SM_OX 227328
#define SM_PF 229376
#define SM_PX 230016
#define SM_RD 198656
#define SM_QA 230656
#define SM_XS 231168
#define SM_BAR 231808
#define SM_Z 231936
#define SM_TS 232128
#define NTS 40
#define SM_TOTAL SM_TS
#define MB_F 0
#define MB_XE0 16
#define MB_XE1 112
#define MB_INIT 24
#define MB_MEM 32
#define MB_W 256
#define MB_XF 64
#define MB_VR 72
#define MB_X0 80
#define MB_WO 88
#define SM_SIDE (SM_BAR + 96)
#define MB_G 192
#define B_QK 1
#define B_V 2
#define B_P 3
#define B_O 4
#define B_O2 5
#define B_PUB 6
#define B_CQ 7
#define B_QK1 8
#define B_LD 9
#define B_PXF 10
#define B_CV 15
#define B_X2 11
#define B_PX 12
#define B_GO 14
#define B_G1 13

#ifdef PROF
__device__ unsigned int g_ts[NCTA][80][32];
#ifdef GT
#define TCLK() gt32()
#else
#define TCLK() clk32()
#endif
#ifndef TMASK
#define TMASK 0xffffffffu
#endif
#define TST(st, i, c, v) do { if ((TMASK >> (i)) & 1u) asm volatile("{\n.reg .pred q;\nsetp.eq.u32 q, %2, 0;\n@q st.global.u32 [%0], %1;\n}" :: "l"(&g_ts[cta][(st) + 1][i]), "r"((uint32_t)(v)), "r"((uint32_t)(c)) : "memory"); } while (0)
#define TS(i) TST(s, i, l16, TCLK())
#define TV(i, v) TST(s, i, l16, v)
#define TSF(i, w) TST(s, i, l16 | (w8 ^ (w)), TCLK())
#define TSP(i, w) TST(s - 1, i, l16 | (w8 ^ (w)), TCLK())
#define TVF(i, v) TV(i, v)
#else
#define TST(a, b, c, d)
#define TSF(i, w)
#define TSP(i, w)
#define TVF(i, v)
#define TS(i)
#define TV(i, v)
#endif

static __device__ __forceinline__ void bar_sync(int id, int n) { asm volatile("bar.sync %0, %1;" :: "r"(id), "r"(n) : "memory"); }
static __device__ __forceinline__ void bar_arrive(int id, int n) { asm volatile("bar.arrive %0, %1;" :: "r"(id), "r"(n) : "memory"); }
static __device__ __forceinline__ uint4 ldg_r4(const void* p) { uint4 v;
  asm volatile("ld.relaxed.gpu.global.v4.u32 {%0,%1,%2,%3}, [%4];" : "=r"(v.x), "=r"(v.y), "=r"(v.z), "=r"(v.w) : "l"(p) : "memory"); return v; }
static __device__ __forceinline__ uint32_t ldg_r1(const void* p) { uint32_t v;
  asm volatile("ld.relaxed.gpu.global.u32 %0, [%1];" : "=r"(v) : "l"(p) : "memory"); return v; }
template <int OFF> static __device__ __forceinline__ uint32_t ldg_r1o(const void* p) { uint32_t v;
  asm volatile("ld.relaxed.gpu.global.u32 %0, [%1+%2];" : "=r"(v) : "l"(p), "n"(OFF) : "memory"); return v; }
static __device__ __forceinline__ void stg_r4(void* p, uint32_t a, uint32_t b, uint32_t c, uint32_t d) {
  asm volatile("st.relaxed.gpu.global.v4.u32 [%0], {%1,%2,%3,%4};" :: "l"(p), "r"(a), "r"(b), "r"(c), "r"(d) : "memory"); }
static __device__ __forceinline__ void stg_r2(void* p, uint32_t a, uint32_t b) {
  asm volatile("st.relaxed.gpu.global.v2.u32 [%0], {%1,%2};" :: "l"(p), "r"(a), "r"(b) : "memory"); }
static __device__ __forceinline__ uint2 ldg_r2(const void* p) { uint2 v;
  asm volatile("ld.relaxed.gpu.global.v2.u32 {%0,%1}, [%2];" : "=r"(v.x), "=r"(v.y) : "l"(p) : "memory"); return v; }
static __device__ __forceinline__ void stg_4(void* p, const uint4& v) {
  asm volatile("st.global.v4.u32 [%0], {%1,%2,%3,%4};" :: "l"(p), "r"(v.x), "r"(v.y), "r"(v.z), "r"(v.w) : "memory"); }
static __device__ __forceinline__ uint32_t f2u(float v) { return __float_as_uint(v); }
static __device__ __forceinline__ void stg_2(void* p, uint32_t a, uint32_t b) {
  asm volatile("st.global.v2.u32 [%0], {%1,%2};" :: "l"(p), "r"(a), "r"(b) : "memory"); }
static __device__ __forceinline__ void stg_r1(void* p, uint32_t a) {
  asm volatile("st.relaxed.gpu.global.u32 [%0], %1;" :: "l"(p), "r"(a) : "memory"); }
static __device__ __forceinline__ void sts128(uint32_t a, uint32_t x, uint32_t y, uint32_t z, uint32_t w) {
  asm volatile("st.shared.v4.u32 [%0], {%1,%2,%3,%4};" :: "r"(a), "r"(x), "r"(y), "r"(z), "r"(w) : "memory"); }
static __device__ __forceinline__ void sts128f(uint32_t a, float x, float y, float z, float w) {
  asm volatile("st.shared.v4.f32 [%0], {%1,%2,%3,%4};" :: "r"(a), "f"(x), "f"(y), "f"(z), "f"(w) : "memory"); }
static __device__ __forceinline__ uint4 lds128(uint32_t a) { uint4 v;
  asm volatile("ld.shared.v4.u32 {%0,%1,%2,%3}, [%4];" : "=r"(v.x), "=r"(v.y), "=r"(v.z), "=r"(v.w) : "r"(a) : "memory"); return v; }
static __device__ __forceinline__ float4 lds128f(uint32_t a) { float4 v;
  asm volatile("ld.shared.v4.f32 {%0,%1,%2,%3}, [%4];" : "=f"(v.x), "=f"(v.y), "=f"(v.z), "=f"(v.w) : "r"(a) : "memory"); return v; }
static __device__ __forceinline__ void sts32(uint32_t a, uint32_t x) { asm volatile("st.shared.u32 [%0], %1;" :: "r"(a), "r"(x) : "memory"); }
static __device__ __forceinline__ void sts64f(uint32_t a, float x, float y) { asm volatile("st.shared.v2.f32 [%0], {%1,%2};" :: "r"(a), "f"(x), "f"(y) : "memory"); }
static __device__ __forceinline__ uint2 lds64(uint32_t a) { uint2 v;
  asm volatile("ld.shared.v2.u32 {%0,%1}, [%2];" : "=r"(v.x), "=r"(v.y) : "r"(a) : "memory"); return v; }
static __device__ __forceinline__ void st_async4(uint32_t ra, float x, float y, float z, float w, uint32_t rbar) {
  asm volatile("st.async.weak.shared::cluster.mbarrier::complete_tx::bytes.v4.f32 [%0], {%1,%2,%3,%4}, [%5];"
               :: "r"(ra), "f"(x), "f"(y), "f"(z), "f"(w), "r"(rbar) : "memory"); }
static __device__ __forceinline__ void stsm4t(uint32_t a, uint32_t x, uint32_t y, uint32_t z, uint32_t w) {
  asm volatile("stmatrix.sync.aligned.m8n8.x4.trans.shared.b16 [%0], {%1,%2,%3,%4};" :: "r"(a), "r"(x), "r"(y), "r"(z), "r"(w) : "memory"); }
static __device__ __forceinline__ void stsm2t(uint32_t a, uint32_t x, uint32_t y) {
  asm volatile("stmatrix.sync.aligned.m8n8.x2.trans.shared.b16 [%0], {%1,%2};" :: "r"(a), "r"(x), "r"(y) : "memory"); }
static __device__ __forceinline__ uint32_t hfma2(uint32_t a, uint32_t b, uint32_t c) { uint32_t d;
  asm("fma.rn.f16x2 %0, %1, %2, %3;" : "=r"(d) : "r"(a), "r"(b), "r"(c)); return d; }
static __device__ __forceinline__ uint32_t hmax2(uint32_t a, uint32_t b) { uint32_t d;
  asm("max.f16x2 %0, %1, %2;" : "=r"(d) : "r"(a), "r"(b)); return d; }
static __device__ __forceinline__ uint32_t hadd2(uint32_t a, uint32_t b) { uint32_t d;
  asm("add.rn.f16x2 %0, %1, %2;" : "=r"(d) : "r"(a), "r"(b)); return d; }
static __device__ __forceinline__ uint32_t packv(float a, float b, float c, float d) { uint32_t r;
  asm volatile("{\n.reg .f32 x, y;\nadd.f32 x, %1, %2;\nadd.f32 y, %3, %4;\ncvt.rn.bf16x2.f32 %0, y, x;\n}" : "=r"(r) : "f"(a), "f"(b), "f"(c), "f"(d)); return r; }
static __device__ __forceinline__ float ex2v(float a, float b, float c) { float y;
  asm volatile("{\n.reg .f32 x;\nfma.rn.f32 x, %1, %2, %3;\nex2.approx.ftz.f32 %0, x;\n}" : "=f"(y) : "f"(a), "f"(b), "f"(c)); return y; }
static __device__ __forceinline__ uint32_t shfl_x(uint32_t a, int m) { uint32_t d;
  asm volatile("shfl.sync.bfly.b32 %0, %1, %2, 0x1f, 0xffffffff;" : "=r"(d) : "r"(a), "r"(m)); return d; }
static __device__ __forceinline__ void h2f(float& lo, float& hi, uint32_t a) {
  asm volatile("{\n.reg .b16 l, h;\nmov.b32 {l, h}, %2;\ncvt.f32.f16 %0, l;\ncvt.f32.f16 %1, h;\n}" : "=f"(lo), "=f"(hi) : "r"(a)); }
static __device__ __forceinline__ uint4 ldsm4(uint32_t a) { uint4 v;
  asm volatile("ldmatrix.sync.aligned.m8n8.x4.shared.b16 {%0,%1,%2,%3}, [%4];" : "=r"(v.x), "=r"(v.y), "=r"(v.z), "=r"(v.w) : "r"(a) : "memory"); return v; }
static __device__ __forceinline__ uint4 ldsm4t(uint32_t a) { uint4 v;
  asm volatile("ldmatrix.sync.aligned.m8n8.x4.trans.shared.b16 {%0,%1,%2,%3}, [%4];" : "=r"(v.x), "=r"(v.y), "=r"(v.z), "=r"(v.w) : "r"(a) : "memory"); return v; }
static __device__ __forceinline__ uint32_t movm(uint32_t a) { uint32_t d;
  asm volatile("movmatrix.sync.aligned.m8n8.trans.b16 %0, %1;" : "=r"(d) : "r"(a)); return d; }
static __device__ __forceinline__ float u2f(uint32_t v) { return __uint_as_float(v); }
static __device__ __forceinline__ uint32_t nz(uint32_t w) { return w == 0u ? 0x8000u : w; }
static __device__ __forceinline__ uint32_t tagw(uint32_t w, uint32_t t) { uint32_t d;
  asm("lop3.b32 %0, %1, %2, 1, 0xd8;" : "=r"(d) : "r"(w), "r"(t)); return d; }
static __device__ __forceinline__ uint32_t pack_m2(float lo, float hi, uint32_t t) { return tagw(pack_bf16(lo, hi), t); }
static __device__ __forceinline__ uint32_t pack_f16(float lo, float hi) { uint32_t d;
  asm("cvt.rn.satfinite.f16x2.f32 %0, %1, %2;" : "=r"(d) : "f"(hi), "f"(lo)); return d; }
static __device__ __forceinline__ void sum_h4(float& lo, float& hi, uint32_t a, uint32_t b, uint32_t c, uint32_t d) {
  const float2 x = __half22float2(*reinterpret_cast<__half2*>(&a)), y = __half22float2(*reinterpret_cast<__half2*>(&b));
  const float2 z = __half22float2(*reinterpret_cast<__half2*>(&c)), w = __half22float2(*reinterpret_cast<__half2*>(&d));
  lo = (x.x + y.x) + (z.x + w.x); hi = (x.y + y.y) + (z.y + w.y);
}
static __device__ __forceinline__ void add_q3(float& lo, float& hi, uint32_t a, uint32_t b, uint32_t c) {
  uint32_t t;
  asm("{\n.reg .b32 u;\nmul.rn.f16x2 u, %1, %4;\nfma.rn.f16x2 u, %2, %4, u;\nfma.rn.f16x2 %0, %3, %4, u;\n}" : "=r"(t) : "r"(a), "r"(b), "r"(c), "r"(0x34003400u));
  const float2 x = __half22float2(*reinterpret_cast<__half2*>(&t));
  lo += x.x; hi += x.y;
}
static __device__ __forceinline__ uint32_t lds32(uint32_t a) { uint32_t v; asm volatile("ld.shared.u32 %0, [%1];" : "=r"(v) : "r"(a) : "memory"); return v; }
static __device__ __forceinline__ uint32_t addb2(uint32_t a, uint32_t b) { uint32_t d;
  asm("add.rn.bf16x2 %0, %1, %2;" : "=r"(d) : "r"(a), "r"(b)); return d; }
static __device__ __forceinline__ uint32_t mulb2(uint32_t a, uint32_t b) { uint32_t d;
  asm("mul.rn.bf16x2 %0, %1, %2;" : "=r"(d) : "r"(a), "r"(b)); return d; }
static __device__ __forceinline__ uint32_t mulb2v(uint32_t a, uint32_t b) { uint32_t d;
  asm volatile("mul.rn.bf16x2 %0, %1, %2;" : "=r"(d) : "r"(a), "r"(b)); return d; }
static __device__ __forceinline__ uint32_t x3(uint32_t a, uint32_t b, uint32_t t) { uint32_t d;
  asm("lop3.b32 %0, %1, %2, %3, 0x7e;" : "=r"(d) : "r"(a), "r"(b), "r"(t)); return d; }
static __device__ __forceinline__ uint32_t or3(uint32_t a, uint32_t b, uint32_t c) { uint32_t d;
  asm("lop3.b32 %0, %1, %2, %3, 0xfe;" : "=r"(d) : "r"(a), "r"(b), "r"(c)); return d; }
static __device__ __forceinline__ uint32_t bad4(const uint4& u, uint32_t t) { return x3(u.x, u.y, t) | x3(u.z, u.w, t); }
static __device__ __forceinline__ uint32_t bad8(const uint4& u, const uint4& v, uint32_t t) {
  return or3(x3(u.x, u.y, t), x3(u.z, u.w, t), x3(v.x, v.y, t)) | x3(v.z, v.w, t); }
static __device__ __forceinline__ float ex2(float x) { float y; asm("ex2.approx.ftz.f32 %0, %1;" : "=f"(y) : "f"(x)); return y; }
static __device__ __forceinline__ float rcpf(float x) { float y; asm("rcp.approx.ftz.f32 %0, %1;" : "=f"(y) : "f"(x)); return y; }
static __device__ __forceinline__ void mbar_wait(uint32_t bar, int parity) {
  asm volatile("{\n.reg .pred p, q;\n.reg .u32 n;\nmbarrier.try_wait.parity.shared::cta.b64 p, [%0], %1;\n@p bra W_DONE;\nmov.u32 n, 0;\n"
               "W_LOOP:\nmbarrier.try_wait.parity.shared::cta.b64 p, [%0], %1;\nadd.u32 n, n, 1;\nsetp.lt.and.u32 q, n, %2, !p;\n@q bra W_LOOP;\nW_DONE:\n}"
               :: "r"(bar), "r"(parity), "n"(SPIN_LIMIT) : "memory");
}
static __device__ __forceinline__ uint32_t mbar_test(uint32_t bar, int parity) { uint32_t ok;
  asm volatile("{\n.reg .pred p;\nmbarrier.test_wait.parity.shared::cta.b64 p, [%1], %2;\nselp.u32 %0, 1, 0, p;\n}" : "=r"(ok) : "r"(bar), "r"(parity) : "memory"); return ok; }
static __device__ __forceinline__ void mbar_arrive(uint32_t bar) {
  asm volatile("mbarrier.arrive.shared::cta.b64 _, [%0];" :: "r"(bar) : "memory"); }
static __device__ __forceinline__ void mbar_arrive_cluster_rlx(uint32_t raddr) {
  asm volatile("mbarrier.arrive.relaxed.cluster.shared::cluster.b64 _, [%0];" :: "r"(raddr) : "memory"); }
static __device__ __forceinline__ void tma_load_mc(uint32_t dst, const CUtensorMap* tm, int c1, int c2, uint32_t bar) {
#ifdef NOTMA
  if ((NOTMA >> (c2 >> 3)) & 1) asm volatile("mbarrier.complete_tx.relaxed.cta.shared::cta.b64 [%0], 32768;" :: "r"(bar) : "memory"); else
#endif
  asm volatile("cp.async.bulk.tensor.3d.shared::cluster.global.mbarrier::complete_tx::bytes.multicast::cluster [%0], [%1, {%3, %4, %5}], [%2], %6;"
               :: "r"(dst), "l"(tm), "r"(bar), "r"(0), "r"(c1), "r"(c2), "h"((uint16_t)3) : "memory"); }
static __device__ __forceinline__ void cp16(uint32_t dst, const void* src) {
  asm volatile("cp.async.cg.shared.global [%0], [%1], 16;" :: "r"(dst), "l"(src) : "memory"); }
static __device__ __forceinline__ void mma_1688(float (&d)[4], uint32_t a0, uint32_t a1, uint32_t b0) {
  asm volatile("mma.sync.aligned.m16n8k8.row.col.f32.bf16.bf16.f32 {%0,%1,%2,%3}, {%4,%5}, {%6}, {%0,%1,%2,%3};"
               : "+f"(d[0]), "+f"(d[1]), "+f"(d[2]), "+f"(d[3]) : "r"(a0), "r"(a1), "r"(b0)); }
static __device__ __forceinline__ void mma4(float (&d)[4], uint32_t a0, uint32_t a1, uint32_t a2, uint32_t a3, uint32_t b0, uint32_t b1) {
  asm volatile("mma.sync.aligned.m16n8k16.row.col.f32.bf16.bf16.f32 {%0,%1,%2,%3}, {%4,%5,%6,%7}, {%8,%9}, {%0,%1,%2,%3};"
               : "+f"(d[0]), "+f"(d[1]), "+f"(d[2]), "+f"(d[3]) : "r"(a0), "r"(a1), "r"(a2), "r"(a3), "r"(b0), "r"(b1)); }
static __device__ __forceinline__ void mma4z(float (&d)[4], uint32_t a0, uint32_t a1, uint32_t a2, uint32_t a3, uint32_t b0, uint32_t b1) {
  asm volatile("mma.sync.aligned.m16n8k16.row.col.f32.bf16.bf16.f32 {%0,%1,%2,%3}, {%4,%5,%6,%7}, {%8,%9}, {%10,%10,%10,%10};"
               : "=f"(d[0]), "=f"(d[1]), "=f"(d[2]), "=f"(d[3]) : "r"(a0), "r"(a1), "r"(a2), "r"(a3), "r"(b0), "r"(b1), "f"(0.f)); }
static __device__ __forceinline__ void mma4h(float (&d)[4], uint32_t a0, uint32_t a1, uint32_t a2, uint32_t a3, uint32_t b) {
  asm volatile("mma.sync.aligned.m16n8k16.row.col.f32.f16.f16.f32 {%0,%1,%2,%3}, {%4,%5,%6,%7}, {%8,%8}, {%0,%1,%2,%3};"
               : "+f"(d[0]), "+f"(d[1]), "+f"(d[2]), "+f"(d[3]) : "r"(a0), "r"(a1), "r"(a2), "r"(a3), "r"(b)); }
static __device__ __forceinline__ void mma2h(float (&d)[4], uint32_t a0, uint32_t a1, uint32_t b) {
  asm volatile("mma.sync.aligned.m16n8k8.row.col.f32.f16.f16.f32 {%0,%1,%2,%3}, {%4,%5}, {%6}, {%0,%1,%2,%3};"
               : "+f"(d[0]), "+f"(d[1]), "+f"(d[2]), "+f"(d[3]) : "r"(a0), "r"(a1), "r"(b)); }
static __device__ __forceinline__ uint32_t clk32() { uint32_t t; asm volatile("mov.u32 %0, %%clock;" : "=r"(t)); return t; }
static __device__ __forceinline__ uint32_t gt32() { uint32_t t; asm volatile("mov.u32 %0, %%globaltimer_lo;" : "=r"(t)); return t; }
static __device__ __forceinline__ void spin(int clk) { if (clk > 0) { uint32_t t = clk32(); while (clk32() - t < (uint32_t)clk) {} } }
#define FENCE() asm volatile("griddepcontrol.launch_dependents;" ::: "memory")
#define OPAQUE_L(p) asm volatile("" : "+l"(p))
#define OPAQUE_R(p) asm volatile("" : "+r"(p))

template <int KK, int K1, int W0, int NW, int FIRST> struct XR {
  static __device__ __forceinline__ void run(float (&d)[16], const uint32_t (&w)[NW][4], uint32_t b16) {
#ifdef NOWG
    if (KK % NOWG == 0)
#endif
    wgmma_n32_ra<(KK >> 2) * 4096 + (KK & 3) * 32, !FIRST>(d, w[W0 + KK], b16);
    XR<KK + 1, K1, W0, NW, 0>::run(d, w, b16);
  }
};
template <int K1, int W0, int NW, int FIRST> struct XR<K1, K1, W0, NW, FIRST> { static __device__ __forceinline__ void run(float (&)[16], const uint32_t (&)[NW][4], uint32_t) {} };
template <int KK, int K0, int K1, int FIRST> struct XS {
  static __device__ __forceinline__ void run(float (&d)[16], uint32_t a16, uint32_t b16) {
#ifdef NOWG
    if (KK % NOWG == 0)
#endif
    wgmma_n32_ss_ta<(KK - K0) * 2048, (KK >> 2) * 4096 + (KK & 3) * 32, !FIRST>(d, a16, b16);
    XS<KK + 1, K0, K1, 0>::run(d, a16, b16);
  }
};
template <int K0, int K1, int FIRST> struct XS<K1, K0, K1, FIRST> { static __device__ __forceinline__ void run(float (&)[16], uint32_t, uint32_t) {} };

static __device__ bf16 g_h[8 * FF];
static __device__ unsigned int g_sbar;
struct SideParams { const bf16* x; const bf16* w_r; const bf16* w_gate; const bf16* w_up; const bf16* w_down; const bf16* gate_w; const bf16* Wo; };

static __device__ __forceinline__ void side_barrier(unsigned int target) {
  __syncthreads();
  if (threadIdx.x == 0) {
    __threadfence();
    atomicAdd(&g_sbar, 1u);
    int n = 0;
    while (*(volatile unsigned int*)&g_sbar < target) { if (++n > (1 << 22)) { g_err = 50; break; } }
    __threadfence();
  }
  __syncthreads();
}
static __device__ __forceinline__ uint4 ldg_nc(const void* p) { uint4 v;
  asm volatile("ld.global.nc.L1::no_allocate.v4.u32 {%0,%1,%2,%3}, [%4];" : "=r"(v.x), "=r"(v.y), "=r"(v.z), "=r"(v.w) : "l"(p)); return v; }
#ifndef SPD
#define SPD 3
#endif
static __device__ __forceinline__ void l2pf(const void* p) { asm volatile("prefetch.global.L2 [%0];" :: "l"(p)); }
static __device__ __forceinline__ void mm8(float (&acc)[8][4], const bf16* W, const bf16* Wn, int ldw, int nk16, uint32_t abase, uint32_t ring, int lane) {
  const int rw = lane >> 3, ch = lane & 7;
  const bf16* wp = W + (size_t)rw * ldw + ch * 8;
  const uint32_t wd = ring + rw * 128, rd = ring + ((rw & 1) * 8 + ch) * 128;
#define MM_LD(k) do { if ((k) < nk16) { const bf16* q = wp + (size_t)(k) * 16 * ldw; \
    _Pragma("unroll") for (int i = 0; i < 4; i++) cp16(wd + ((k) & 3) * 2048 + i * 512 + ((ch ^ (rw + (i & 1) * 4)) << 4), q + (size_t)(4 * i) * ldw); } \
    asm volatile("cp.async.commit_group;" ::: "memory"); } while (0)
  __syncwarp();
  MM_LD(0); MM_LD(1); MM_LD(2);
#pragma unroll 1
  for (int k = 0; k < nk16; k++) {
    if ((k & 1) == 0) {
      const int kp = k + 4 * SPD;
      const bf16* pf = kp < nk16 ? W + (size_t)(kp * 16) * ldw : Wn ? Wn + (size_t)((kp - nk16) * 16) * ldw : nullptr;
      if (pf) l2pf(pf + (size_t)lane * ldw);
    }
    asm volatile("cp.async.wait_group 2;" ::: "memory");
    __syncwarp();
    MM_LD(k + 3);
    const uint32_t a0 = lds32(abase + k * 32), a2 = lds32(abase + k * 32 + 16);
#pragma unroll
    for (int i = 0; i < 4; i++) {
      const uint4 b = ldsm4t(rd + (k & 3) * 2048 + (((2 * i + (rw >> 1)) ^ ch) << 4));
      mma4(acc[2 * i], a0, 0u, a2, 0u, b.x, b.y); mma4(acc[2 * i + 1], a0, 0u, a2, 0u, b.z, b.w);
    }
  }
}
static __device__ __noinline__ void side_work(const SideParams& P, unsigned char* smem, int q) {
  const int tid = threadIdx.x, lane = tid & 31, warp = tid >> 5, g = lane >> 2, t = lane & 3;
  const uint32_t sb = smem_u32(smem);
  unsigned int* cand = reinterpret_cast<unsigned int*>(smem);
  bf16* xs = reinterpret_cast<bf16*>(smem + 1024);
  float* part = reinterpret_cast<float*>(smem + 65536);
  {
    for (int i = tid; i < 256; i += 384) *reinterpret_cast<uint4*>(smem + 1024 + i * 16) = ldg_nc((i < 128 ? P.gate_w : P.w_r - DM) + i * 8);
    __syncthreads();
#pragma unroll 1
    for (int it = warp; it < 64; it += 12) {
      const bf16* xp = P.x + (size_t)(q * 512 + (it >> 1) * 16 + g) * DM + (it & 1) * 512 + t * 8;
      for (int a = it == warp ? 0 : 1; a < 2 && it + 12 * a < 64; a++)
#pragma unroll
        for (int i = 0; i < 4; i++) l2pf(P.x + (size_t)(q * 512 + (it >> 1) * 16 + a * 96 + i * 4 + (lane >> 3)) * DM + (it & 1) * 512 + (lane & 7) * 64);
      const uint32_t xb = sb + 16384 + warp * 16384 + lane * 16;
#pragma unroll
      for (int i = 0; i < 16; i++) { cp16(xb + i * 1024, xp + i * 32); cp16(xb + i * 1024 + 512, xp + 8 * DM + i * 32); }
      asm volatile("cp.async.commit_group;\ncp.async.wait_group 0;" ::: "memory");
      float sg[4] = {0.f, 0.f, 0.f, 0.f}, sr[4] = {0.f, 0.f, 0.f, 0.f};
#pragma unroll
      for (int i = 0; i < 16; i++) {
        const uint4 gw = lds128(sb + 1024 + (it & 1) * 1024 + i * 64 + t * 16), wr = lds128(sb + 3072 + (it & 1) * 1024 + i * 64 + t * 16);
        const uint4 lo = lds128(xb + i * 1024), hi = lds128(xb + i * 1024 + 512);
        mma4(sr, lo.x, hi.x, lo.y, hi.y, wr.x, wr.y); mma4(sr, lo.z, hi.z, lo.w, hi.w, wr.z, wr.w);
        mma4(sg, mulb2(lo.x, gw.x), mulb2(hi.x, gw.x), mulb2(lo.y, gw.y), mulb2(hi.y, gw.y), 0x3F803F80u, 0x3F803F80u);
        mma4(sg, mulb2(lo.z, gw.z), mulb2(hi.z, gw.z), mulb2(lo.w, gw.w), mulb2(hi.w, gw.w), 0x3F803F80u, 0x3F803F80u);
      }
      if (t == 0) {
        float* pp = reinterpret_cast<float*>(smem + 8192) + (it & 1) * 1024 + (it >> 1) * 16 + g;
        pp[0] = sg[0]; pp[8] = sg[2]; pp[512] = sr[0]; pp[520] = sr[2];
      }
    }
    __syncthreads();
    for (int i = tid; i < 512; i += 384) {
      const float* pp = reinterpret_cast<const float*>(smem + 8192);
      g_gate[q * 512 + i] = rbf(1.f / (1.f + expf(-rbf(pp[i] + pp[1024 + i]))));
      g_r[q * 512 + i] = rbf(pp[512 + i] + pp[1536 + i]);
    }
    for (int i = tid; i < 16 * 896; i += 384) part[i] = 0.f;
  }
#define GU(u) (((u) % 28) / 14 ? P.w_up : P.w_gate) + (size_t)((u) / 28) * 512 * FF + q * 896 + ((u) % 14) * 64
  for (int i = lane; i < 64 * SPD; i += 32) l2pf(GU(warp) + (size_t)i * FF);
  side_barrier(4);
  {
    unsigned int key[8];
#pragma unroll
    for (int i = 0; i < 8; i++) {
      const int tok = (warp & 7) * 256 + i * 32 + lane;
      const uint32_t b = __float_as_uint(__ldcg(&g_r[tok]) + 0.f) >> 16;
      key[i] = (((b & 0x8000u) ? (~b & 0xffffu) : (b | 0x8000u)) << 16) | (uint32_t)(2047 - tok);
    }
    for (int pass = 0; pass < 2; pass++) {
      if (pass == 0 ? warp < 8 : warp == 0) {
        for (int c = 0; c < 8; c++) {
          const unsigned int m = __reduce_max_sync(~0u, max(max(max(key[0], key[1]), max(key[2], key[3])), max(max(key[4], key[5]), max(key[6], key[7]))));
#pragma unroll
          for (int i = 0; i < 8; i++) if (key[i] == m) key[i] = 0u;
          if (lane == 0) cand[pass ? 128 + c : warp * 8 + c] = m;
        }
      }
      __syncthreads();
      if (pass == 0 && warp == 0) {
#pragma unroll
        for (int i = 0; i < 8; i++) key[i] = i < 2 ? cand[i * 32 + lane] : 0u;
      }
    }
    if (q == 0 && tid < 8) g_idx[tid] = 2047 - (int)(cand[128 + tid] & 0xffffu);
    for (int i = tid; i < 1024; i += 384) {
      const int c = i >> 7, tok = 2047 - (int)(cand[128 + c] & 0xffffu);
      *reinterpret_cast<uint4*>(xs + c * (FF + 8) + (i & 127) * 8) = ldg_nc(P.x + (size_t)tok * DM + (i & 127) * 8);
    }
    __syncthreads();
  }
#ifdef NOFFN
  return;
#endif
  const uint32_t abase = sb + 1024 + g * (FF + 8) * 2 + t * 4, ring = sb + 131072 + warp * 8192;
  for (int u = warp; u < 56; u += 12) {
    const int kh = u / 28, mat = (u % 28) / 14, cb = u % 14;
    float acc[8][4];
#pragma unroll
    for (int i = 0; i < 8; i++) acc[i][0] = acc[i][1] = acc[i][2] = acc[i][3] = 0.f;
    mm8(acc, GU(u), u + 12 < 56 ? GU(u + 12) : nullptr, FF, DM / 32, abase + kh * 1024, ring, lane);
    float* pp = part + (mat * 8 + g) * 896 + cb * 64 + 2 * t;
#pragma unroll
    for (int i = 0; i < 8; i++) { atomicAdd(pp + 8 * i, acc[i][0]); atomicAdd(pp + 8 * i + 1, acc[i][1]); }
  }
  for (int i = lane; i < 64 * SPD; i += 32) l2pf(P.w_down + (size_t)((warp >> 2) * 1216 + i) * DM + q * 256 + (warp & 3) * 64);
  __syncthreads();
  for (int i = tid; i < 8 * 896; i += 384) {
    const float ag = rbf(part[i]), au = rbf(part[8 * 896 + i]);
    g_h[(i / 896) * FF + q * 896 + i % 896] = __float2bfloat16(rbf(ag / (1.f + expf(-ag))) * au);
  }
  side_barrier(8);
  for (int i = tid; i < 8 * FF / 8; i += 384) {
    const int c = i / (FF / 8), o = i % (FF / 8);
    *reinterpret_cast<uint4*>(xs + c * (FF + 8) + o * 8) = __ldcg(reinterpret_cast<const uint4*>(g_h + c * FF + o * 8));
  }
  __syncthreads();
  {
    const int cb = warp & 3, kq = warp >> 2;
    float acc[8][4];
#pragma unroll
    for (int i = 0; i < 8; i++) acc[i][0] = acc[i][1] = acc[i][2] = acc[i][3] = 0.f;
    mm8(acc, P.w_down + (size_t)kq * 1216 * DM + q * 256 + cb * 64, nullptr, DM, kq == 2 ? 72 : 76, abase + kq * 1216 * 2, ring, lane);
#pragma unroll
    for (int i = 0; i < 8; i++) { part[(kq * 8 + g) * 256 + cb * 64 + 2 * t + 8 * i] = acc[i][0]; part[(kq * 8 + g) * 256 + cb * 64 + 2 * t + 8 * i + 1] = acc[i][1]; }
    __syncthreads();
    for (int i = tid; i < 2048; i += 384) {
      const int c = i >> 8, tok = 2047 - (int)(cand[128 + c] & 0xffffu);
      const float y = (part[i] + part[2048 + i]) + part[4096 + i];
      const float rs = rbf(1.f / (1.f + expf(-__ldcg(&g_r[tok]))));
      g_upd[c * DM + q * 256 + (i & 255)] = __float2bfloat16(rbf(y) * rs);
    }
  }
}
struct RecParams { const bf16* mem0; unsigned char* win; };
struct WMaps { CUtensorMap q, k, v; };
#ifndef RLX
#define RLX 1
#endif
#ifndef DLY_SIDE
#define DLY_SIDE 16000
#endif
#ifndef WSPL
#define WSPL 1
#endif

#ifndef DLY_S
#define DLY_S 270
#endif
#ifndef DLY_V
#define DLY_V 300
#endif
#ifndef DLY_M3
#define DLY_M3 560
#endif
#ifndef RF_FAT
#define RF_FAT 208
#endif
#ifndef RF_CTL
#define RF_CTL 88
#endif
#ifndef NCH
#define NCH 2
#endif
#ifndef WPF
#define WPF 7
#endif
#ifndef WRF
#define WRF 7
#endif
#ifndef VPF
#define VPF 2
#endif
#ifndef DLY_WO
#define DLY_WO 720
#endif
#ifndef XPF
#define XPF 4
#endif
#ifndef DLY_FA
#define DLY_FA 50
#endif
#ifndef DLY_XL
#define DLY_XL 400
#endif
#ifndef NPROBE
#define NPROBE 3
#endif
#ifndef O2P
#define O2P 2
#endif
#ifndef WS
#define WS 0
#endif
#ifndef NOB
#define NOB 2
#endif
#ifndef XG
#define XG 1
#endif
#ifndef VAL
#define VAL 0
#endif
#ifndef WPA0
#define WPA0 0
#endif
#ifndef WPA1
#define WPA1 WPA
#endif
#ifndef PG
#define PG 0
#endif
#ifndef LPF
#define LPF 0
#endif
#ifndef DLY_LQ
#define DLY_LQ 0
#endif
#ifndef DLY_LP
#define DLY_LP 0
#endif
#ifndef BP
#define BP 0
#endif
#ifndef NG
#define NG 0
#endif
#ifndef VE
#define VE 1
#endif
#ifndef PA
#define PA 1
#endif
#ifndef KU
#define KU 32
#endif
#ifndef KD
#define KD 4
#endif
#ifndef DLY_RR
#define DLY_RR 500
#endif
#ifndef GW
#define GW 0
#endif
#ifndef BI
#define BI 1
#endif
#ifndef BR
#define BR 8
#endif
#ifndef BG
#define BG 1
#endif
#ifndef VI
#define VI 1
#endif
#ifndef DLY_VI
#define DLY_VI 0
#endif
#ifndef F0W
#define F0W 0
#endif
#ifndef DLY_B
#define DLY_B 0
#endif
#ifndef BGT
#define BGT 0
#endif
#ifndef EG
#define EG 0
#endif
#ifndef W0I
#define W0I 0
#endif
#ifndef XH
#define XH 1
#endif
#ifndef F1L
#define F1L 1
#endif
#ifndef QB
#define QB 0
#endif
#ifndef LN
#define LN 0
#endif
#ifndef NSW
#define NSW 0
#endif
#ifndef EPI
#define EPI 0
#endif
#ifndef PXE
#define PXE 0
#endif
#ifndef GF
#define GF 12
#endif
#ifndef WNS
#define WNS -1
#endif
#ifndef DLY_NW
#define DLY_NW 0
#endif
#ifndef ETW
#define ETW 0
#endif
#ifndef KB
#define KB 8
#endif
#ifndef H16
#define H16 1
#endif
#ifndef DLY_N
#define DLY_N 0
#endif
#ifndef F1C
#define F1C 2
#endif
#ifndef KA
#define KA 0
#endif
#define KEEP() do { float kd[4]; mma4z(kd, 0u, 0u, 0u, 0u, 0u, 0u); } while (0)
#ifndef WKA
#define WKA 8
#endif
#ifndef WPA
#define WPA 3
#endif
#ifndef F0T
#define F0T 1
#endif
#ifndef DLY_K
#define DLY_K 1248
#endif
#ifndef DLY_KS
#define DLY_KS 850
#endif
#ifndef DLY_E
#define DLY_E 0
#endif
#ifndef DLY_PF
#define DLY_PF 10
#endif
#ifndef DLY_F0
#define DLY_F0 300
#endif
#ifndef DLY_XD
#define DLY_XD 200
#endif
#ifndef DLY_PX
#define DLY_PX 60
#endif
#ifndef DLY_TB
#define DLY_TB 700
#endif
#if 1
#define NTUNE 10
#define TUNE_NAMES {"OM3", "XL", "S", "NW", "WO", "PX", "V", "OK", "OKS", "ORR"}
__constant__ int g_tune[NTUNE] = {DLY_M3, DLY_XL, DLY_S, DLY_NW, DLY_WO, DLY_PX, DLY_V, DLY_K, DLY_KS, DLY_RR};
#undef DLY_M3
#define DLY_M3 g_tune[0]
#undef DLY_XL
#define DLY_XL g_tune[1]
#undef DLY_S
#define DLY_S g_tune[2]
#undef DLY_NW
#define DLY_NW g_tune[3]
#undef DLY_WO
#define DLY_WO g_tune[4]
#undef DLY_PX
#define DLY_PX g_tune[5]
#undef DLY_V
#define DLY_V g_tune[6]
#undef DLY_K
#define DLY_K g_tune[7]
#undef DLY_RR
#define DLY_RR g_tune[9]
#undef DLY_KS
#define DLY_KS g_tune[8]
#endif
#ifdef PRO
__device__ unsigned g_pro[NCTA][16];
#define PT(i, c) do { if (c) g_pro[cta][i] = gt32(); } while (0)
#else
#define PT(i, c)
#endif
#ifdef PROBE
__constant__ int g_probe[16];
#define PRB(i) spin(g_probe[i])
#else
#define PRB(i)
#endif
#ifdef PER
__device__ unsigned g_pk[NCTA][64], g_pclk[NCTA][64], g_per[NCTA][64], g_end[8] = {0, 0, 0, 0, 0, 0, 0, 100000};
#endif
#define ADD3(a, b, c) addb2(addb2(a, c), b)
#define STR2(x) #x
#define STR(x) STR2(x)

static __device__ __forceinline__ void cp16p(uint32_t dst, const void* src, uint32_t v) {
  asm volatile("{\n.reg .pred q;\nsetp.ne.u32 q, %2, 0;\n@q cp.async.cg.shared.global [%0], [%1], 16;\n}" :: "r"(dst), "l"(src), "r"(v) : "memory"); }
static __device__ __forceinline__ void red_bf2(void* p, uint32_t v) {
  asm volatile("red.relaxed.gpu.global.add.noftz.bf16x2 [%0], %1;" :: "l"(p), "r"(v) : "memory"); }
static __device__ __forceinline__ void red_bf2p(void* p, uint32_t v, uint32_t e) {
  asm volatile("{\n.reg .pred q;\nsetp.lt.u32 q, %2, 2;\n@q red.relaxed.gpu.global.add.noftz.bf16x2 [%0], %1;\n}" :: "l"(p), "r"(v), "r"(e) : "memory"); }
static __device__ __forceinline__ void red_bf2p4(void* p, uint32_t v, uint32_t e) {
  asm volatile("{\n.reg .pred q;\nsetp.lt.u32 q, %2, 4;\n@q red.relaxed.gpu.global.add.noftz.bf16x2 [%0], %1;\n}" :: "l"(p), "r"(v), "r"(e) : "memory"); }
static __device__ __forceinline__ void eta2(void* p, uint32_t t, uint32_t first, uint32_t l16) {
  asm volatile("{\n.reg .pred q;\nsetp.lt.u32 q, %3, 32;\n@q red.relaxed.gpu.global.max.u32 [%0+4], %1;\n@q red.relaxed.gpu.global.add.u32 [%0], %2;\n}" :: "l"(p), "r"(t), "r"(first), "r"(l16) : "memory"); }
static __device__ __forceinline__ void sts16(uint32_t a, uint32_t x) { asm volatile("{\n.reg .b16 h;\ncvt.u16.u32 h, %1;\nst.shared.u16 [%0], h;\n}" :: "r"(a), "r"(x) : "memory"); }
static __device__ __forceinline__ uint32_t cnt_word(uint32_t L) { return (L & 17u) | ((L & 6u) << 1) | ((L & 8u) >> 2); }
static __device__ __forceinline__ uint32_t cnt_line(uint32_t l) { return (l & 17u) | ((l & 12u) >> 1) | ((l & 2u) << 2); }
static __device__ __forceinline__ int m3_check(uint32_t sb, const unsigned char* p3, const unsigned char* pd, int dq, uint32_t l16, uint32_t mc, int hf, int s) {
  const uint32_t md = l16 + (sb + SM_MEM + hf * 8192), dd = l16 + (sb + SM_RD + hf * 256), dc = (l16 >> 2) + (sb + SM_RD + hf * 256);
  int n = 0;
  uint32_t c0 = 0, c1 = 0, d0 = 0, d1 = 0;
#pragma unroll 1
  do {
    if (n) {
      const int src = cnt_word(l16 >> 4);
      const uint32_t m0 = __ballot_sync(~0u, (__shfl_sync(~0u, c0, src) >> 16) != 0x4200u) >> (l16 >> 7), m1 = __ballot_sync(~0u, (__shfl_sync(~0u, c1, src) >> 16) != 0x4200u) >> (l16 >> 7);
      const uint32_t m2 = __ballot_sync(~0u, (d0 >> 16) != 0x4200u), m3 = __ballot_sync(~0u, (d1 >> 16) != 0x4200u);
#pragma unroll
      for (int i = 0; i < 8; i++) { cp16p(md + i * 512, p3 + i * 1024, m0 & (1u << (4 * i))); cp16p(md + 4096 + i * 512, p3 + dq + i * 1024, m1 & (1u << (4 * i))); }
      cp16p(dd, pd, l16 < 256u ? (((l16 & 128u) ? m3 : m2) >> ((l16 >> 2) & 28u)) & 15u : 0u);
      sts32(sb + SM_Z + 40, s);
      asm volatile("cp.async.commit_group;\ncp.async.wait_group 0;" ::: "memory");
      __syncwarp();
    }
    n++;
    mbar_wait(sb + SM_BAR + MB_G + hf * 8, s & 1);
    c0 = lds32(mc); c1 = lds32(mc + 4096); d0 = lds32(dc); d1 = lds32(dc + 128);
  } while (__any_sync(~0u, (x3(c0, c1, 0x42000000u) | x3(d0, d1, 0x42000000u)) >= 0x10000u) && n < SPIN_LIMIT);
  PRB(4);
  sts16(mc + 2, d0); sts16(mc + 4098, d1);
  mbar_arrive(sb + SM_BAR + MB_MEM + hf * 8);
  return n - 1;
}

__global__ void __cluster_dims__(2, 1, 1) __launch_bounds__(384, 1)
rec_kernel(const __grid_constant__ CUtensorMap tmx, const __grid_constant__ CUtensorMap tmw, const __grid_constant__ WMaps W, RecParams P, const __grid_constant__ SideParams SP) {
  extern __shared__ __align__(1024) unsigned char smem[];
  asm volatile("griddepcontrol.launch_dependents;");
  const uint32_t sb = smem_u32(smem);
  const int tid = threadIdx.x, lane = tid & 31, t128 = tid & 127;
  const int wg = __shfl_sync(~0u, tid >> 7, 0), wq = __shfl_sync(~0u, (tid >> 5) & 3, 0);
  const int r = blockIdx.x & 1, pp = blockIdx.x >> 1;
  const int mi = lane >> 3, r8 = lane & 7;
  const uint32_t xb16 = __shfl_sync(~0u, (((sb + SM_X + (tid >> 7) * 32768 + r * 16384) & 0x3FFFF) >> 4) | (1u << 16), 0);
  const uint32_t va16 = __shfl_sync(~0u, (((sb + SM_WVS + (tid >> 7) * 16384) & 0x3FFFF) >> 4) | (64u << 16), 0);
#if defined(PER) || defined(PRO)
  const uint32_t tstart = gt32();
#endif

  if (tid == 0) {
    mbar_init(sb + SM_BAR + MB_F, BGT == 2 ? 8 : BGT == 1 ? 4 : 1); mbar_init(sb + SM_BAR + MB_F + 8, 1); mbar_init(sb + SM_BAR + MB_XE0, 2); mbar_init(sb + SM_BAR + MB_XE1, 2); mbar_init(sb + SM_BAR + MB_INIT, 2);
    mbar_init(sb + SM_BAR + MB_MEM, 32); mbar_init(sb + SM_BAR + MB_MEM + 8, 32); for (int i = 0; i < 8; i++) mbar_init(sb + SM_BAR + MB_W + i * 8, 1);
    mbar_init(sb + SM_BAR + MB_XF, 8); mbar_init(sb + SM_BAR + MB_X0, 1); mbar_init(sb + SM_BAR + MB_WO, 1); mbar_init(sb + SM_BAR + MB_VR, 5); mbar_init(sb + SM_BAR + MB_G, 32); mbar_init(sb + SM_BAR + MB_G + 8, 32);
    sts32(sb + SM_Z + 40, ~0u);
    asm volatile("fence.mbarrier_init.release.cluster;" ::: "memory");
  }
  if (tid >= 64 && tid < 96) {
    const uint32_t l16 = lane * 16, qa = ((l16 & 0x30u) << 3) | ((l16 & 0x10u) << 2) | ((l16 >> 3) & 0x30u) | ((l16 >> 4) & 4u);
    sts128(sb + SM_QA + l16, qa + (sb + SM_QKP), (qa ^ 64u) + (sb + SM_QKP), 0u, 0u);
  }
  if (tid == 32) {
    asm volatile("prefetch.tensormap [%0];" :: "l"(&W.q) : "memory"); asm volatile("prefetch.tensormap [%0];" :: "l"(&W.k) : "memory");
    asm volatile("prefetch.tensormap [%0];" :: "l"(&W.v) : "memory"); asm volatile("prefetch.tensormap [%0];" :: "l"(&tmx) : "memory");
  }
  if (tid >= 256 && tid < 320) {
    unsigned char* pl = P.win + r * W_2 + (W_UP | (1u << 19) | ((pp >> 5) << 14)) + (pp & 31) * 128 + wq * 4096;
    stg_r1(pl + lane * 4, 0u);
    uint32_t best = 1u << 30;
    if (lane == 0) {
#pragma unroll 1
      for (int rep = 0; rep < NPROBE; rep++) {
        uint32_t dt;
        asm volatile("{\n.reg .u32 a, b, v;\nmov.u32 a, %%clock;\natom.relaxed.gpu.global.exch.b32 v, [%1], 0;\n"
                     "st.volatile.shared.u32 [%2], v;\nmov.u32 b, %%clock;\nsub.u32 %0, b, a;\n}" : "=r"(dt) : "l"(pl), "r"(sb + SM_SIDE + wq * 4) : "memory");
        best = min(best, dt);
      }
    }
    if (lane == 0) sts32(sb + SM_SIDE + wq * 4, best);
    bar_sync(B_P, 64);
    if (wq == 0) {
      const uint2 bt = lds64(sb + SM_SIDE);
      if (lane < 8 && (r == 0 || pp == 0)) stg_r1(&g_side[(r ? 66 : pp) * 32 + lane], 2u | (bt.x < bt.y ? 1u : 0u));
      spin(DLY_TB);
      uint32_t a, b, c; int n = 0;
#pragma unroll 1
      do {
        a = ldg_r1(&g_side[lane * 32]); b = ldg_r1(&g_side[(32 + lane) * 32]); c = ldg_r1(&g_side[(64 + min(lane, 2)) * 32]);
      } while (!__all_sync(~0u, a & b & c & 2u) && ++n < SPIN_LIMIT);
      a = __ballot_sync(~0u, a & 1u); b = __ballot_sync(~0u, b & 1u); c = __ballot_sync(~0u, c & 1u);
      const uint32_t pol2 = (a ^ (c >> 2)) & 1u;
      c &= 3u;
      const unsigned long long ab = ((unsigned long long)b << 32) | a;
      const int sd = pp < 64 ? (int)(ab >> pp) & 1 : (int)(c >> (pp - 64)) & 1;
      const int n1 = __popcll(ab) + __popc(c), n0 = 66 - n1;
      const int below1 = pp < 64 ? __popcll(ab & ((1ull << pp) - 1)) : __popcll(ab) + (pp == 65 ? (int)(c & 1u) : 0);
      const int rk = sd ? below1 : pp - below1;
      const int k0 = (n0 & 1) ? n0 - 1 : n0 >= n1 ? n0 - 2 : n0, k1 = 64 - k0;
      const int role = rk >= (sd ? k1 : k0) ? 64 + ((n0 & 1) ? sd : rk - (sd ? k1 : k0)) : sd ? k0 + rk : rk;
      __syncwarp();
      if (lane == 0) sts128(sb + SM_SIDE, 2 * k0, 0u, pol2, role * 2 + r);
#ifdef PER
      if (lane == 0) { atomicMax(&g_end[6], gt32()); atomicMin(&g_end[7], max(bt.x, bt.y) - min(bt.x, bt.y)); }
#endif
    }
  }
  __syncthreads();
  const int cta = __shfl_sync(~0u, (int)lds32(sb + SM_SIDE + 12), 0), h = cta >> 2, j = cta & 3, p = j >> 1;
  const int sw = (cta >= __shfl_sync(~0u, (int)lds32(sb + SM_SIDE), 0) ? 1 : 0) ^ r ^ NSW;
  if (cta >= NCTA) {
    spin(DLY_SIDE);
#ifndef NOSIDE
    side_work(SP, smem, cta - NCTA);
#endif
#ifdef PER
    if (threadIdx.x == 0) atomicMax(&g_end[1], gt32());
#endif
    return;
  }
#ifdef PER
  if (threadIdx.x == 0) g_per[cta][63] = tstart;
#endif
#ifdef PRO
  if (tid == 0) { g_pro[cta][0] = tstart; g_pro[cta][1] = gt32(); }
#endif
  asm volatile("barrier.cluster.arrive.relaxed.aligned;" ::: "memory");
#define WLOAD(i0, i1) _Pragma("unroll 1") for (int u = i0; u < i1; u++) {        \
    const int g2 = u >> 2, i = u & 3, k = g2 * 512 + ((i * 128 + r * 256) & 511); \
    const uint32_t mb = sb + SM_BAR + MB_W + u * 8; \
    mbar_expect_tx(mb, i < 2 ? 32768 : 16384); \
    tma_load_2d(sb + g2 * 65536 + i * 8192, &W.q, h * DH + j * 32, k, mb); \
    tma_load_2d(sb + g2 * 65536 + 32768 + i * 8192, &W.k, h * DH + j * 32, k, mb); \
    if (i < 2) tma_load_2d(sb + (i ? SM_WVS : SM_VST) + g2 * 16384, &W.v, h * DH + p * 64, k, mb); }
  if (tid == 288) {
    mbar_expect_tx(sb + SM_BAR + MB_X0, 32768);
#pragma unroll 1
    for (int i = 0; i < 2; i++)
      asm volatile("cp.async.bulk.tensor.3d.shared::cluster.global.mbarrier::complete_tx::bytes [%0], [%1, {%3, %3, %4}], [%2];"
                   :: "r"(sb + SM_MEM + i * 16384), "l"(&tmx), "r"(sb + SM_BAR + MB_X0), "r"(0), "r"(i * 4) : "memory");
    WLOAD(0, 4 + WSPL);
  }
  __syncwarp();
  asm volatile("barrier.cluster.wait.acquire.aligned;" ::: "memory");
#define SIDES() const uint4 sm2 = lds128(sb + SM_SIDE); const int nlo = sm2.x; const uint32_t me = cta >= nlo

#define XLOAD(t, sg) tma_load_mc(sb + SM_X + ((t) * 8 + r * 4) * 4096, &tmx, (sg) * SEG, (t) * 8 + r * 4, sb + SM_BAR + MB_F + (t) * 8)
#define F0LOAD() do { mbar_wait(sb + SM_BAR + MB_XE0, s & 1); \
    if (l16 == 0) XLOAD(0, s + 2); \
    __syncwarp(); } while (0)
  if (wg < 2) {
    asm volatile("setmaxnreg.inc.sync.aligned.u32 " STR(RF_FAT) ";");
    uint32_t w[32][4], wv[8][4];
    uint32_t lm = ((mi >> 1) * 8 + r8) * 128 + (((wq * 2 + (mi & 1)) ^ r8) << 4), l16 = lane * 16;
    lm = __shfl_sync(~0u, lm, lane); l16 = __shfl_sync(~0u, l16, lane);
    {
      const uint32_t lq0 = sb + wg * 65536 + (wq >> 1) * 32768 + ((mi >> 1) * 8 + r8) * 64 + ((((wq & 1) * 2 + (mi & 1)) ^ (r8 >> 1)) << 4);
      const uint32_t f = wq < 2 ? 0x3D003D00u : 0x3F803F80u;
#pragma unroll
      for (int i = 0; i < 4; i++) {
        mbar_wait(sb + SM_BAR + MB_W + (wg * 4 + i) * 8, 0);
        if (i == 3) PT(2 + wg, t128 == 0);
#pragma unroll
        for (int kk = 8 * i; kk < 8 * i + 8; kk++) ldmatrix_x4_trans(w[kk], lq0 + kk * 1024);
        if (i == 0) {
#pragma unroll
          for (int kk = 0; kk < 8; kk++) ldmatrix_x4_trans(wv[kk], sb + SM_VST + wg * 16384 + kk * 2048 + lm);
        }
#pragma unroll
        for (int kk = 32 * i; kk < 32 * i + 32; kk++) w[kk >> 2][kk & 3] = mulb2v(w[kk >> 2][kk & 3], f);
      }
    }
    if (wg == 0) bar_sync(B_V, 160);
    else bar_arrive(B_P, 160);
    const int w8 = wg * 4 + wq;
    const int cw = sw ^ wg, near = wg ^ 1 ^ NSW;
    const uint32_t xh16 = xb16 ^ 1024u;
    const uint32_t rsb = mapa(sb, r ^ 1);
#define MT (l16 + (sb + SM_MEM + wg * 8192))
#define WA (lm + (sb + SM_WVS + wg * 16384))
#if WS
#define WOF(f) (lm + (sb + SM_WOS + wg * 32768 + (f) * 2048))
#else
#define WOF(f) (lm + (sb + SM_WOS + wg * 32768 + ((f) & 1) * 16384 + ((f) >> 1) * 2048))
#endif
#define TH(base) (l16 + (sb + (base) + w8 * 512))
#define TQ(base) (l16 + (sb + (base) + wq * 512))
#define DUMP(base) _Pragma("unroll") for (int n = 0; n < 4; n++) sts128f(TQ((base) + n * 2048), d[4 * n], d[4 * n + 1], d[4 * n + 2], d[4 * n + 3])
#define INIT(base) _Pragma("unroll") for (int n = 0; n < 4; n++) { const float4 t = lds128f(TQ((base) + n * 2048)); d[4 * n] = t.x; d[4 * n + 1] = t.y; d[4 * n + 2] = t.z; d[4 * n + 3] = t.w; }
#define XQK(first, b0, b1) do { wg_fence(); XR<0, 16, 0, 32, first>::run(d, w, b0); XR<0, 16, 16, 32, 0>::run(d, w, b1); wg_commit(); wg_wait0(); } while (0)
#define XVS(first, b0) do { wg_fence(); XS<8, 8, 16, first>::run(d, va16, b0); XR<0, 8, 0, 8, 0>::run(d, wv, b0); wg_commit(); wg_wait0(); } while (0)
#define XVR(first, b0) do { wg_fence(); XR<0, 8, 0, 8, first>::run(d, wv, b0); XS<8, 8, 16, 0>::run(d, va16, b0); wg_commit(); wg_wait0(); } while (0)
#define XREL(mb) do { if (wq == 0 && l16 == 0) { mbar_arrive_cluster_rlx(rsb + SM_BAR + (mb)); mbar_arrive(sb + SM_BAR + (mb)); } } while (0)
#define XFOUT() do { \
          _Pragma("unroll") for (int hf = 0; hf < 2; hf++) \
            stsm4t(l16 + (sb + SM_XF + (wq * 2 + hf) * 512), pack_bf16(d[8 * hf], d[8 * hf + 1]), pack_bf16(d[8 * hf + 2], d[8 * hf + 3]), \
                   pack_bf16(d[8 * hf + 4], d[8 * hf + 5]), pack_bf16(d[8 * hf + 6], d[8 * hf + 7])); \
          __syncwarp(); \
          if (l16 < 32) mbar_arrive(sb + SM_BAR + MB_XF); } while (0)
#define VDUMP(base) _Pragma("unroll") for (int n = 0; n < 2; n++) sts128(TQ((base) + n * 2048), pack_bf16(d[8 * n], d[8 * n + 1]), pack_bf16(d[8 * n + 2], d[8 * n + 3]), pack_bf16(d[8 * n + 4], d[8 * n + 5]), pack_bf16(d[8 * n + 6], d[8 * n + 7]))
#define ADDIN(base) _Pragma("unroll") for (int n = 0; n < 4; n++) { const float4 t = lds128f(TQ((base) + n * 2048)); d[4 * n] += t.x; d[4 * n + 1] += t.y; d[4 * n + 2] += t.z; d[4 * n + 3] += t.w; }
    if (wg == 0) {
      float d[16];
      const uint32_t x0 = (((sb + SM_MEM + r * 16384) & 0x3FFFF) >> 4) | (1u << 16), x1 = (((sb + SM_MEM + (r ^ 1) * 16384) & 0x3FFFF) >> 4) | (1u << 16);
      mbar_wait(sb + SM_BAR + MB_X0, 0);
      XQK(1, x0, x1);
      DUMP(SM_CQ);
      XVS(1, x0);
      bar_arrive(B_X2, 256);
      VDUMP(SM_CV);
      bar_sync(B_CQ, 256);
    } else {
      float d[16];
      bar_sync(B_CQ, 256);
      INIT(SM_CQ);
      mbar_wait(sb + SM_BAR + MB_F + 8, 0);
      PT(4, t128 == 0);
      XQK(0, xb16, xh16);
      XFOUT();
      PT(5, t128 == 0);
    }
    if (wg == 0) mbar_wait(sb + SM_BAR + MB_F, 0);
    for (int s = -1;; s++) {
      if (s >= 0) {
        OPAQUE_R(lm); OPAQUE_R(l16);
        {
          uint32_t sa[4][4];
#pragma unroll
          for (int i = 0; i < VPF; i++) ldmatrix_x4_trans(sa[i], WA + i * 2048);
          float a[2][4], v[2][4]; uint4 c[4]; uint2 qa;
          FENCE();
          mbar_wait(sb + SM_BAR + MB_MEM + wg * 8, s & 1);
#define QP(i) ((i) >= 12 ? (i) - 8 : (i) % 3 == 1 ? (i) / 3 : 8 + (i) - ((i) + 2) / 3)
#pragma unroll
          for (int i = 0; i < 3; i++) c[i] = ldsm4t(MT + QP(i) * 512);
#pragma unroll
          for (int i = 0; i < 16; i++) {
            if (i + 3 < 16) c[(i + 3) & 3] = ldsm4t(MT + QP(i + 3) * 512);
            if (i == 13) qa = lds64(l16 + (sb + SM_QA));
            if (i == 0) {
              mma4z(a[0], w[2 * QP(i)][0], w[2 * QP(i)][1], w[2 * QP(i)][2], w[2 * QP(i)][3], c[i & 3].x, c[i & 3].y);
              mma4z(a[1], w[2 * QP(i) + 1][0], w[2 * QP(i) + 1][1], w[2 * QP(i) + 1][2], w[2 * QP(i) + 1][3], c[i & 3].z, c[i & 3].w);
            } else {
              mma_16816(a[0], w[2 * QP(i)], c[i & 3].x, c[i & 3].y);
              mma_16816(a[1], w[2 * QP(i) + 1], c[i & 3].z, c[i & 3].w);
            }
            if (QP(i) == 0) {
              mma4z(v[0], wv[0][0], wv[0][1], wv[0][2], wv[0][3], c[i & 3].x, c[i & 3].y);
              mma4z(v[1], wv[1][0], wv[1][1], wv[1][2], wv[1][3], c[i & 3].z, c[i & 3].w);
            } else if (QP(i) < 4) {
              mma_16816(v[0], wv[2 * (QP(i) & 3)], c[i & 3].x, c[i & 3].y);
              mma_16816(v[1], wv[2 * (QP(i) & 3) + 1], c[i & 3].z, c[i & 3].w);
            }
            if (VE && i == 12) {
              mma_16816(v[0], sa[0], c[0].x, c[0].y); mma_16816(v[1], sa[1], c[0].z, c[0].w);
            }
            if (VE && i == 13) { ldmatrix_x4_trans(sa[0], WA + 2 * 2048); ldmatrix_x4_trans(sa[1], WA + 3 * 2048); ldmatrix_x4_trans(sa[2], WA + 4 * 2048); }
            FENCE();
          }
#pragma unroll
          for (int i = 0; i < 4; i++) sts32(((i & 1) ? qa.y : qa.x) + (w8 * 512 + (i >> 1) * 8), f2u(a[0][i] + a[1][i]));
          bar_arrive(B_QK, 288);
          bar_arrive(B_QK1, 288);
          FENCE();
#if VE
          uint32_t sc2[4];
          ldmatrix_x4_trans(sa[3], WA + 5 * 2048); ldmatrix_x4_trans(sc2, WA + 6 * 2048);
          mma_16816(v[0], sa[0], c[1].x, c[1].y); mma_16816(v[1], sa[1], c[1].z, c[1].w);
          FENCE();
          ldmatrix_x4_trans(sa[0], WA + 7 * 2048);
          FENCE();
          mma_16816(v[0], sa[2], c[2].x, c[2].y); mma_16816(v[1], sa[3], c[2].z, c[2].w);
          mma_16816(v[0], sc2, c[3].x, c[3].y); mma_16816(v[1], sa[0], c[3].z, c[3].w);
          FENCE();
#else
#pragma unroll
          for (int i = VPF; i < 4; i++) ldmatrix_x4_trans(sa[i], WA + i * 2048);
          FENCE();
#pragma unroll
          for (int i = 0; i < 4; i++) {
            mma_16816(v[0], sa[(2 * i) & 3], c[i].x, c[i].y);
            mma_16816(v[1], sa[(2 * i + 1) & 3], c[i].z, c[i].w);
            if (i < 2) { ldmatrix_x4_trans(sa[2 * i], WA + (4 + 2 * i) * 2048); ldmatrix_x4_trans(sa[2 * i + 1], WA + (5 + 2 * i) * 2048); }
            FENCE();
          }
#endif
          sts128f(TH(SM_VP), v[0][0] + v[1][0], v[0][1] + v[1][1], v[0][2] + v[1][2], v[0][3] + v[1][3]);
          bar_arrive(B_V, 320);
        }
        if (s == NSEG - 1) break;
        OPAQUE_R(lm); OPAQUE_R(l16);
        uint32_t wo[WPF][4];
        {
          float d[16];
#define XOUT(g) _Pragma("unroll") for (int n = 0; n < 2; n++) sts128f(TQ(SM_CQ + ((g) * 2 + n) * 2048), d[8 - 8 * (g) + 4 * n], d[9 - 8 * (g) + 4 * n], d[10 - 8 * (g) + 4 * n], d[11 - 8 * (g) + 4 * n])
#define XIN(g) do { \
            const float4 t0 = lds128f(TQ(SM_CQ + (2 - 2 * (g)) * 2048)), t1 = lds128f(TQ(SM_CQ + (3 - 2 * (g)) * 2048)); \
            stsm4t(l16 + (sb + SM_XF + (wq * 2 + (g)) * 512), pack_bf16(d[8 * (g)] + t0.x, d[8 * (g) + 1] + t0.y), pack_bf16(d[8 * (g) + 2] + t0.z, d[8 * (g) + 3] + t0.w), \
                   pack_bf16(d[8 * (g) + 4] + t1.x, d[8 * (g) + 5] + t1.y), pack_bf16(d[8 * (g) + 6] + t1.z, d[8 * (g) + 7] + t1.w)); } while (0)
          if (wg == 0) {
            INIT(SM_CW);
            bar_sync(B_PUB, 320);
            wg_fence();
            XR<KB, 16, 0, 32, 0>::run(d, w, xb16); XR<0, 16, 16, 32, 0>::run(d, w, xh16);
            wg_commit(); wg_wait0();
            TSF(13, 1);
            OPAQUE_R(l16);
            XOUT(0);
            bar_arrive(B_G1, 256);
            XREL(MB_XE0);
#pragma unroll
            for (int f = 0; f < WPA0; f++) ldmatrix_x4_trans(wo[f], WOF(f));
            bar_sync(B_CQ, 256);
            XIN(0);
#pragma unroll
            for (int f = WPA0; f < WPA; f++) ldmatrix_x4_trans(wo[f], WOF(f));
          } else {
            const uint32_t ok = mbar_test(sb + SM_BAR + MB_F + 8, (s + 1) & 1);
            bar_sync(B_PUB, 320);
            if (!ok) mbar_wait(sb + SM_BAR + MB_F + 8, (s + 1) & 1);
            wg_fence();
            XR<0, 16, 0, 32, 1>::run(d, w, xb16); XR<0, 16, 16, 32, 0>::run(d, w, xh16);
            wg_commit();
#pragma unroll
            for (int f = 0; f < WPA1; f++) ldmatrix_x4_trans(wo[f], WOF(f));
            wg_wait0();
            TSF(31, 5);
            OPAQUE_R(l16);
            XOUT(1);
            bar_arrive(B_CQ, 256);
            bar_sync(B_G1, 256);
            XIN(1);
#pragma unroll
            for (int f = WPA1; f < WPA; f++) ldmatrix_x4_trans(wo[f], WOF(f));
          }
          __syncwarp();
          if (l16 == 0) mbar_arrive(sb + SM_BAR + MB_XF);
          TSF(3, 5);
        }
        if (PG) bar_sync(B_LD, 320);
#pragma unroll
        for (int f = WPA; f < WPF; f++) ldmatrix_x4_trans(wo[f], WOF(f));
        unsigned char* pa = P.win + (w_ar(s) + (j * 32 + cw * 16 + wq * 2) * 256 + (l16 >> 2));
        uint32_t ce = (l16 >> 4) - 4 * (cw * 4 + wq);
        OPAQUE_L(pa); OPAQUE_R(ce);
        FENCE();
        bar_sync(wg ? B_O : B_O2, XG && !wg ? 224 : 192);
#if WS
        uint4 ob[NOB];
#pragma unroll
        for (int i = 0; i < NOB; i++) ob[i] = ldsm4(l16 + (sb + SM_OF + i * 512));
        float acc[2][4], dv; uint32_t f0ok;
#pragma unroll
        for (int f = 0; f < 16; f++) {
          const int ks = f & 7;
          const uint32_t b0 = (ks & 1) ? ob[(f >> 1) % NOB].z : ob[(f >> 1) % NOB].x, b1 = (ks & 1) ? ob[(f >> 1) % NOB].w : ob[(f >> 1) % NOB].y;
          const uint32_t (&a)[4] = wo[f < WPF ? f : 2 + (f - WPF) % (WPF - 2)];
          if (f == 8) {
            const float x0 = acc[0][0] + acc[1][0], x1 = acc[0][1] + acc[1][1], x2 = acc[0][2] + acc[1][2], x3_ = acc[0][3] + acc[1][3];
            red_bf2(pa, pack_bf16(x0, ce == 0 ? 1.f : x1)); red_bf2(pa + 256, pack_bf16(x2, ce == 1 ? 1.f : x3_));
            dv = ce == 0 ? x1 : x3_;
          }
          if (ks < 2) mma4z(acc[ks], a[0], a[1], a[2], a[3], b0, b1);
          else mma_16816(acc[ks & 1], a, b0, b1);
          if (NOB < 4 && (f & 1) == 0 && f >= 2 && (f >> 1) - 1 + NOB < 8) ob[((f >> 1) - 1) % NOB] = ldsm4(l16 + (sb + SM_OF + (((f >> 1) - 1 + NOB) & 3) * 512));
          if (f - 1 >= 2 && f - 1 + (WPF - 2) < 16) {
            const int nf = f - 1 + (WPF - 2);
            ldmatrix_x4_trans(wo[2 + (nf - WPF) % (WPF - 2)], WOF(nf));
          }
          if (f == GF) f0ok = mbar_test(sb + SM_BAR + MB_F, (s + 1) & 1);
          if (f < 15) FENCE();
        }
        if (!wg) bar_arrive(B_CV, 256);
        {
          const float x0 = acc[0][0] + acc[1][0], x1 = acc[0][1] + acc[1][1], x2 = acc[0][2] + acc[1][2], x3_ = acc[0][3] + acc[1][3];
          red_bf2(pa + 2048, pack_bf16(x0, ce == 2 ? 1.f : x1)); red_bf2(pa + 2304, pack_bf16(x2, ce == 3 ? 1.f : x3_));
          red_bf2p4(pa + (W_DS + (wq & 1) * 256), pack_bf16(ce == 2 ? x1 : ce == 3 ? x3_ : dv, 1.f), ce);
        }
#else
        uint4 ob[2];
        ob[0] = ldsm4(l16 + (sb + SM_OF)); ob[1] = ldsm4(l16 + (sb + SM_OF + 512));
        float acc[2][4]; uint32_t f0ok;
#pragma unroll
        for (int f = 0; f < 16; f++) {
          const int ks = f >> 1;
          const uint32_t b0 = (ks & 1) ? ob[(ks >> 1) & 1].z : ob[(ks >> 1) & 1].x, b1 = (ks & 1) ? ob[(ks >> 1) & 1].w : ob[(ks >> 1) & 1].y;
          if (f < 2) mma4z(acc[f], wo[f][0], wo[f][1], wo[f][2], wo[f][3], b0, b1);
          else mma_16816(acc[f % 2], wo[f < WPF ? f : 2 + (f - WPF) % (WPF - 2)], b0, b1);
          if (f - 1 >= 2 && f - 1 + (WPF - 2) < 16) {
            const int nf = f - 1 + (WPF - 2);
            ldmatrix_x4_trans(wo[2 + (nf - WPF) % (WPF - 2)], WOF(nf));
          }
          if (f == 4 || f == 8) ob[((f >> 2) - 1) & 1] = ldsm4(l16 + (sb + SM_OF + (1 + (f >> 2)) * 512));
          if (f == GF) f0ok = mbar_test(sb + SM_BAR + MB_F, (s + 1) & 1);
          if (f < 15) FENCE();
        }
        if (!wg) bar_arrive(B_CV, 256);
        red_bf2(pa, pack_bf16(acc[0][0], ce == 0 ? 1.f : acc[0][1])); red_bf2(pa + 256, pack_bf16(acc[0][2], ce == 1 ? 1.f : acc[0][3]));
        red_bf2(pa + 2048, pack_bf16(acc[1][0], ce == 2 ? 1.f : acc[1][1])); red_bf2(pa + 2304, pack_bf16(acc[1][2], ce == 3 ? 1.f : acc[1][3]));
        red_bf2p4(pa + (W_DS + (wq & 1) * 256), pack_bf16(ce == 0 ? acc[0][1] : ce == 1 ? acc[0][3] : ce == 2 ? acc[1][1] : acc[1][3], 1.f), ce);
#endif
        TSF(4, 1); TSF(2, 6);
        if (wg) bar_sync(B_CV, 256);
        else if (!f0ok) mbar_wait(sb + SM_BAR + MB_F, (s + 1) & 1);
      }
      OPAQUE_R(lm); OPAQUE_R(l16);
      {
        float d[16];
        const uint32_t cv = TQ(SM_CV + ((s ^ wg) & 1) * 4096);
        TSF(9, 1);
#if BI == 1
        wg_fence();
        XR<0, 1, 0, 8, 1>::run(d, wv, xb16); XS<8, 8, 9, 0>::run(d, va16, xb16); XR<1, 2, 0, 8, 0>::run(d, wv, xb16); XS<9, 8, 10, 0>::run(d, va16, xb16);
        XR<2, 3, 0, 8, 0>::run(d, wv, xb16); XS<10, 8, 11, 0>::run(d, va16, xb16); XR<3, 4, 0, 8, 0>::run(d, wv, xb16); XS<11, 8, 12, 0>::run(d, va16, xb16);
        XR<4, 5, 0, 8, 0>::run(d, wv, xb16); XS<12, 8, 13, 0>::run(d, va16, xb16); XR<5, 6, 0, 8, 0>::run(d, wv, xb16); XS<13, 8, 14, 0>::run(d, va16, xb16);
        XR<6, 7, 0, 8, 0>::run(d, wv, xb16); XS<14, 8, 15, 0>::run(d, va16, xb16); XR<7, 8, 0, 8, 0>::run(d, wv, xb16); XS<15, 8, 16, 0>::run(d, va16, xb16);
        wg_commit(); wg_wait0();
#elif BI == 3
        wg_fence(); XR<0, 8, 0, 8, 1>::run(d, wv, xb16); XR<8, 16, -8, 8, 0>::run(d, wv, xb16); wg_commit(); wg_wait0();
#elif BI == 6
        {
          uint32_t sv[2][4];
          ldmatrix_x4_trans(sv[0], WA); ldmatrix_x4_trans(sv[1], WA + 2048);
          wg_fence(); XR<0, 2, 0, 8, 1>::run(d, wv, xb16); wg_commit();
          wg_fence(); XR<8, 10, -8, 2, 0>::run(d, sv, xb16); wg_commit(); XR<2, 4, 0, 8, 0>::run(d, wv, xb16); wg_commit(); wg_wait1();
          ldmatrix_x4_trans(sv[0], WA + 2 * 2048); ldmatrix_x4_trans(sv[1], WA + 3 * 2048);
          wg_fence(); XR<10, 12, -10, 2, 0>::run(d, sv, xb16); wg_commit(); XR<4, 6, 0, 8, 0>::run(d, wv, xb16); wg_commit(); wg_wait1();
          ldmatrix_x4_trans(sv[0], WA + 4 * 2048); ldmatrix_x4_trans(sv[1], WA + 5 * 2048);
          wg_fence(); XR<12, 14, -12, 2, 0>::run(d, sv, xb16); wg_commit(); XR<6, 8, 0, 8, 0>::run(d, wv, xb16); wg_commit(); wg_wait1();
          ldmatrix_x4_trans(sv[0], WA + 6 * 2048); ldmatrix_x4_trans(sv[1], WA + 7 * 2048);
          wg_fence(); XR<14, 16, -14, 2, 0>::run(d, sv, xb16); wg_commit(); wg_wait0();
        }
#elif BI == 4
        wg_fence(); XR<0, BR, 0, 8, 1>::run(d, wv, xb16);
        bar_sync(B_LD, 320);
        XR<BR, 8, 0, 8, 0>::run(d, wv, xb16); XS<8, 8, 16, 0>::run(d, va16, xb16); wg_commit(); wg_wait0();
#elif BI == 5
        if (wg == 0) { wg_fence(); XR<0, KB, 0, 32, 1>::run(d, w, xb16); wg_commit(); wg_wait0(); OPAQUE_R(l16); DUMP(SM_CW); }
        wg_fence(); XR<0, BR, 0, 8, 1>::run(d, wv, xb16); XS<8, 8, 16, BR == 0>::run(d, va16, xb16); XR<BR, 8, 0, 8, 0>::run(d, wv, xb16); wg_commit(); wg_wait0();
#else
        wg_fence(); XR<0, BR, 0, 8, 1>::run(d, wv, xb16); XS<8, 8, 16, BR == 0>::run(d, va16, xb16); XR<BR, 8, 0, 8, 0>::run(d, wv, xb16); wg_commit(); wg_wait0();
#endif
        uint32_t q[8];
#pragma unroll
        for (int i = 0; i < 8; i++) q[i] = pack_bf16(d[2 * i], d[2 * i + 1]);
        if (wg == 0) {
          sts128(cv, q[0], q[1], q[2], q[3]); sts128(cv + 2048, q[4], q[5], q[6], q[7]);
          if (BI != 5) {
          wg_fence(); XR<0, KB, 0, 32, 1>::run(d, w, xb16); wg_commit(); wg_wait0();
          OPAQUE_R(l16);
          DUMP(SM_CW);
          }
          TSF(5, 1);
        } else {
          const uint4 o = lds128(cv + (r ^ 1) * 2048), k = lds128(cv + r * 2048);
          XREL(MB_XE1);
          st_async4(l16 + (rsb + SM_VR + wq * 512), u2f(addb2(r ? q[0] : q[4], o.x)), u2f(addb2(r ? q[1] : q[5], o.y)), u2f(addb2(r ? q[2] : q[6], o.z)), u2f(addb2(r ? q[3] : q[7], o.w)),
                    rsb + SM_BAR + MB_VR);
          sts128(TQ(SM_VL), addb2(r ? q[4] : q[0], k.x), addb2(r ? q[5] : q[1], k.y), addb2(r ? q[6] : q[2], k.z), addb2(r ? q[7] : q[3], k.w));
          __syncwarp();
          if (l16 == 0) mbar_arrive(sb + SM_BAR + MB_VR);
          TSF(28, 5);
        }
      }
    }
  } else {
    asm volatile("setmaxnreg.dec.sync.aligned.u32 " STR(RF_CTL) ";");
    const int g = lane >> 2, tq = lane & 3;
    if (wq == 0) {
      if (lane < 12) asm volatile("prefetch.global.L2 [%0];" :: "l"(SP.x + (size_t)(cta * 12 + lane) * 64));
      __syncwarp();
      {
        SIDES();
        const uint32_t o[6] = {w_blk(w_h1(cta), me), w_blk(w_h1(cta) ^ H1_V, me), w_blk(w_mvx(cta, 0), me ^ sm2.z), w_blk(w_mvx(cta, 1), me ^ sm2.z),
                               w_blk(w_mxa(cta, 0), me ^ sm2.z), w_blk(w_mxa(cta, 1), me ^ sm2.z)};
#pragma unroll
        for (int i = 0; i < 24; i++) stg_r4(P.win + (o[i >> 2] + (i & 3) * 512 + lane * 16), 0u, 0u, 0u, 0u);
#pragma unroll
        for (int i = 0; i < 6; i++) stg_r1(P.win + (w_ar(i >> 1) + cta * 256 + (i & 1) * W_DS + lane * 4), 0u);
        __threadfence();
        __syncwarp();
      }
      {
        const uint32_t wv = movm(*reinterpret_cast<const uint32_t*>(P.mem0 + g * DM + cta * 8 + tq * 2));
        const bool sp = lane == cnt_word(cta & 31);
        stg_r1(P.win + (w_ar(-1) + cta * 256 + lane * 4), sp ? (wv & 0xffffu) | 0x42000000u : wv);
        if (sp) stg_r1(P.win + (w_ar(-1) + ((cta & ~9) + ((cta >> 1) & 1)) * 256 + W_DS + lane * 4), (wv >> 16) | 0x42000000u);
      }
      bar_sync(B_V, 160);
      if (lane == 0) {
        fence_async_smem(); mbar_arrive_cluster_rlx(mapa(sb + SM_BAR + MB_INIT, 0)); mbar_arrive_cluster_rlx(mapa(sb + SM_BAR + MB_INIT, 1));
        mbar_wait(sb + SM_BAR + MB_INIT, 0);
        mbar_expect_tx(sb + SM_BAR + MB_F, 32768);
        for (int i = 0; i < (BGT == 2 ? 7 : BGT == 1 ? 3 : 0); i++) mbar_arrive(sb + SM_BAR + MB_F);
        mbar_expect_tx(sb + SM_BAR + MB_F + 8, 32768);
        XLOAD(1, 0); XLOAD(0, 1);
        WLOAD(4 + WSPL, 8);
      }
      __syncwarp();
#ifdef PER
      if (lane == 0) atomicMax(&g_end[5], gt32());
#endif
    }
    bar_sync(B_X2, 256);
    SIDES();
    uint32_t l16 = __shfl_sync(~0u, lane * 16, lane);
    const uint32_t me2 = me ^ sm2.z;
    const float sc = 32.f * 0.08838834764831845f * 1.4426950408889634f;
    uint32_t ls = l16 + sb;
#define PVM(o, zs, p0, p2, M1, M2) do { \
        FENCE(); \
        mma4z(zs, 0x3F803F80u, 0x3F803F80u, 0x3F803F80u, 0x3F803F80u, p0.x, p0.y); \
        FENCE(); M1; \
        _Pragma("unroll") for (int t = 0; t < 4; t++) mma4z(o[t], va[2 * t].x, va[2 * t].y, va[2 * t].z, va[2 * t].w, p0.x, p0.y); \
        FENCE(); \
        mma4(zs, 0x3F803F80u, 0x3F803F80u, 0x3F803F80u, 0x3F803F80u, p0.z, p0.w); \
        _Pragma("unroll") for (int t = 0; t < 2; t++) mma4(o[t], va[2 * t + 1].x, va[2 * t + 1].y, va[2 * t + 1].z, va[2 * t + 1].w, p0.z, p0.w); \
        FENCE(); M2; \
        mma_1688(zs, 0x3F803F80u, 0x3F803F80u, p2); \
        _Pragma("unroll") for (int t = 2; t < 4; t++) mma4(o[t], va[2 * t + 1].x, va[2 * t + 1].y, va[2 * t + 1].z, va[2 * t + 1].w, p0.z, p0.w); \
        mma_1688(o[0], vm[0].x, vm[0].y, p2); mma_1688(o[1], vm[0].z, vm[0].w, p2); mma_1688(o[2], vm[1].x, vm[1].y, p2); mma_1688(o[3], vm[1].z, vm[1].w, p2); } while (0)
#define PVE(o, z, dst) do { \
        const float i0 = rcpf(z[0]), i1 = rcpf(z[1]); \
        _Pragma("unroll") for (int u = 0; u < 2; u++) \
          stsm4t(ls + (dst) + u * 1024, pack_bf16(o[2 * u][0] * i0, o[2 * u][1] * i1), pack_bf16(o[2 * u][2] * i0, o[2 * u][3] * i1), \
                 pack_bf16(o[2 * u + 1][0] * i0, o[2 * u + 1][1] * i1), pack_bf16(o[2 * u + 1][2] * i0, o[2 * u + 1][3] * i1)); } while (0)
#define SOFTMAX(pf, f) do { \
        float mx = fmaxf(fmaxf(fmaxf(sx[2], sx[3]), fmaxf(sx[4], sx[5])), fmaxf(fmaxf(sx[6], sx[7]), fmaxf(sx[8], sx[9]))); \
        mx = fmaxf(mx, fmaxf(sx[0], sx[1])); \
        mx = fmaxf(mx, __shfl_xor_sync(~0u, mx, 1)); \
        mx = fmaxf(mx, __shfl_xor_sync(~0u, mx, 2)); \
        mx *= -(f); \
        _Pragma("unroll") for (int i = 0; i < 10; i++) sx[i] = ex2(fmaf(sx[i], f, mx)); \
        sts128(ls + (pf), pack_bf16(sx[2], sx[3]), pack_bf16(sx[4], sx[5]), pack_bf16(sx[6], sx[7]), pack_bf16(sx[8], sx[9])); \
        sts32(ls - l12 + (pf) + 512, pack_bf16(sx[0], sx[1])); } while (0)
    const uint32_t lq = (l16 ^ ((l16 >> 1) & 64u)) + sb, l12 = (l16 >> 2) * 3;
#define M3PTR(sl) \
            const uint32_t tf = me ^ 1 ^ r, m3i = w_ar(sl) + (wq & 1) * 16384 + BP * 1024 + (l16 & 0x70u) + ((l16 & 0x180u) << 1); \
            const unsigned char* p0f = P.win + (m3i + r * 8192 + tf * 4096); const unsigned char* p0n = P.win + (m3i + r * 8192 + (tf ^ 1) * 4096); \
            const unsigned char* p1f = P.win + (m3i + (r ^ 1) * 8192 + (tf ^ 1) * 4096); const unsigned char* p1n = P.win + (m3i + (r ^ 1) * 8192 + tf * 4096); \
            const unsigned char* pd = P.win + (w_ar(sl) + (wq & 1) * 16384 + (((l16 >> 7) ^ r) & 1u) * 8192 + ((l16 & 64u) * 4 + (l16 & 48u) * 2 + (l16 & 16u)) * 16 + W_DS + (l16 & 0x70u)); \
            uint32_t mf = ls + SM_MEM + (wq & 1) * 8192 + tf * 2048, mn = ls + SM_MEM + (wq & 1) * 8192 + (tf ^ 1) * 2048, nr = l16 < 256u ? 1u + (((l16 >> 6) ^ (l16 >> 7) ^ tf) & 1u) : 0u; \
            OPAQUE_L(p0f); OPAQUE_L(p0n); OPAQUE_L(p1f); OPAQUE_L(p1n); OPAQUE_L(pd); OPAQUE_R(mf); OPAQUE_R(mn); OPAQUE_R(nr); FENCE()
#define M3REQ(arr) \
            _Pragma("unroll") for (int i = 0; i < 4; i++) { cp16(mn + 4096 + i * 512, p1f + (i - BP) * 1024); cp16(mf + i * 512, p0f + (i - BP) * 1024); } \
            cp16p(ls + SM_RD + (wq & 1) * 256, pd, nr & 1u); \
            if (NG) spin(DLY_NW); \
            _Pragma("unroll") for (int i = 0; i < 4; i++) { cp16(mf + 4096 + i * 512, p1n + (i - BP) * 1024); cp16(mn + i * 512, p0n + (i - BP) * 1024); } \
            cp16p(ls + SM_RD + (wq & 1) * 256, pd, nr & 2u); \
            asm volatile("cp.async.mbarrier.arrive.noinc.shared::cta.b64 [%0];" :: "r"(sb + SM_BAR + MB_G + (wq & 1) * 8) : "memory"); \
            if (BI == 4 && (arr)) bar_arrive(B_LD, 320)
    if (wq < 2) { M3PTR(-1); M3REQ(1); }
    if (wq == 0) {
      bar_sync(B_P, 160);
      if (l16 == 0) {
        fence_async_smem();
        mbar_expect_tx(sb + SM_BAR + MB_WO, 65536);
        for (int i = 0; i < 8; i++) tma_load_2d(sb + SM_WOS + i * 8192, &tmw, j * 256 + ((i >> 1) ^ (2 * sw)) * 64, h * DH + (i & 1) * 64, sb + SM_BAR + MB_WO);
      }
      __syncwarp();
    }
#define ETA(k, first) ETAT(gt32() + (k), first)
#define ETAT(tm, first) do { unsigned char* pt = P.win + (w_ar(s) + (W_DS + 256) + (cta >> 5) * 8192 + ((cta >> 4) & 1) * 2048 + (l16 & 16u) * 256); \
          asm volatile("{\n.reg .pred q;\nsetp.lt.u32 q, %2, 32;\n@q red.relaxed.gpu.global.max.u32 [%0+4], %1;\n}" :: "l"(pt), "r"(tm), "r"(l16) : "memory"); \
          if (first) asm volatile("{\n.reg .pred q;\nsetp.lt.u32 q, %1, 32;\n@q red.relaxed.gpu.global.add.u32 [%0], 1;\n}" :: "l"(pt), "r"(l16) : "memory"); } while (0)
    if (wq == 1) {
      const uint32_t xin = w_blk(w_mxa(cta, 0), me2) + l16;
      const uint32_t lsq = sb + ((l16 & 0x70u) | ((l16 & 0x80u) << 1) | ((l16 & 0x100u) >> 1));
      int kd = DLY_K;
      mbar_wait(sb + SM_BAR + MB_MEM, 0); mbar_wait(sb + SM_BAR + MB_MEM + 8, 0);
      for (int s = 0; s < NSEG; s++) {
        const uint32_t t2 = ((s >> 1) & 1) ^ 1;
        mbar_wait(sb + SM_BAR + MB_XF, s & 1);
        PRB(10);
        {
        uint4 kx[4], qx[4];
#pragma unroll
        for (int i = 0; i < 4; i++) { kx[i] = ldsm4(ls + (SM_XF + (4 + i) * 512)); qx[i] = ldsm4(lsq + (SM_XF + i * 512)); }
        const uint32_t db = w_blk(w_mxa(h * 4, s), me2) + l16 - 512;
        {
          float S[2][4][4];
#pragma unroll
          for (int mt = 0; mt < 2; mt++) {
            const uint4 q0 = qx[mt];
            mma4z(S[mt][0], q0.x, q0.y, q0.z, q0.w, kx[0].x, kx[0].y); mma4z(S[mt][1], q0.x, q0.y, q0.z, q0.w, kx[0].z, kx[0].w);
            mma4z(S[mt][2], q0.x, q0.y, q0.z, q0.w, kx[1].x, kx[1].y); mma4z(S[mt][3], q0.x, q0.y, q0.z, q0.w, kx[1].z, kx[1].w);
          }
#pragma unroll
          for (int mt = 0; mt < 2; mt++) {
            const uint4 q1 = qx[2 + mt];
            mma4(S[mt][0], q1.x, q1.y, q1.z, q1.w, kx[2].x, kx[2].y); mma4(S[mt][1], q1.x, q1.y, q1.z, q1.w, kx[2].z, kx[2].w);
            mma4(S[mt][2], q1.x, q1.y, q1.z, q1.w, kx[3].x, kx[3].y); mma4(S[mt][3], q1.x, q1.y, q1.z, q1.w, kx[3].z, kx[3].w);
          }
          FENCE();
          if (XG && s > 0) bar_arrive(B_O2, 224);
          FENCE();
#pragma unroll
          for (int u = 0; u < 4; u++) {
            const int mt = u >> 1, c = 2 * (u & 1);
            const uint32_t m0 = tagw(pack_f16(S[mt][0][c], S[mt][0][c + 1]), t2), m1 = pack_f16(S[mt][1][c], S[mt][1][c + 1]),
                           m2 = pack_f16(S[mt][2][c], S[mt][2][c + 1]), m3 = pack_f16(S[mt][3][c], S[mt][3][c + 1]);
            const int e = u ^ j;
            if (e) stg_r4(P.win + (db + mt * 16384 + (u & 1) * 2048 + e * 512), m0, m1, m2, m3);
            else sts128(ls + SM_XS, m0, m1, m2, m3);
          }
        }
        TS(15);
        float sx[10];
        const unsigned char* pa = P.win + (xin + ((s & 1) << 20));
        uint4 xv[3];
        if (s > 0) spin(DLY_XD);
#pragma unroll
        for (int i = 0; i < 3; i++) xv[i] = ldg_r4(pa + i * 512);
        FENCE();
        if (GW == 0 && s > 0) {
          M3PTR(s - 1);
          bar_sync(B_GO, 64);
          const uint32_t tg0 = lds32(sb + SM_Z + 32);
          while (tg0 - gt32() - 1u < 8192u) {}
          M3REQ(s < NSEG);
        }
        FENCE();
        int n = 0; float mx;
#pragma unroll 1
        while (__any_sync(~0u, (x3(xv[0].x, xv[1].x, t2) | (xv[2].x ^ t2)) & 1u) && ++n < SPIN_LIMIT) {
#pragma unroll
          for (int i = 0; i < 3; i++) xv[i] = ldg_r4(pa + i * 512);
        }
        {
          const uint4 v3 = lds128(ls + SM_XS);
          sum_h4(sx[2], sx[3], xv[0].x, xv[1].x, xv[2].x, v3.x); sum_h4(sx[4], sx[5], xv[0].y, xv[1].y, xv[2].y, v3.y);
          sum_h4(sx[6], sx[7], xv[0].z, xv[1].z, xv[2].z, v3.z); sum_h4(sx[8], sx[9], xv[0].w, xv[1].w, xv[2].w, v3.w);
          const int row = 8 * j + g - 2 * tq;
#pragma unroll
          for (int i = 0; i < 8; i++) if ((i >> 1) * 8 + (i & 1) > row) sx[2 + i] = -INFINITY;
        }
        mx = fmaxf(fmaxf(fmaxf(sx[2], sx[3]), fmaxf(sx[4], sx[5])), fmaxf(fmaxf(sx[6], sx[7]), fmaxf(sx[8], sx[9])));
        sts32(ls - l12 + SM_XS + 512, f2u(mx));
        {
          if (l16 == 0) mbar_expect_tx(sb + SM_BAR + MB_VR, 2048);
          unsigned char* d = P.win + (w_blk(w_mvx(cta, s), me2) + l16);
          OPAQUE_L(d); FENCE();
          mbar_wait(sb + SM_BAR + MB_VR, s & 1);
          PRB(14);
#pragma unroll
          for (int t = 0; t < 4; t++) {
            const uint4 a0 = lds128(ls + (SM_VL + t * 512)), a1 = lds128(ls + (SM_VR + t * 512));
            stg_r4(d + t * 512, tagw(addb2(a0.x, a1.x), t2), addb2(a0.y, a1.y), addb2(a0.z, a1.z), addb2(a0.w, a1.w));
          }
          TS(23);
        }
        unsigned char* pm = P.win + (db + 2048 + j * 128 - l12);
        const unsigned char* py = pa + 1536 - l12;
        OPAQUE_L(pm); OPAQUE_L(py);
        if (s > 0) bar_sync(B_PXF, 96);
        FENCE();
        bar_sync(B_QK1, 288);
        uint32_t kb[2][2];
#pragma unroll
        for (int t = 0; t < 2; t++) {
          const float4 u = lds128f(lq + (SM_QKP + (2 + t) * 512)), v4 = lds128f(lq + (SM_QKP + 2048 + (2 + t) * 512));
          kb[t][0] = pack_bf16(u.x + v4.x, u.y + v4.y); kb[t][1] = pack_bf16(u.z + v4.z, u.w + v4.w);
        }
        float S[2][4];
#pragma unroll
        for (int mt = 0; mt < 2; mt++) mma4z(S[mt], qx[mt].x, qx[mt].y, qx[mt].z, qx[mt].w, kb[0][0], kb[0][1]);
#pragma unroll
        for (int mt = 0; mt < 2; mt++) mma4(S[mt], qx[2 + mt].x, qx[2 + mt].y, qx[2 + mt].z, qx[2 + mt].w, kb[1][0], kb[1][1]);
        PT(14, s == 0 && l16 == 0);
        if (s == 0) mbar_wait(sb + SM_BAR + MB_WO, 0);
        PT(15, s == 0 && l16 == 0);
        if (s < NSEG - 1) bar_arrive(B_PUB, 320);
        FENCE();
#pragma unroll
        for (int u = 0; u < 4; u++) stg_r1(pm + (u >> 1) * 16384 + (u & 1) * 2048, tagw(pack_f16(S[u >> 1][2 * (u & 1)], S[u >> 1][2 * (u & 1) + 1]), t2));
        TS(30);
        FENCE();
        if (ETW == 1 && s < NSEG - 1) {
          const uint32_t te = gt32();
          kd = lds32(sb + SM_Z + 40) == (uint32_t)s && s ? min(kd + KU, DLY_K + 256) : max(kd - KD, DLY_K);
          ETAT(te + kd, 1);
        }
        spin(DLY_XL);
        uint32_t xy[4];
#pragma unroll
        for (int i = 0; i < 4; i++) xy[i] = ldg_r1(py + i * 128);
        FENCE();

        n = 0;
#pragma unroll 1
        while (__any_sync(~0u, (x3(xy[0], xy[1], t2) | x3(xy[2], xy[3], t2)) & 1u) && ++n < SPIN_LIMIT) {
#pragma unroll
          for (int i = 0; i < 4; i++) xy[i] = ldg_r1(py + i * 128);
        }
        sum_h4(sx[0], sx[1], xy[0], xy[1], xy[2], xy[3]);
        mx = fmaxf(mx, fmaxf(sx[0], sx[1]));
        mx = fmaxf(fmaxf(mx, __shfl_xor_sync(~0u, mx, 1)), fmaxf(__shfl_xor_sync(~0u, mx, 2), __shfl_xor_sync(~0u, mx, 3)));
#pragma unroll
        for (int i = 0; i < 10; i++) sx[i] = ex2(fmaf(sx[i], sc, -sc * mx));
        sts128(ls + SM_PX, pack_bf16(sx[2], sx[3]), pack_bf16(sx[4], sx[5]), pack_bf16(sx[6], sx[7]), pack_bf16(sx[8], sx[9]));
        sts32(ls - l12 + SM_PX + 512, pack_bf16(sx[0], sx[1]));
        bar_arrive(B_PX, 96);
        TS(1);
        }
      }
    } else {
      const uint32_t ho = (wq & 1) * 512 + l16, hv = wq == 0 ? 0u : H1_V;
      uint32_t ow = w_blk(w_h1(cta) ^ hv, me) + ho, or0 = w_blk(w_h1(cta ^ 1) ^ hv, me) + ho, or1 = w_blk(w_h1((cta ^ 2) & ~1) ^ hv, me) + ho;
#define PTRS() OPAQUE_R(ow); OPAQUE_R(or0); OPAQUE_R(or1); \
      unsigned char* pw0 = P.win + ow; const unsigned char* pr0 = P.win + or0; const unsigned char* pr1 = P.win + or1; \
      OPAQUE_L(pw0); OPAQUE_L(pr0); OPAQUE_L(pr1); FENCE()
      if (wq == 0) {
        const uint32_t xcnt = me ? NCTA - nlo : nlo, xrank = (me ? cta - nlo : cta) + lane * xcnt;
        int kd = DLY_K;
        mbar_wait(sb + SM_BAR + MB_XE1, 0);
        if (l16 == 0) { mbar_expect_tx(sb + SM_BAR + MB_F + 8, 32768); XLOAD(1, 1); }
        __syncwarp();
        for (int s = 0; s < NSEG - 1; s++) {
          const uint32_t tg = (s & 1) ^ 1;
          mbar_wait(sb + SM_BAR + MB_XF, s & 1);
          uint4 xf[4];
#pragma unroll
          for (int i = 0; i < 4; i++) xf[i] = ldsm4(ls + (SM_XF + (4 + i) * 512));
          PTRS();
          unsigned char* pw1 = pw0 + 512 - l12; OPAQUE_L(pw1);
          bar_sync(B_QK, 288);
          PRB(9);
          float4 u[4], v4[4];
#pragma unroll
          for (int t = 0; t < 4; t++) { u[t] = lds128f(lq + (SM_QKP + t * 512)); v4[t] = lds128f(lq + (SM_QKP + 2048 + t * 512)); }
          FENCE();
          uint32_t f[4][2], m[5];
#pragma unroll
          for (int t = 0; t < 2; t++) { f[t][0] = pack_bf16(u[t].x + v4[t].x, u[t].y + v4[t].y); f[t][1] = pack_bf16(u[t].z + v4[t].z, u[t].w + v4[t].w); }
          float S[5][4], T[5][4];
          mma4z(S[1], f[0][0], f[1][0], f[0][1], f[1][1], xf[0].x, xf[0].y); mma4z(T[1], f[0][0], f[1][0], f[0][1], f[1][1], xf[2].x, xf[2].y);
          mma4z(S[2], f[0][0], f[1][0], f[0][1], f[1][1], xf[0].z, xf[0].w); mma4z(T[2], f[0][0], f[1][0], f[0][1], f[1][1], xf[2].z, xf[2].w);
          FENCE();
#pragma unroll
          for (int t = 2; t < 4; t++) { f[t][0] = packv(u[t].x, v4[t].x, u[t].y, v4[t].y); f[t][1] = packv(u[t].z, v4[t].z, u[t].w, v4[t].w); }
          mma4z(S[3], f[0][0], f[1][0], f[0][1], f[1][1], xf[1].x, xf[1].y); mma4z(T[3], f[0][0], f[1][0], f[0][1], f[1][1], xf[3].x, xf[3].y);
          mma4z(S[4], f[0][0], f[1][0], f[0][1], f[1][1], xf[1].z, xf[1].w); mma4z(T[4], f[0][0], f[1][0], f[0][1], f[1][1], xf[3].z, xf[3].w);
          FENCE();
          mma4z(S[0], f[0][0], f[1][0], f[0][1], f[1][1], f[2][0], f[2][1]); mma4z(T[0], f[0][0], f[1][0], f[0][1], f[1][1], f[3][0], f[3][1]);
          bar_arrive(B_PUB, 320);
          FENCE();
#pragma unroll
          for (int i = 1; i < 5; i++) m[i] = pack_f16(S[i][0] + T[i][2], S[i][1] + T[i][3]);
          stg_r4(pw0, tagw(m[1], tg), m[2], m[3], m[4]);
          m[0] = pack_f16(S[0][0] + T[0][2], S[0][1] + T[0][3]);
          stg_r1(pw1, tagw(m[0], tg));
          TS(6); PT(11, s == 0 && l16 == 0);
          FENCE();
          const uint32_t ts = clk32();
          uint32_t te = gt32() + kd;
          const unsigned char* py0 = pr0 + 512 - l12; const unsigned char* py1 = pr1 + 512 - l12;
          OPAQUE_L(py0); OPAQUE_L(py1);
          unsigned char* pt = P.win + (w_ar(s) + (W_DS + 256) + (cta >> 5) * 8192 + ((cta >> 4) & 1) * 2048 + (l16 & 16u) * 256);
          OPAQUE_L(pt);
          if (l16 == 0) mbar_expect_tx(sb + SM_BAR + MB_F, s < NSEG - 2 ? 32768 : 0);
          FENCE();
          while (clk32() - ts < (uint32_t)DLY_S) {}
          {
            float sx[10]; uint32_t x, x1, x2, x3_; int n = 0; bool bad;
#pragma unroll 1
            do {
              uint4 v[3]; uint32_t y[3], t[5];
              v[0] = ldg_r4(pr0); v[1] = ldg_r4(pr1); v[2] = ldg_r4(pr1 + 2048);
              y[0] = ldg_r1(py0); y[1] = ldg_r1(py1); y[2] = ldg_r1(py1 + 2048);
              if (ETW == 0) { if (n) te = gt32() + DLY_KS; eta2(pt, te, n == 0, l16); }
              else if (n) ETA(DLY_KS, 0);
              n++;
              FENCE();
#define Q3(o, a, b, c) hadd2(hadd2(o, a), hadd2(b, c))
              t[1] = Q3(m[1], v[0].x, v[1].x, v[2].x); t[2] = Q3(m[2], v[0].y, v[1].y, v[2].y); t[3] = Q3(m[3], v[0].z, v[1].z, v[2].z); t[4] = Q3(m[4], v[0].w, v[1].w, v[2].w);
              t[0] = Q3(m[0], y[0], y[1], y[2]);
              bad = __any_sync(~0u, or3(x3(v[0].x, v[1].x, tg), x3(v[2].x, y[0], tg), x3(y[1], y[2], tg)) & (n < SPIN_LIMIT ? 1u : 0u));
              x = hmax2(hmax2(hmax2(t[1], t[2]), hmax2(t[3], t[4])), t[0]);
              const float2 xm = __half22float2(*reinterpret_cast<__half2*>(&x));
              x = f2u(fmaxf(xm.x, xm.y) * -sc);
              x1 = shfl_x(x, 1); x2 = shfl_x(x, 2); x3_ = shfl_x(x, 3);
              FENCE();
#pragma unroll
              for (int i = 1; i < 6; i++) h2f(sx[2 * (i % 5)], sx[2 * (i % 5) + 1], t[i % 5]);
              FENCE();
            } while (bad);
            const float mx = fminf(fminf(u2f(x), u2f(x1)), fminf(u2f(x2), u2f(x3_)));
#pragma unroll
            for (int i = 2; i < 12; i++) sx[i % 10] = ex2v(sx[i % 10], sc, mx);
#pragma unroll
            for (int i = 1; i < 6; i++) m[i % 5] = pack_bf16(sx[2 * (i % 5)], sx[2 * (i % 5) + 1]);
            sts128(ls + SM_PF, m[1], m[2], m[3], m[4]);
            sts32(ls - l12 + SM_PF + 512, m[0]);
            TV(19, n - 1);
          }
          TS(12);
          bar_sync(B_P, 96);
          PT(12, s == 0 && l16 == 0);
          if (LN) {
            const uint4 pa = lds128(ls + SM_PF); const uint32_t pb = lds32(ls - l12 + SM_PF + 512);
#define S2(w) (u2f((w) << 16) + u2f((w) & 0xffff0000u))
            float z = ((S2(pa.x) + S2(pa.y)) + (S2(pa.z) + S2(pa.w))) + S2(pb);
            z += __shfl_xor_sync(~0u, z, 1); z += __shfl_xor_sync(~0u, z, 2);
            sts32(sb + SM_Z + (l16 >> 6) * 4, f2u(rcpf(z)));
            bar_arrive(B_O, 352);
          }
          OPAQUE_R(l16);
          {
            const unsigned char* pe = P.win + w_blk(w_ar(s) + (W_DS + 256) + (l16 & 0x60u) * 256 + (l16 & 16u) * 128, me);
            const uint32_t tp = gt32() + DLY_M3;
            PRB(12);
            if (F0W == 0 && s < NSEG - 2) F0LOAD();
            if (PA) ETAT(tp, 0);
            uint32_t tg0; int n = 0;
#pragma unroll 1
            for (;;) {
              const uint2 e = ldg_r2(pe);
              tg0 = __reduce_max_sync(~0u, e.y);
              if (tg0 - tp >= 4096u) tg0 = tp;
              if ((!__any_sync(~0u, e.x != 16u) && (int)(tg0 - gt32()) < DLY_RR) || ++n >= SPIN_LIMIT) break;
            }
            sts32(sb + SM_Z + 32, tg0);
            bar_arrive(B_GO, GW ? 96 : 64);

            if (GW == 0) {
            M3PTR(s);
            while (tg0 - gt32() - 1u < 8192u) {}
            PRB(13);
            TS(16);
            M3REQ(s + 1 < NSEG);
            }
            TS(25); PT(13, s == 0 && l16 == 0);
          }
          if (F1C && s < NSEG - 2) {
            if (F1C == 1) spin(DLY_FA);
            mbar_wait(sb + SM_BAR + MB_XE1, (s + 1) & 1);
            if (l16 == 0) mbar_expect_tx(sb + SM_BAR + MB_F + 8, 32768);
            if (F1C == 2) { mbar_wait(sb + SM_BAR + MB_MEM, (s + 1) & 1); mbar_wait(sb + SM_BAR + MB_MEM + 8, (s + 1) & 1); }
            if (F1C == 3) { mbar_wait(sb + SM_BAR + MB_G, (s + 1) & 1); mbar_wait(sb + SM_BAR + MB_G + 8, (s + 1) & 1); }
            PRB(11);
            if (l16 == 0) XLOAD(1, s + 2);
            __syncwarp();
          }
          if (XPF && s + XPF < NSEG) {
            spin(DLY_PF);
            for (uint32_t i = xrank; i < 512; i += 32 * xcnt)
              asm volatile("prefetch.global.L2 [%0];" :: "l"(SP.x + (size_t)(s + XPF) * (SEG * DM) + i * 64));
            __syncwarp();
          }
          stg_2(P.win + (w_ar(s + 2) + cta * 256 + (l16 >> 8) * W_DS + ((l16 >> 1) & 127u)), 0u, 0u);
          kd = lds32(sb + SM_Z + 40) == (uint32_t)(s + 1) ? min(kd + KU, DLY_K + 256) : max(kd - KD, DLY_K);
          kd = __shfl_sync(~0u, kd, l16 >> 4);
#ifdef PER
          if (l16 == 0) { g_per[cta][s] = gt32(); g_pclk[cta][s] = clk32(); g_pk[cta][s] = kd - DLY_K; }
#endif
        }
        bar_sync(B_QK, 288);
      } else {
        const int mt = wq - 2;
        const uint32_t lt = ls + mt * 1024;
        const uint32_t vi0 = w_blk(w_mvx(h * 4, 0), me2) + mt * 1024;
        const int m3d = r ? -8192 : 8192;
#ifdef PROF
        const uint32_t epoch = gt32(); TST(-1, 30 + mt, l16, epoch);
#endif
        float ox[4][4], zx[4];
#pragma unroll
        for (int i = 0; i < 16; i++) ox[i >> 2][i & 3] = zx[i & 3] = 1.f;
        for (int s = 0;; s++) {
          const uint32_t tg = (s & 1) ^ 1, t2 = ((s >> 1) & 1) ^ 1;
          {
            OPAQUE_R(l16);
            const uint32_t m3i = (mt * 2 + r) * 8192 + (l16 & 0x70u) + ((l16 & 0x180u) << 1);
            const uint32_t m3j = (mt * 2 + (r ^ (l16 >> 7 & 1))) * 8192 + ((l16 & 64u) * 4 + (l16 & 48u) * 2 + (l16 & 16u)) * 16 + W_DS + (l16 & 0x70u);
            uint32_t m3c = sb + SM_MEM + mt * 8192 + cnt_line(l16 >> 4) * 128 + (l16 >> 2);
            const unsigned char* p3 = P.win + (m3i + w_ar(s - 1)); const unsigned char* pd = P.win + (m3j + w_ar(s - 1));
            OPAQUE_L(pd); OPAQUE_R(m3c);
#define XEPI() do {        \
              PVE(ox, zx, SM_OX + mt * 512); \
              __syncwarp(); \
              const uint32_t oa = sb + SM_OX + mt * 512 + ((l16 & 48u) << 3) + ((l16 >> 2) & 0x70u); \
              const uint4 a = lds128(oa), b = lds128(oa + 1024); \
              unsigned char* o = reinterpret_cast<unsigned char*>(g_ox + (size_t)((s - 1) * SEG + 8 * j) * (NH * DH) + h * DH + mt * 32) + ((l16 >> 6) * (NH * DH * 2) + (l16 & 48u)); \
              stg_4(o, a); stg_4(o + 128, b); \
              TST(s - 1, 18, l16 | mt, TCLK()); } while (0)
            if (s > 0) XEPI();
            if (s == NSEG) break;
            if (GW && s > 0) {
              M3PTR(s - 1);
              bar_sync(B_GO, 96);
              const uint32_t tg0 = lds32(sb + SM_Z + 32);
              while (tg0 - gt32() - 1u < 8192u) {}
              M3REQ(0);
            }
            FENCE();
            const int n = m3_check(sb, p3, pd, m3d, l16, m3c, mt, s);
            FENCE();
            if (ETW == 3 && s < NSEG - 1) ETA(DLY_K, mt);
            TST(s, mt ? 21 : 0, l16, TCLK());
            TST(s, mt ? 22 : 17, l16, n);
            PT(6 + s, s < 5 && (l16 | mt) == 0);
          }
          uint4 va[8], vm[2], p0, q0; uint32_t p2, q2;
          const unsigned char* a0 = P.win + (vi0 + ((s & 1) << 20) + l16);
#define VALD() _Pragma("unroll") for (int i = 0; i < 4; i++) { va[i] = ldg_r4(a0 + (i >> 1) * 512 + (i & 1) * 2048); va[4 + i] = ldg_r4(a0 + 16384 + (i >> 1) * 512 + (i & 1) * 2048); }
          if (!VAL) { spin(DLY_WO); VALD(); }
          {
          PTRS();
          bar_sync(B_V, 320);
            const float4 u0 = lds128f(lt + SM_VP), w0 = lds128f(lt + SM_VP + 2048), u1 = lds128f(lt + SM_VP + 512), w1 = lds128f(lt + SM_VP + 2560);
            const uint32_t m0 = tagw(pack_bf16(u0.x + w0.x, u0.y + w0.y), tg), m1 = pack_bf16(u0.z + w0.z, u0.w + w0.w),
                           m2 = pack_bf16(u1.x + w1.x, u1.y + w1.y), m3 = pack_bf16(u1.z + w1.z, u1.w + w1.w);
            stg_r4(pw0, m0, m1, m2, m3);
            if (wq == 2) TS(10);
            FENCE();
            const uint32_t tv = clk32();
            if (VAL) { VALD(); }
            if (ETW == 2 && wq == 3 && s < NSEG - 1) ETA(DLY_K, 1);
            while (clk32() - tv < (uint32_t)DLY_V) {}
            uint4 v[3]; int n = 0; uint32_t bada = 0;
#pragma unroll 1
            do {
              v[0] = ldg_r4(pr0); v[1] = ldg_r4(pr1); v[2] = ldg_r4(pr1 + 2048);
              if (n) {
                TST(s, __any_sync(~0u, bada & 1u) ? 26 : 24, l16, epoch);
                if (__any_sync(~0u, bada & 1u)) { VALD(); }
                if (s < NSEG - 1) ETA(DLY_KS - 192, 0);
              }
              n++;
              FENCE();
              bada = or3(x3(va[0].x, va[1].x, t2), x3(va[2].x, va[3].x, t2), x3(va[4].x, va[5].x, t2)) | x3(va[6].x, va[7].x, t2);
            } while (__any_sync(~0u, or3(bada, x3(v[0].x, v[1].x, tg), v[2].x ^ tg) & 1u) && n < SPIN_LIMIT);
            const uint4 A = make_uint4(addb2(m0, v[0].x), addb2(m1, v[0].y), addb2(m2, v[0].z), addb2(m3, v[0].w));
            const uint4 B = make_uint4(addb2(v[1].x, v[2].x), addb2(v[1].y, v[2].y), addb2(v[1].z, v[2].z), addb2(v[1].w, v[2].w));
            vm[0] = p ? B : A; vm[1] = p ? A : B;
            TST(s, 11, l16 | mt, TCLK()); TST(s, 29, l16 | (mt ^ 1), TCLK());
          }
          if (F0W == 2 && wq == 3 && s < NSEG - 2) F0LOAD();
          if (PXE) { bar_sync(B_PX, 96); q0 = lds128(ls + SM_PX); q2 = lds32(ls - l12 + SM_PX + 512); }
          FENCE();
          if (s < NSEG - 1) {
          PRB(5);
          bar_sync(B_P, 96);
          PRB(6);
          p0 = lds128(ls + SM_PF); p2 = lds32(ls - l12 + SM_PF + 512);
          float o[4][4], z[4];
#if LN
          FENCE();
#pragma unroll
          for (int t = 0; t < 4; t++) mma4z(o[t], va[2 * t].x, va[2 * t].y, va[2 * t].z, va[2 * t].w, p0.x, p0.y);
#pragma unroll
          for (int t = 0; t < 4; t++) mma4(o[t], va[2 * t + 1].x, va[2 * t + 1].y, va[2 * t + 1].z, va[2 * t + 1].w, p0.z, p0.w);
          mma_1688(o[0], vm[0].x, vm[0].y, p2); mma_1688(o[1], vm[0].z, vm[0].w, p2); mma_1688(o[2], vm[1].x, vm[1].y, p2); mma_1688(o[3], vm[1].z, vm[1].w, p2);
#pragma unroll
          for (int u = 0; u < 2; u++)
            stsm4t(ls + (SM_OF + mt * 512) + u * 1024, pack_bf16(o[2 * u][0], o[2 * u][1]), pack_bf16(o[2 * u][2], o[2 * u][3]),
                   pack_bf16(o[2 * u + 1][0], o[2 * u + 1][1]), pack_bf16(o[2 * u + 1][2], o[2 * u + 1][3]));
          bar_arrive(B_O, 352);
#else
#ifdef PROF
          uint32_t tq0, tq1;
          asm volatile("{\n.reg .u32 x;\nand.b32 x, %1, 0;\nmov.u32 %0, %%clock;\nadd.u32 %0, %0, x;\n}" : "=r"(tq0) : "r"(p0.x ^ p2));
#endif
          PVM(o, z, p0, p2, if (PG) bar_arrive(B_LD, 320), );
#ifdef PROF
          FENCE();
          asm volatile("{\n.reg .pred q;\nsetp.eq.f32 q, %1, 0f7f7fffff;\n@q trap;\nmov.u32 %0, %%clock;\n}" : "=r"(tq1) : "f"(o[3][0]));
#endif
          PVE(o, z, SM_OF + mt * 512);
          bar_arrive(B_O, 192);
          TST(s, 20, l16 | mt, tq1);
#endif
          }
          FENCE();
          TST(s, 8, l16 | mt, TCLK());
          if (!PXE) { bar_sync(B_PX, 96); q0 = lds128(ls + SM_PX); q2 = lds32(ls - l12 + SM_PX + 512); }
          if (O2P == 0 && s < NSEG - 1) bar_arrive(B_O2, XG ? 224 : 192);
          PVM(ox, zx, q0, q2, if (O2P == 1 && s < NSEG - 1) bar_arrive(B_O2, XG ? 224 : 192), if (O2P == 2 && s < NSEG - 1) bar_arrive(B_O2, XG ? 224 : 192));
          FENCE();
          if (s < NSEG - 1) { if (O2P == 3) bar_arrive(B_O2, XG ? 224 : 192); bar_arrive(B_PXF, 96); }
        }
      }
    }
  }
#if RLX
  asm volatile("barrier.cluster.arrive.relaxed.aligned;\nbarrier.cluster.wait.aligned;" ::: "memory");
#else
  asm volatile("barrier.cluster.arrive.release.aligned;\nbarrier.cluster.wait.acquire.aligned;" ::: "memory");
#endif
#ifdef PER
  if (threadIdx.x == 0) atomicMax(&g_end[0], gt32());
#endif
}
#ifndef PW
#define PW 2
#endif
#ifndef G2K
#define G2K 4
#endif
#ifndef G2_ST
#define G2_ST 6
#endif
#define G2_TB (G2_ST * 32768 + 1024)
#define G2_SMEM (G2_TB + 32768)
static __device__ __forceinline__ void wgmma_n128_ta(float (&d)[64], uint64_t da, uint64_t db) {
  asm volatile(
      "wgmma.mma_async.sync.aligned.m64n128k16.f32.bf16.bf16 "
      "{%0,%1,%2,%3,%4,%5,%6,%7,%8,%9,%10,%11,%12,%13,%14,%15,%16,%17,%18,%19,%20,%21,%22,%23,%24,%25,%26,%27,%28,%29,%30,%31,"
      "%32,%33,%34,%35,%36,%37,%38,%39,%40,%41,%42,%43,%44,%45,%46,%47,%48,%49,%50,%51,%52,%53,%54,%55,%56,%57,%58,%59,%60,%61,%62,%63}, "
      "%64, %65, 1, 1, 1, 1, 0;"
      : "+f"(d[0]), "+f"(d[1]), "+f"(d[2]), "+f"(d[3]), "+f"(d[4]), "+f"(d[5]), "+f"(d[6]), "+f"(d[7]), "+f"(d[8]), "+f"(d[9]), "+f"(d[10]), "+f"(d[11]),
        "+f"(d[12]), "+f"(d[13]), "+f"(d[14]), "+f"(d[15]), "+f"(d[16]), "+f"(d[17]), "+f"(d[18]), "+f"(d[19]), "+f"(d[20]), "+f"(d[21]), "+f"(d[22]), "+f"(d[23]),
        "+f"(d[24]), "+f"(d[25]), "+f"(d[26]), "+f"(d[27]), "+f"(d[28]), "+f"(d[29]), "+f"(d[30]), "+f"(d[31]), "+f"(d[32]), "+f"(d[33]), "+f"(d[34]), "+f"(d[35]),
        "+f"(d[36]), "+f"(d[37]), "+f"(d[38]), "+f"(d[39]), "+f"(d[40]), "+f"(d[41]), "+f"(d[42]), "+f"(d[43]), "+f"(d[44]), "+f"(d[45]), "+f"(d[46]), "+f"(d[47]),
        "+f"(d[48]), "+f"(d[49]), "+f"(d[50]), "+f"(d[51]), "+f"(d[52]), "+f"(d[53]), "+f"(d[54]), "+f"(d[55]), "+f"(d[56]), "+f"(d[57]), "+f"(d[58]), "+f"(d[59]),
        "+f"(d[60]), "+f"(d[61]), "+f"(d[62]), "+f"(d[63])
      : "l"(da), "l"(db));
}
__global__ void __cluster_dims__(2, 1, 1) __launch_bounds__(384, 1)
gemm2_kernel(const __grid_constant__ CUtensorMap tmo, const __grid_constant__ CUtensorMap tmw, const bf16* __restrict__ x, bf16* __restrict__ out, unsigned char* win) {
  extern __shared__ __align__(1024) unsigned char smem[];
  const uint32_t sb = smem_u32(smem), bars = sb + G2_ST * 32768;
  const int tid = threadIdx.x, lane = tid & 31, warp = tid >> 5;
  const int r = blockIdx.x & 1, n0 = (blockIdx.x & 7) * 128, m0 = (blockIdx.x >> 3) * 128;
  if (tid == 0) {
    for (int i = 0; i < G2_ST; i++) { mbar_init(bars + i * 8, 1); mbar_init(bars + 64 + i * 8, 4); }
    asm volatile("fence.mbarrier_init.release.cluster;" ::: "memory");
  }
  if (tid == 32) { asm volatile("prefetch.tensormap [%0];" :: "l"(&tmw) : "memory"); asm volatile("prefetch.tensormap [%0];" :: "l"(&tmo) : "memory"); }
  __syncthreads();
  asm volatile("barrier.cluster.arrive.relaxed.aligned;" ::: "memory");
#define LW(kt, st) do { tma_load_2d(sb + (st) * 32768, &tmw, n0, (kt) * 64, bars + (st) * 8); tma_load_2d(sb + (st) * 32768 + 8192, &tmw, n0 + 64, (kt) * 64, bars + (st) * 8); } while (0)
#define LO(kt, st) asm volatile("cp.async.bulk.tensor.2d.shared::cluster.global.mbarrier::complete_tx::bytes.multicast::cluster [%0], [%1, {%3, %4}], [%2], %5;" \
                     :: "r"(sb + (st) * 32768 + 16384 + r * 8192), "l"(&tmo), "r"(bars + (st) * 8), "r"((kt) * 64), "r"(m0 + r * 64), "h"((uint16_t)3) : "memory")
  if (tid == 256) for (int kt = 0; kt < G2_ST; kt++) { mbar_expect_tx(bars + kt * 8, 32768); if (kt < PW) LW(kt, kt); }
  __syncwarp();
  asm volatile("barrier.cluster.wait.acquire.aligned;" ::: "memory");
  if (warp == 8) {
    if (lane == 0) {
      asm volatile("griddepcontrol.wait;" ::: "memory");
      for (int kt = 0; kt < G2_ST; kt++) { LO(kt, kt); if (kt >= PW) LW(kt, kt); }
      for (int kt = G2_ST; kt < 64; kt++) {
        const int st = kt % G2_ST;
        mbar_wait(bars + 64 + st * 8, ((kt / G2_ST) - 1) & 1);
        mbar_expect_tx(bars + st * 8, 32768);
        LO(kt, st); LW(kt, st);
      }
    }
  } else if (warp > 8) {
    const int t = tid - 288, ch = t & 15;
    asm volatile("griddepcontrol.wait;" ::: "memory");
#ifdef PER
    if (t == 0) atomicMax(&g_end[3], gt32());
#endif
    int idx[8];
#pragma unroll
    for (int c = 0; c < 8; c++) idx[c] = g_idx[c];
    const int gi = blockIdx.x * 96 + t;
    if (gi < 67) g_side[gi * 32] = 0u;
    if (gi == 0) g_sbar = 0u;
#pragma unroll 4
    for (int row = t >> 4; row < 128; row += 6) {
      const int tok = m0 + row;
      const uint4 xv = *reinterpret_cast<const uint4*>(x + (size_t)tok * DM + n0 + ch * 8);
      const float g = g_gate[tok], omg = rbf(1.f - g);
      int sel = -1;
#pragma unroll
      for (int c = 0; c < 8; c++) if (idx[c] == tok) sel = c;
      uint4 uv = make_uint4(0u, 0u, 0u, 0u);
      if (sel >= 0) uv = *reinterpret_cast<const uint4*>(g_upd + sel * DM + n0 + ch * 8);
      const uint32_t x4[4] = {xv.x, xv.y, xv.z, xv.w}, u4[4] = {uv.x, uv.y, uv.z, uv.w};
      uint32_t o4[4];
#pragma unroll
      for (int e = 0; e < 4; e++) {
        const float b0 = rbf(u2f(x4[e] << 16) + u2f(u4[e] << 16)), b1 = rbf(u2f(x4[e] & 0xffff0000u) + u2f(u4[e] & 0xffff0000u));
        o4[e] = pack_bf16(omg * b0, omg * b1);
      }
      sts128(sb + G2_TB + row * 256 + ch * 16, o4[0], o4[1], o4[2], o4[3]);
      if (ch == 0) sts32(bars + 512 + row * 4, __float_as_uint(g));
    }
    bar_arrive(2, 352);
  } else {
    const int wg = warp >> 2;
    float d[64];
#pragma unroll
    for (int i = 0; i < 64; i++) d[i] = 0.f;
    const uint32_t e0 = mapa(bars + 64, 0), e1 = mapa(bars + 64, 1);
#ifdef PER
    if (threadIdx.x == 0) { mbar_wait(bars, 0); atomicMax(&g_end[4], gt32()); }
    __syncwarp();
#endif
    for (int kt = 0; kt < 64; kt++) {
      const int st = kt % G2_ST;
      mbar_wait(bars + st * 8, (kt / G2_ST) & 1);
      wg_fence();
#pragma unroll
      for (int kk = 0; kk < G2K; kk++)
        wgmma_n128_ta(d, make_desc(sb + st * 32768 + wg * 8192 + kk * 2048, 1024, 1024), make_desc(sb + st * 32768 + 16384 + kk * 32, 16, 1024));
      wg_commit();
      asm volatile("wgmma.wait_group.sync.aligned 1;" ::: "memory");
      if (kt > 0 && (tid & 127) == 0) { const int ps = (kt - 1) % G2_ST; mbar_arrive_cluster_rlx(e0 + ps * 8); mbar_arrive_cluster_rlx(e1 + ps * 8); }
    }
    wg_wait0();
#ifdef PER
    if (threadIdx.x == 0) atomicMax(&g_end[5], gt32());
#endif
    bar_sync(1, 256);
#pragma unroll
    for (int jj = 0; jj < 8; jj++) {
      const uint32_t q0 = pack_bf16(d[8 * jj], d[8 * jj + 1]), q1 = pack_bf16(d[8 * jj + 2], d[8 * jj + 3]);
      const uint32_t q2 = pack_bf16(d[8 * jj + 4], d[8 * jj + 5]), q3 = pack_bf16(d[8 * jj + 6], d[8 * jj + 7]);
      stsm4t(sb + (jj * 16 + (lane >> 4) * 8 + (lane & 7)) * 272 + (warp * 16 + ((lane >> 3) & 1) * 8) * 2, q0, q1, q2, q3);
    }
    bar_sync(2, 352);
#pragma unroll
    for (int it = 0; it < 8; it++) {
      const int row = it * 16 + (tid >> 4), ch = tid & 15, tok = m0 + row;
      const uint4 av = lds128(sb + row * 272 + ch * 16), tv = lds128(sb + G2_TB + row * 256 + ch * 16);
      const float g = u2f(lds32(bars + 512 + row * 4));
      const uint32_t a4[4] = {av.x, av.y, av.z, av.w}, t4[4] = {tv.x, tv.y, tv.z, tv.w};
      uint32_t o4[4];
#pragma unroll
      for (int e = 0; e < 4; e++)
        o4[e] = pack_bf16(rbf(g * u2f(a4[e] << 16)) + u2f(t4[e] << 16), rbf(g * u2f(a4[e] & 0xffff0000u)) + u2f(t4[e] & 0xffff0000u));
      *reinterpret_cast<uint4*>(out + (size_t)tok * DM + n0 + ch * 8) = make_uint4(o4[0], o4[1], o4[2], o4[3]);
    }
  }
  asm volatile("barrier.cluster.arrive.relaxed.aligned;\nbarrier.cluster.wait.aligned;" ::: "memory");
#ifdef PER
  if (threadIdx.x == 0) atomicMax(&g_end[2], gt32());
#endif
}
#ifndef WPROM
#define WPROM CU_TENSOR_MAP_L2_PROMOTION_L2_128B
#endif
#ifndef PDL
#define PDL 1
#endif
typedef CUresult (*PFN_encodeTiled)(CUtensorMap*, CUtensorMapDataType, cuuint32_t, void*, const cuuint64_t*, const cuuint64_t*,
                                    const cuuint32_t*, const cuuint32_t*, CUtensorMapInterleave, CUtensorMapSwizzle,
                                    CUtensorMapL2promotion, CUtensorMapFloatOOBfill);

extern "C" void kernel_launch(void* const* d_in, const int* in_sizes, int n_in, void* d_out, int out_size) {
  const bf16* x = (const bf16*)d_in[0];
  const bf16* mem0 = (const bf16*)d_in[1];
  const bf16* Wq = (const bf16*)d_in[2];
  const bf16* Wk = (const bf16*)d_in[3];
  const bf16* Wv = (const bf16*)d_in[4];
  const bf16* Wo = (const bf16*)d_in[5];
  const bf16* w_r = (const bf16*)d_in[8];
  const bf16* w_gate = (const bf16*)d_in[9];
  const bf16* w_up = (const bf16*)d_in[10];
  const bf16* w_down = (const bf16*)d_in[11];
  const bf16* gate_w = (const bf16*)d_in[12];
  bf16* out = (bf16*)d_out;

  static PFN_encodeTiled encode = nullptr;
  if (!encode) {
    void* fn = nullptr; cudaDriverEntryPointQueryResult st;
    cudaGetDriverEntryPoint("cuTensorMapEncodeTiled", &fn, cudaEnableDefault, &st);
    encode = (PFN_encodeTiled)fn;
    cudaFuncSetAttribute(rec_kernel, cudaFuncAttributeMaxDynamicSharedMemorySize, SM_TOTAL);
    cudaFuncSetAttribute(gemm2_kernel, cudaFuncAttributeMaxDynamicSharedMemorySize, G2_SMEM);
  }
  CUtensorMap tmx;
  {
    cuuint64_t gd[3] = {64, S_TOK, DM / 64};
    cuuint64_t gs[2] = {DM * 2, 128};
    cuuint32_t bx[3] = {64, SEG, 4};
    cuuint32_t es[3] = {1, 1, 1};
    encode(&tmx, CU_TENSOR_MAP_DATA_TYPE_BFLOAT16, 3, (void*)x, gd, gs, bx, es, CU_TENSOR_MAP_INTERLEAVE_NONE,
           CU_TENSOR_MAP_SWIZZLE_128B, CU_TENSOR_MAP_L2_PROMOTION_L2_128B, CU_TENSOR_MAP_FLOAT_OOB_FILL_NONE);
  }
  bf16* ox;
  cudaGetSymbolAddress((void**)&ox, g_ox);
  CUtensorMap tmo, tmw;
  {
    cuuint64_t gd[2] = {NH * DH, S_TOK}; cuuint64_t gs[1] = {NH * DH * 2}; cuuint32_t bx[2] = {64, 64}; cuuint32_t es[2] = {1, 1};
    encode(&tmo, CU_TENSOR_MAP_DATA_TYPE_BFLOAT16, 2, (void*)ox, gd, gs, bx, es, CU_TENSOR_MAP_INTERLEAVE_NONE,
           CU_TENSOR_MAP_SWIZZLE_128B, CU_TENSOR_MAP_L2_PROMOTION_L2_128B, CU_TENSOR_MAP_FLOAT_OOB_FILL_NONE);
    cuuint64_t gd2[2] = {DM, NH * DH}; cuuint64_t gs2[1] = {DM * 2}; cuuint32_t bx2[2] = {64, 64};
    encode(&tmw, CU_TENSOR_MAP_DATA_TYPE_BFLOAT16, 2, (void*)Wo, gd2, gs2, bx2, es, CU_TENSOR_MAP_INTERLEAVE_NONE,
           CU_TENSOR_MAP_SWIZZLE_128B, CU_TENSOR_MAP_L2_PROMOTION_L2_128B, CU_TENSOR_MAP_FLOAT_OOB_FILL_NONE);
  }
  unsigned char* win;
  cudaGetSymbolAddress((void**)&win, g_win);
  win = (unsigned char*)(((uintptr_t)win + (2u << 20) - 1) & ~(uintptr_t)((2u << 20) - 1));
  WMaps W;
  {
    cuuint64_t gd[2] = {NH * DH, DM}; cuuint64_t gs[1] = {NH * DH * 2}; cuuint32_t b32[2] = {32, 128}, b64[2] = {64, 128}; cuuint32_t es[2] = {1, 1};
    encode(&W.q, CU_TENSOR_MAP_DATA_TYPE_BFLOAT16, 2, (void*)Wq, gd, gs, b32, es, CU_TENSOR_MAP_INTERLEAVE_NONE,
           CU_TENSOR_MAP_SWIZZLE_64B, WPROM, CU_TENSOR_MAP_FLOAT_OOB_FILL_NONE);
    encode(&W.k, CU_TENSOR_MAP_DATA_TYPE_BFLOAT16, 2, (void*)Wk, gd, gs, b32, es, CU_TENSOR_MAP_INTERLEAVE_NONE,
           CU_TENSOR_MAP_SWIZZLE_64B, WPROM, CU_TENSOR_MAP_FLOAT_OOB_FILL_NONE);
    encode(&W.v, CU_TENSOR_MAP_DATA_TYPE_BFLOAT16, 2, (void*)Wv, gd, gs, b64, es, CU_TENSOR_MAP_INTERLEAVE_NONE,
           CU_TENSOR_MAP_SWIZZLE_128B, WPROM, CU_TENSOR_MAP_FLOAT_OOB_FILL_NONE);
  }
  RecParams P{mem0, win};
  SideParams SP{x, w_r, w_gate, w_up, w_down, gate_w, Wo};
  rec_kernel<<<NCTA + 4, 384, SM_TOTAL, cudaStreamPerThread>>>(tmx, tmw, W, P, SP);
  {
    cudaLaunchConfig_t cfg = {};
    cfg.gridDim = dim3(NCTA); cfg.blockDim = dim3(384); cfg.dynamicSmemBytes = G2_SMEM; cfg.stream = cudaStreamPerThread;
    cudaLaunchAttribute at[1];
    at[0].id = cudaLaunchAttributeProgrammaticStreamSerialization; at[0].val.programmaticStreamSerializationAllowed = 1;
    cfg.attrs = at; cfg.numAttrs = PDL;
    cudaLaunchKernelEx(&cfg, gemm2_kernel, tmo, tmw, x, out, win);
  }
}
```

```cpp
#include <cuda_runtime.h>
#include <cuda_bf16.h>
#include <cuda_fp16.h>
#include <cuda.h>
#include <stdint.h>

typedef __nv_bfloat16 bf16;

#define S_TOK 2048
#define DM 1024
#define NH 32
#define DH 128
#define SEG 32
#define NSEG 64
#define FF 3584
#define NCTA 128

static __device__ bf16 g_ox[(size_t)S_TOK * NH * DH];
static __device__ float g_gate[S_TOK];
static __device__ float g_r[S_TOK];
static __device__ int g_idx[8];
static __device__ bf16 g_upd[8 * DM];

static __device__ __forceinline__ float rbf(float v) { return __bfloat162float(__float2bfloat16(v)); }
static __device__ __forceinline__ uint32_t smem_u32(const void* p) { return (uint32_t)__cvta_generic_to_shared(p); }
static __device__ __forceinline__ uint32_t pack_bf16(float lo, float hi) {
  __nv_bfloat162 v = __floats2bfloat162_rn(lo, hi);
  return *reinterpret_cast<uint32_t*>(&v);
}

static __device__ __forceinline__ void wg_fence() { asm volatile("wgmma.fence.sync.aligned;" ::: "memory"); }
static __device__ __forceinline__ void wg_commit() { asm volatile("wgmma.commit_group.sync.aligned;" ::: "memory"); }
static __device__ __forceinline__ void wg_wait0() { asm volatile("wgmma.wait_group.sync.aligned 0;" ::: "memory"); }
static __device__ __forceinline__ void fence_async_smem() { asm volatile("fence.proxy.async.shared::cta;" ::: "memory"); }

static __device__ __forceinline__ uint64_t make_desc(uint32_t addr, uint32_t lbo, uint32_t sbo) {
  uint64_t d = 0;
  d |= (uint64_t)((addr & 0x3FFFF) >> 4);
  d |= (uint64_t)((lbo >> 4) & 0x3FFF) << 16;
  d |= (uint64_t)((sbo >> 4) & 0x3FFF) << 32;
  d |= (uint64_t)1 << 62;
  return d;
}

#define DESC_HI(sbo) (((sbo) >> 4) | (1u << 30))
template <int OFF, int SCALE>
static __device__ __forceinline__ void wgmma_n32_ra(float (&d)[16], const uint32_t (&a)[4], uint32_t base16) {
  asm volatile(
      "{\n.reg .b32 t;\n.reg .b64 dd;\nadd.u32 t, %20, %21;\nmov.b64 dd, {t, %22};\n"
      "wgmma.mma_async.sync.aligned.m64n32k16.f32.bf16.bf16 "
      "{%0,%1,%2,%3,%4,%5,%6,%7,%8,%9,%10,%11,%12,%13,%14,%15}, {%16,%17,%18,%19}, dd, %23, 1, 1, 0;\n}"
      : "+f"(d[0]), "+f"(d[1]), "+f"(d[2]), "+f"(d[3]), "+f"(d[4]), "+f"(d[5]), "+f"(d[6]), "+f"(d[7]),
        "+f"(d[8]), "+f"(d[9]), "+f"(d[10]), "+f"(d[11]), "+f"(d[12]), "+f"(d[13]), "+f"(d[14]), "+f"(d[15])
      : "r"(a[0]), "r"(a[1]), "r"(a[2]), "r"(a[3]), "r"(base16), "n"(OFF >> 4), "n"(DESC_HI(1024)), "n"(SCALE));
}
template <int AOFF, int BOFF, int SCALE>
static __device__ __forceinline__ void wgmma_n32_ss_ta(float (&d)[16], uint32_t abase16, uint32_t bbase16) {
  asm volatile(
      "{\n.reg .b32 t, u;\n.reg .b64 da, db;\nadd.u32 t, %16, %18;\nmov.b64 da, {t, %20};\nadd.u32 u, %17, %19;\nmov.b64 db, {u, %20};\n"
      "wgmma.mma_async.sync.aligned.m64n32k16.f32.bf16.bf16 "
      "{%0,%1,%2,%3,%4,%5,%6,%7,%8,%9,%10,%11,%12,%13,%14,%15}, da, db, %21, 1, 1, 1, 0;\n}"
      : "+f"(d[0]), "+f"(d[1]), "+f"(d[2]), "+f"(d[3]), "+f"(d[4]), "+f"(d[5]), "+f"(d[6]), "+f"(d[7]),
        "+f"(d[8]), "+f"(d[9]), "+f"(d[10]), "+f"(d[11]), "+f"(d[12]), "+f"(d[13]), "+f"(d[14]), "+f"(d[15])
      : "r"(abase16), "r"(bbase16), "n"(AOFF >> 4), "n"(BOFF >> 4), "n"(DESC_HI(1024)), "n"(SCALE));
}
static __device__ __forceinline__ void ldmatrix_x4_trans(uint32_t (&r)[4], uint32_t addr) {
  asm volatile("ldmatrix.sync.aligned.m8n8.x4.trans.shared.b16 {%0,%1,%2,%3}, [%4];"
               : "=r"(r[0]), "=r"(r[1]), "=r"(r[2]), "=r"(r[3]) : "r"(addr) : "memory");
}
static __device__ __forceinline__ void mma_16816(float (&d)[4], const uint32_t (&a)[4], uint32_t b0, uint32_t b1) {
  asm volatile("mma.sync.aligned.m16n8k16.row.col.f32.bf16.bf16.f32 {%0,%1,%2,%3}, {%4,%5,%6,%7}, {%8,%9}, {%0,%1,%2,%3};"
               : "+f"(d[0]), "+f"(d[1]), "+f"(d[2]), "+f"(d[3])
               : "r"(a[0]), "r"(a[1]), "r"(a[2]), "r"(a[3]), "r"(b0), "r"(b1));
}

static __device__ __forceinline__ uint32_t mapa(uint32_t addr, uint32_t rank) {
  uint32_t r; asm volatile("mapa.shared::cluster.u32 %0, %1, %2;" : "=r"(r) : "r"(addr), "r"(rank)); return r;
}

static __device__ __forceinline__ void mbar_init(uint32_t bar, int cnt) {
  asm volatile("mbarrier.init.shared::cta.b64 [%0], %1;" :: "r"(bar), "r"(cnt) : "memory");
}
static __device__ __forceinline__ void mbar_expect_tx(uint32_t bar, uint32_t bytes) {
  asm volatile("mbarrier.arrive.expect_tx.shared::cta.b64 _, [%0], %1;" :: "r"(bar), "r"(bytes) : "memory");
}
static __device__ __forceinline__ void tma_load_2d(uint32_t dst, const CUtensorMap* tm, int c0, int c1, uint32_t bar) {
  asm volatile("cp.async.bulk.tensor.2d.shared::cluster.global.mbarrier::complete_tx::bytes [%0], [%1, {%3, %4}], [%2];"
               :: "r"(dst), "l"(tm), "r"(bar), "r"(c0), "r"(c1) : "memory");
}

static __device__ unsigned char g_win[6 << 20];
static __device__ unsigned int g_side[67 * 32];
static __device__ unsigned int g_err;
#define W_UP (1u << 20)
#define W_2 (2u << 20)
static __device__ __forceinline__ uint32_t w_blk(uint32_t off, uint32_t side) { return off | (((__popc((off >> 12) & 0xb3u) ^ side) & 1u) << 12); }
static __device__ __forceinline__ uint32_t w_h1(int c) { return W_UP | (1u << 13) | ((c >> 1) << 14) | ((c & 1) << 11); }
#define W_DS 0x30000u
static __device__ __forceinline__ uint32_t w_ar(int s) { return ((s & 1) << 15) | ((s & 2) << 17); }
static __device__ __forceinline__ uint32_t w_mvx(int c, int s) { return W_2 | ((s & 1) << 20) | ((c >> 1) << 14) | ((c & 1) << 11); }
static __device__ __forceinline__ uint32_t w_mxa(int c, int s) { return W_2 | ((s & 1) << 20) | (1u << 13) | ((c >> 1) << 14) | ((c & 1) << 11); }
#define H1_V (1u << 13)

#define SPIN_LIMIT (1 << 18)

#define SM_X 0
#define SM_WOS 65536
#define SM_WVS 131072
#define SM_MEM 163840
#define SM_QKP 180224
#define SM_VP 184320
#define SM_CW 188416
#define SM_VST 196608
#define SM_VR 196608
#define SM_CQ 200704
#define SM_CV 208896
#define SM_XF 217088
#define SM_VL 221184
#define SM_OF 225280
#define SM_OX 227328
#define SM_PF 229376
#define SM_PX 230016
#define SM_RD 198656
#define SM_QA 230656
#define SM_XS 231168
#define SM_BAR 231808
#define SM_Z 231936
#define SM_TOTAL 232128
#define MB_F 0
#define MB_XE0 16
#define MB_XE1 112
#define MB_INIT 24
#define MB_MEM 32
#define MB_W 256
#define MB_XF 64
#define MB_VR 72
#define MB_X0 80
#define MB_WO 88
#define SM_SIDE (SM_BAR + 96)
#define B_QK 1
#define B_V 2
#define B_P 3
#define B_O 4
#define B_O2 5
#define B_PUB 6
#define B_CQ 7
#define B_QK1 8
#define B_PXF 10
#define B_CV 15
#define B_X2 11
#define B_PX 12
#define B_GO 14
#define B_G1 13

#ifdef PROF
__device__ unsigned int g_ts[NCTA][80][32];
#ifdef GT
#define TCLK() gt32()
#else
#define TCLK() clk32()
#endif
#ifndef TMASK
#define TMASK 0xffffffffu
#endif
#define TST(st, i, c, v) do { if ((TMASK >> (i)) & 1u) asm volatile("{\n.reg .pred q;\nsetp.eq.u32 q, %2, 0;\n@q st.global.u32 [%0], %1;\n}" :: "l"(&g_ts[cta][(st) + 1][i]), "r"((uint32_t)(v)), "r"((uint32_t)(c)) : "memory"); } while (0)
#define TS(i) TST(s, i, l16, TCLK())
#define TV(i, v) TST(s, i, l16, v)
#define TSF(i, w) TST(s, i, l16 | (w8 ^ (w)), TCLK())
#define TSP(i, w) TST(s - 1, i, l16 | (w8 ^ (w)), TCLK())
#define TVF(i, v) TV(i, v)
#else
#define TST(a, b, c, d)
#define TSF(i, w)
#define TSP(i, w)
#define TVF(i, v)
#define TS(i)
#define TV(i, v)
#endif

static __device__ __forceinline__ void bar_sync(int id, int n) { asm volatile("bar.sync %0, %1;" :: "r"(id), "r"(n) : "memory"); }
static __device__ __forceinline__ void bar_arrive(int id, int n) { asm volatile("bar.arrive %0, %1;" :: "r"(id), "r"(n) : "memory"); }
static __device__ __forceinline__ uint4 ldg_r4(const void* p) { uint4 v;
  asm volatile("ld.relaxed.gpu.global.v4.u32 {%0,%1,%2,%3}, [%4];" : "=r"(v.x), "=r"(v.y), "=r"(v.z), "=r"(v.w) : "l"(p) : "memory"); return v; }
static __device__ __forceinline__ uint32_t ldg_r1(const void* p) { uint32_t v;
  asm volatile("ld.relaxed.gpu.global.u32 %0, [%1];" : "=r"(v) : "l"(p) : "memory"); return v; }
static __device__ __forceinline__ void stg_r4(void* p, uint32_t a, uint32_t b, uint32_t c, uint32_t d) {
  asm volatile("st.relaxed.gpu.global.v4.u32 [%0], {%1,%2,%3,%4};" :: "l"(p), "r"(a), "r"(b), "r"(c), "r"(d) : "memory"); }
static __device__ __forceinline__ uint2 ldg_r2(const void* p) { uint2 v;
  asm volatile("ld.relaxed.gpu.global.v2.u32 {%0,%1}, [%2];" : "=r"(v.x), "=r"(v.y) : "l"(p) : "memory"); return v; }
static __device__ __forceinline__ void stg_4(void* p, const uint4& v) {
  asm volatile("st.global.v4.u32 [%0], {%1,%2,%3,%4};" :: "l"(p), "r"(v.x), "r"(v.y), "r"(v.z), "r"(v.w) : "memory"); }
static __device__ __forceinline__ uint32_t f2u(float v) { return __float_as_uint(v); }
static __device__ __forceinline__ void stg_2(void* p, uint32_t a, uint32_t b) {
  asm volatile("st.global.v2.u32 [%0], {%1,%2};" :: "l"(p), "r"(a), "r"(b) : "memory"); }
static __device__ __forceinline__ void stg_r1(void* p, uint32_t a) {
  asm volatile("st.relaxed.gpu.global.u32 [%0], %1;" :: "l"(p), "r"(a) : "memory"); }
static __device__ __forceinline__ void sts128(uint32_t a, uint32_t x, uint32_t y, uint32_t z, uint32_t w) {
  asm volatile("st.shared.v4.u32 [%0], {%1,%2,%3,%4};" :: "r"(a), "r"(x), "r"(y), "r"(z), "r"(w) : "memory"); }
static __device__ __forceinline__ void sts128f(uint32_t a, float x, float y, float z, float w) {
  asm volatile("st.shared.v4.f32 [%0], {%1,%2,%3,%4};" :: "r"(a), "f"(x), "f"(y), "f"(z), "f"(w) : "memory"); }
static __device__ __forceinline__ uint4 lds128(uint32_t a) { uint4 v;
  asm volatile("ld.shared.v4.u32 {%0,%1,%2,%3}, [%4];" : "=r"(v.x), "=r"(v.y), "=r"(v.z), "=r"(v.w) : "r"(a) : "memory"); return v; }
static __device__ __forceinline__ float4 lds128f(uint32_t a) { float4 v;
  asm volatile("ld.shared.v4.f32 {%0,%1,%2,%3}, [%4];" : "=f"(v.x), "=f"(v.y), "=f"(v.z), "=f"(v.w) : "r"(a) : "memory"); return v; }
static __device__ __forceinline__ void sts32(uint32_t a, uint32_t x) { asm volatile("st.shared.u32 [%0], %1;" :: "r"(a), "r"(x) : "memory"); }
static __device__ __forceinline__ uint2 lds64(uint32_t a) { uint2 v;
  asm volatile("ld.shared.v2.u32 {%0,%1}, [%2];" : "=r"(v.x), "=r"(v.y) : "r"(a) : "memory"); return v; }
static __device__ __forceinline__ void st_async4(uint32_t ra, float x, float y, float z, float w, uint32_t rbar) {
  asm volatile("st.async.weak.shared::cluster.mbarrier::complete_tx::bytes.v4.f32 [%0], {%1,%2,%3,%4}, [%5];"
               :: "r"(ra), "f"(x), "f"(y), "f"(z), "f"(w), "r"(rbar) : "memory"); }
static __device__ __forceinline__ void stsm4t(uint32_t a, uint32_t x, uint32_t y, uint32_t z, uint32_t w) {
  asm volatile("stmatrix.sync.aligned.m8n8.x4.trans.shared.b16 [%0], {%1,%2,%3,%4};" :: "r"(a), "r"(x), "r"(y), "r"(z), "r"(w) : "memory"); }
static __device__ __forceinline__ uint32_t hmax2(uint32_t a, uint32_t b) { uint32_t d;
  asm("max.f16x2 %0, %1, %2;" : "=r"(d) : "r"(a), "r"(b)); return d; }
static __device__ __forceinline__ uint32_t hadd2(uint32_t a, uint32_t b) { uint32_t d;
  asm("add.rn.f16x2 %0, %1, %2;" : "=r"(d) : "r"(a), "r"(b)); return d; }
static __device__ __forceinline__ uint32_t packv(float a, float b, float c, float d) { uint32_t r;
  asm volatile("{\n.reg .f32 x, y;\nadd.f32 x, %1, %2;\nadd.f32 y, %3, %4;\ncvt.rn.bf16x2.f32 %0, y, x;\n}" : "=r"(r) : "f"(a), "f"(b), "f"(c), "f"(d)); return r; }
static __device__ __forceinline__ float ex2v(float a, float b, float c) { float y;
  asm volatile("{\n.reg .f32 x;\nfma.rn.f32 x, %1, %2, %3;\nex2.approx.ftz.f32 %0, x;\n}" : "=f"(y) : "f"(a), "f"(b), "f"(c)); return y; }
static __device__ __forceinline__ uint32_t shfl_x(uint32_t a, int m) { uint32_t d;
  asm volatile("shfl.sync.bfly.b32 %0, %1, %2, 0x1f, 0xffffffff;" : "=r"(d) : "r"(a), "r"(m)); return d; }
static __device__ __forceinline__ void h2f(float& lo, float& hi, uint32_t a) {
  asm volatile("{\n.reg .b16 l, h;\nmov.b32 {l, h}, %2;\ncvt.f32.f16 %0, l;\ncvt.f32.f16 %1, h;\n}" : "=f"(lo), "=f"(hi) : "r"(a)); }
static __device__ __forceinline__ uint4 ldsm4(uint32_t a) { uint4 v;
  asm volatile("ldmatrix.sync.aligned.m8n8.x4.shared.b16 {%0,%1,%2,%3}, [%4];" : "=r"(v.x), "=r"(v.y), "=r"(v.z), "=r"(v.w) : "r"(a) : "memory"); return v; }
static __device__ __forceinline__ uint4 ldsm4t(uint32_t a) { uint4 v;
  asm volatile("ldmatrix.sync.aligned.m8n8.x4.trans.shared.b16 {%0,%1,%2,%3}, [%4];" : "=r"(v.x), "=r"(v.y), "=r"(v.z), "=r"(v.w) : "r"(a) : "memory"); return v; }
static __device__ __forceinline__ uint32_t movm(uint32_t a) { uint32_t d;
  asm volatile("movmatrix.sync.aligned.m8n8.trans.b16 %0, %1;" : "=r"(d) : "r"(a)); return d; }
static __device__ __forceinline__ float u2f(uint32_t v) { return __uint_as_float(v); }
static __device__ __forceinline__ uint32_t tagw(uint32_t w, uint32_t t) { uint32_t d;
  asm("lop3.b32 %0, %1, %2, 1, 0xd8;" : "=r"(d) : "r"(w), "r"(t)); return d; }
static __device__ __forceinline__ uint32_t pack_f16(float lo, float hi) { uint32_t d;
  asm("cvt.rn.satfinite.f16x2.f32 %0, %1, %2;" : "=r"(d) : "f"(hi), "f"(lo)); return d; }
static __device__ __forceinline__ void sum_h4(float& lo, float& hi, uint32_t a, uint32_t b, uint32_t c, uint32_t d) {
  const float2 x = __half22float2(*reinterpret_cast<__half2*>(&a)), y = __half22float2(*reinterpret_cast<__half2*>(&b));
  const float2 z = __half22float2(*reinterpret_cast<__half2*>(&c)), w = __half22float2(*reinterpret_cast<__half2*>(&d));
  lo = (x.x + y.x) + (z.x + w.x); hi = (x.y + y.y) + (z.y + w.y);
}
static __device__ __forceinline__ uint32_t lds32(uint32_t a) { uint32_t v; asm volatile("ld.shared.u32 %0, [%1];" : "=r"(v) : "r"(a) : "memory"); return v; }
static __device__ __forceinline__ uint32_t addb2(uint32_t a, uint32_t b) { uint32_t d;
  asm("add.rn.bf16x2 %0, %1, %2;" : "=r"(d) : "r"(a), "r"(b)); return d; }
static __device__ __forceinline__ uint32_t mulb2(uint32_t a, uint32_t b) { uint32_t d;
  asm("mul.rn.bf16x2 %0, %1, %2;" : "=r"(d) : "r"(a), "r"(b)); return d; }
static __device__ __forceinline__ uint32_t mulb2v(uint32_t a, uint32_t b) { uint32_t d;
  asm volatile("mul.rn.bf16x2 %0, %1, %2;" : "=r"(d) : "r"(a), "r"(b)); return d; }
static __device__ __forceinline__ uint32_t x3(uint32_t a, uint32_t b, uint32_t t) { uint32_t d;
  asm("lop3.b32 %0, %1, %2, %3, 0x7e;" : "=r"(d) : "r"(a), "r"(b), "r"(t)); return d; }
static __device__ __forceinline__ uint32_t or3(uint32_t a, uint32_t b, uint32_t c) { uint32_t d;
  asm("lop3.b32 %0, %1, %2, %3, 0xfe;" : "=r"(d) : "r"(a), "r"(b), "r"(c)); return d; }
static __device__ __forceinline__ float ex2(float x) { float y; asm("ex2.approx.ftz.f32 %0, %1;" : "=f"(y) : "f"(x)); return y; }
static __device__ __forceinline__ float rcpf(float x) { float y; asm("rcp.approx.ftz.f32 %0, %1;" : "=f"(y) : "f"(x)); return y; }
static __device__ __forceinline__ void mbar_wait(uint32_t bar, int parity) {
  asm volatile("{\n.reg .pred p, q;\n.reg .u32 n;\nmbarrier.try_wait.parity.shared::cta.b64 p, [%0], %1;\n@p bra W_DONE;\nmov.u32 n, 0;\n"
               "W_LOOP:\nmbarrier.try_wait.parity.shared::cta.b64 p, [%0], %1;\nadd.u32 n, n, 1;\nsetp.lt.and.u32 q, n, %2, !p;\n@q bra W_LOOP;\nW_DONE:\n}"
               :: "r"(bar), "r"(parity), "n"(SPIN_LIMIT) : "memory");
}
static __device__ __forceinline__ uint32_t mbar_test(uint32_t bar, int parity) { uint32_t ok;
  asm volatile("{\n.reg .pred p;\nmbarrier.test_wait.parity.shared::cta.b64 p, [%1], %2;\nselp.u32 %0, 1, 0, p;\n}" : "=r"(ok) : "r"(bar), "r"(parity) : "memory"); return ok; }
static __device__ __forceinline__ void mbar_arrive(uint32_t bar) {
  asm volatile("mbarrier.arrive.shared::cta.b64 _, [%0];" :: "r"(bar) : "memory"); }
static __device__ __forceinline__ void mbar_arrive_cluster_rlx(uint32_t raddr) {
  asm volatile("mbarrier.arrive.relaxed.cluster.shared::cluster.b64 _, [%0];" :: "r"(raddr) : "memory"); }
static __device__ __forceinline__ void tma_load_mc(uint32_t dst, const CUtensorMap* tm, int c1, int c2, uint32_t bar) {
#ifdef NOTMA
  if ((NOTMA >> (c2 >> 3)) & 1) asm volatile("mbarrier.complete_tx.relaxed.cta.shared::cta.b64 [%0], 32768;" :: "r"(bar) : "memory"); else
#endif
  asm volatile("cp.async.bulk.tensor.3d.shared::cluster.global.mbarrier::complete_tx::bytes.multicast::cluster [%0], [%1, {%3, %4, %5}], [%2], %6;"
               :: "r"(dst), "l"(tm), "r"(bar), "r"(0), "r"(c1), "r"(c2), "h"((uint16_t)3) : "memory"); }
static __device__ __forceinline__ void cp16(uint32_t dst, const void* src) {
  asm volatile("cp.async.cg.shared.global [%0], [%1], 16;" :: "r"(dst), "l"(src) : "memory"); }
static __device__ __forceinline__ void mma_1688(float (&d)[4], uint32_t a0, uint32_t a1, uint32_t b0) {
  asm volatile("mma.sync.aligned.m16n8k8.row.col.f32.bf16.bf16.f32 {%0,%1,%2,%3}, {%4,%5}, {%6}, {%0,%1,%2,%3};"
               : "+f"(d[0]), "+f"(d[1]), "+f"(d[2]), "+f"(d[3]) : "r"(a0), "r"(a1), "r"(b0)); }
static __device__ __forceinline__ void mma4(float (&d)[4], uint32_t a0, uint32_t a1, uint32_t a2, uint32_t a3, uint32_t b0, uint32_t b1) {
  asm volatile("mma.sync.aligned.m16n8k16.row.col.f32.bf16.bf16.f32 {%0,%1,%2,%3}, {%4,%5,%6,%7}, {%8,%9}, {%0,%1,%2,%3};"
               : "+f"(d[0]), "+f"(d[1]), "+f"(d[2]), "+f"(d[3]) : "r"(a0), "r"(a1), "r"(a2), "r"(a3), "r"(b0), "r"(b1)); }
static __device__ __forceinline__ void mma4z(float (&d)[4], uint32_t a0, uint32_t a1, uint32_t a2, uint32_t a3, uint32_t b0, uint32_t b1) {
  asm volatile("mma.sync.aligned.m16n8k16.row.col.f32.bf16.bf16.f32 {%0,%1,%2,%3}, {%4,%5,%6,%7}, {%8,%9}, {%10,%10,%10,%10};"
               : "=f"(d[0]), "=f"(d[1]), "=f"(d[2]), "=f"(d[3]) : "r"(a0), "r"(a1), "r"(a2), "r"(a3), "r"(b0), "r"(b1), "f"(0.f)); }
static __device__ __forceinline__ uint32_t clk32() { uint32_t t; asm volatile("mov.u32 %0, %%clock;" : "=r"(t)); return t; }
static __device__ __forceinline__ uint32_t gt32() { uint32_t t; asm volatile("mov.u32 %0, %%globaltimer_lo;" : "=r"(t)); return t; }
static __device__ __forceinline__ void spin(int clk) { if (clk > 0) { uint32_t t = clk32(); while (clk32() - t < (uint32_t)clk) {} } }
#define FENCE() asm volatile("griddepcontrol.launch_dependents;" ::: "memory")
#define OPAQUE_L(p) asm volatile("" : "+l"(p))
#define OPAQUE_R(p) asm volatile("" : "+r"(p))

template <int KK, int K1, int W0, int NW, int FIRST> struct XR {
  static __device__ __forceinline__ void run(float (&d)[16], const uint32_t (&w)[NW][4], uint32_t b16) {
#ifdef NOWG
    if (KK % NOWG == 0)
#endif
    wgmma_n32_ra<(KK >> 2) * 4096 + (KK & 3) * 32, !FIRST>(d, w[W0 + KK], b16);
    XR<KK + 1, K1, W0, NW, 0>::run(d, w, b16);
  }
};
template <int K1, int W0, int NW, int FIRST> struct XR<K1, K1, W0, NW, FIRST> { static __device__ __forceinline__ void run(float (&)[16], const uint32_t (&)[NW][4], uint32_t) {} };
template <int KK, int K0, int K1, int FIRST> struct XS {
  static __device__ __forceinline__ void run(float (&d)[16], uint32_t a16, uint32_t b16) {
#ifdef NOWG
    if (KK % NOWG == 0)
#endif
    wgmma_n32_ss_ta<(KK - K0) * 2048, (KK >> 2) * 4096 + (KK & 3) * 32, !FIRST>(d, a16, b16);
    XS<KK + 1, K0, K1, 0>::run(d, a16, b16);
  }
};
template <int K0, int K1, int FIRST> struct XS<K1, K0, K1, FIRST> { static __device__ __forceinline__ void run(float (&)[16], uint32_t, uint32_t) {} };

static __device__ bf16 g_h[8 * FF];
static __device__ unsigned int g_sbar;
struct SideParams { const bf16* x; const bf16* w_r; const bf16* w_gate; const bf16* w_up; const bf16* w_down; const bf16* gate_w; const bf16* Wo; };

static __device__ __forceinline__ void side_barrier(unsigned int target) {
  __syncthreads();
  if (threadIdx.x == 0) {
    __threadfence();
    atomicAdd(&g_sbar, 1u);
    int n = 0;
    while (*(volatile unsigned int*)&g_sbar < target) { if (++n > (1 << 22)) { g_err = 50; break; } }
    __threadfence();
  }
  __syncthreads();
}
static __device__ __forceinline__ uint4 ldg_nc(const void* p) { uint4 v;
  asm volatile("ld.global.nc.L1::no_allocate.v4.u32 {%0,%1,%2,%3}, [%4];" : "=r"(v.x), "=r"(v.y), "=r"(v.z), "=r"(v.w) : "l"(p)); return v; }
#ifndef SPD
#define SPD 3
#endif
static __device__ __forceinline__ void l2pf(const void* p) { asm volatile("prefetch.global.L2 [%0];" :: "l"(p)); }
static __device__ __forceinline__ void mm8(float (&acc)[8][4], const bf16* W, const bf16* Wn, int ldw, int nk16, uint32_t abase, uint32_t ring, int lane) {
  const int rw = lane >> 3, ch = lane & 7;
  const bf16* wp = W + (size_t)rw * ldw + ch * 8;
  const uint32_t wd = ring + rw * 128, rd = ring + ((rw & 1) * 8 + ch) * 128;
#define MM_LD(k) do { if ((k) < nk16) { const bf16* q = wp + (size_t)(k) * 16 * ldw; \
    _Pragma("unroll") for (int i = 0; i < 4; i++) cp16(wd + ((k) & 3) * 2048 + i * 512 + ((ch ^ (rw + (i & 1) * 4)) << 4), q + (size_t)(4 * i) * ldw); } \
    asm volatile("cp.async.commit_group;" ::: "memory"); } while (0)
  __syncwarp();
  MM_LD(0); MM_LD(1); MM_LD(2);
#pragma unroll 1
  for (int k = 0; k < nk16; k++) {
    if ((k & 1) == 0) {
      const int kp = k + 4 * SPD;
      const bf16* pf = kp < nk16 ? W + (size_t)(kp * 16) * ldw : Wn ? Wn + (size_t)((kp - nk16) * 16) * ldw : nullptr;
      if (pf) l2pf(pf + (size_t)lane * ldw);
    }
    asm volatile("cp.async.wait_group 2;" ::: "memory");
    __syncwarp();
    MM_LD(k + 3);
    const uint32_t a0 = lds32(abase + k * 32), a2 = lds32(abase + k * 32 + 16);
#pragma unroll
    for (int i = 0; i < 4; i++) {
      const uint4 b = ldsm4t(rd + (k & 3) * 2048 + (((2 * i + (rw >> 1)) ^ ch) << 4));
      mma4(acc[2 * i], a0, 0u, a2, 0u, b.x, b.y); mma4(acc[2 * i + 1], a0, 0u, a2, 0u, b.z, b.w);
    }
  }
}
static __device__ __noinline__ void side_work(const SideParams& P, unsigned char* smem, int q) {
  const int tid = threadIdx.x, lane = tid & 31, warp = tid >> 5, g = lane >> 2, t = lane & 3;
  const uint32_t sb = smem_u32(smem);
  unsigned int* cand = reinterpret_cast<unsigned int*>(smem);
  bf16* xs = reinterpret_cast<bf16*>(smem + 1024);
  float* part = reinterpret_cast<float*>(smem + 65536);
  {
    for (int i = tid; i < 256; i += 384) *reinterpret_cast<uint4*>(smem + 1024 + i * 16) = ldg_nc((i < 128 ? P.gate_w : P.w_r - DM) + i * 8);
    __syncthreads();
#pragma unroll 1
    for (int it = warp; it < 64; it += 12) {
      const bf16* xp = P.x + (size_t)(q * 512 + (it >> 1) * 16 + g) * DM + (it & 1) * 512 + t * 8;
      for (int a = it == warp ? 0 : 1; a < 2 && it + 12 * a < 64; a++)
#pragma unroll
        for (int i = 0; i < 4; i++) l2pf(P.x + (size_t)(q * 512 + (it >> 1) * 16 + a * 96 + i * 4 + (lane >> 3)) * DM + (it & 1) * 512 + (lane & 7) * 64);
      const uint32_t xb = sb + 16384 + warp * 16384 + lane * 16;
#pragma unroll
      for (int i = 0; i < 16; i++) { cp16(xb + i * 1024, xp + i * 32); cp16(xb + i * 1024 + 512, xp + 8 * DM + i * 32); }
      asm volatile("cp.async.commit_group;\ncp.async.wait_group 0;" ::: "memory");
      float sg[4] = {0.f, 0.f, 0.f, 0.f}, sr[4] = {0.f, 0.f, 0.f, 0.f};
#pragma unroll
      for (int i = 0; i < 16; i++) {
        const uint4 gw = lds128(sb + 1024 + (it & 1) * 1024 + i * 64 + t * 16), wr = lds128(sb + 3072 + (it & 1) * 1024 + i * 64 + t * 16);
        const uint4 lo = lds128(xb + i * 1024), hi = lds128(xb + i * 1024 + 512);
        mma4(sr, lo.x, hi.x, lo.y, hi.y, wr.x, wr.y); mma4(sr, lo.z, hi.z, lo.w, hi.w, wr.z, wr.w);
        mma4(sg, mulb2(lo.x, gw.x), mulb2(hi.x, gw.x), mulb2(lo.y, gw.y), mulb2(hi.y, gw.y), 0x3F803F80u, 0x3F803F80u);
        mma4(sg, mulb2(lo.z, gw.z), mulb2(hi.z, gw.z), mulb2(lo.w, gw.w), mulb2(hi.w, gw.w), 0x3F803F80u, 0x3F803F80u);
      }
      if (t == 0) {
        float* pp = reinterpret_cast<float*>(smem + 8192) + (it & 1) * 1024 + (it >> 1) * 16 + g;
        pp[0] = sg[0]; pp[8] = sg[2]; pp[512] = sr[0]; pp[520] = sr[2];
      }
    }
    __syncthreads();
    for (int i = tid; i < 512; i += 384) {
      const float* pp = reinterpret_cast<const float*>(smem + 8192);
      g_gate[q * 512 + i] = rbf(1.f / (1.f + expf(-rbf(pp[i] + pp[1024 + i]))));
      g_r[q * 512 + i] = rbf(pp[512 + i] + pp[1536 + i]);
    }
    for (int i = tid; i < 16 * 896; i += 384) part[i] = 0.f;
  }
#define GU(u) (((u) % 28) / 14 ? P.w_up : P.w_gate) + (size_t)((u) / 28) * 512 * FF + q * 896 + ((u) % 14) * 64
  for (int i = lane; i < 64 * SPD; i += 32) l2pf(GU(warp) + (size_t)i * FF);
  side_barrier(4);
  {
    unsigned int key[8];
#pragma unroll
    for (int i = 0; i < 8; i++) {
      const int tok = (warp & 7) * 256 + i * 32 + lane;
      const uint32_t b = __float_as_uint(__ldcg(&g_r[tok]) + 0.f) >> 16;
      key[i] = (((b & 0x8000u) ? (~b & 0xffffu) : (b | 0x8000u)) << 16) | (uint32_t)(2047 - tok);
    }
    for (int pass = 0; pass < 2; pass++) {
      if (pass == 0 ? warp < 8 : warp == 0) {
        for (int c = 0; c < 8; c++) {
          const unsigned int m = __reduce_max_sync(~0u, max(max(max(key[0], key[1]), max(key[2], key[3])), max(max(key[4], key[5]), max(key[6], key[7]))));
#pragma unroll
          for (int i = 0; i < 8; i++) if (key[i] == m) key[i] = 0u;
          if (lane == 0) cand[pass ? 128 + c : warp * 8 + c] = m;
        }
      }
      __syncthreads();
      if (pass == 0 && warp == 0) {
#pragma unroll
        for (int i = 0; i < 8; i++) key[i] = i < 2 ? cand[i * 32 + lane] : 0u;
      }
    }
    if (q == 0 && tid < 8) g_idx[tid] = 2047 - (int)(cand[128 + tid] & 0xffffu);
    for (int i = tid; i < 1024; i += 384) {
      const int c = i >> 7, tok = 2047 - (int)(cand[128 + c] & 0xffffu);
      *reinterpret_cast<uint4*>(xs + c * (FF + 8) + (i & 127) * 8) = ldg_nc(P.x + (size_t)tok * DM + (i & 127) * 8);
    }
    __syncthreads();
  }
  const uint32_t abase = sb + 1024 + g * (FF + 8) * 2 + t * 4, ring = sb + 131072 + warp * 8192;
  for (int u = warp; u < 56; u += 12) {
    const int kh = u / 28, mat = (u % 28) / 14, cb = u % 14;
    float acc[8][4];
#pragma unroll
    for (int i = 0; i < 8; i++) acc[i][0] = acc[i][1] = acc[i][2] = acc[i][3] = 0.f;
    mm8(acc, GU(u), u + 12 < 56 ? GU(u + 12) : nullptr, FF, DM / 32, abase + kh * 1024, ring, lane);
    float* pp = part + (mat * 8 + g) * 896 + cb * 64 + 2 * t;
#pragma unroll
    for (int i = 0; i < 8; i++) { atomicAdd(pp + 8 * i, acc[i][0]); atomicAdd(pp + 8 * i + 1, acc[i][1]); }
  }
  for (int i = lane; i < 64 * SPD; i += 32) l2pf(P.w_down + (size_t)((warp >> 2) * 1216 + i) * DM + q * 256 + (warp & 3) * 64);
  __syncthreads();
  for (int i = tid; i < 8 * 896; i += 384) {
    const float ag = rbf(part[i]), au = rbf(part[8 * 896 + i]);
    g_h[(i / 896) * FF + q * 896 + i % 896] = __float2bfloat16(rbf(ag / (1.f + expf(-ag))) * au);
  }
  side_barrier(8);
  for (int i = tid; i < 8 * FF / 8; i += 384) {
    const int c = i / (FF / 8), o = i % (FF / 8);
    *reinterpret_cast<uint4*>(xs + c * (FF + 8) + o * 8) = __ldcg(reinterpret_cast<const uint4*>(g_h + c * FF + o * 8));
  }
  __syncthreads();
  {
    const int cb = warp & 3, kq = warp >> 2;
    float acc[8][4];
#pragma unroll
    for (int i = 0; i < 8; i++) acc[i][0] = acc[i][1] = acc[i][2] = acc[i][3] = 0.f;
    mm8(acc, P.w_down + (size_t)kq * 1216 * DM + q * 256 + cb * 64, nullptr, DM, kq == 2 ? 72 : 76, abase + kq * 1216 * 2, ring, lane);
#pragma unroll
    for (int i = 0; i < 8; i++) { part[(kq * 8 + g) * 256 + cb * 64 + 2 * t + 8 * i] = acc[i][0]; part[(kq * 8 + g) * 256 + cb * 64 + 2 * t + 8 * i + 1] = acc[i][1]; }
    __syncthreads();
    for (int i = tid; i < 2048; i += 384) {
      const int c = i >> 8, tok = 2047 - (int)(cand[128 + c] & 0xffffu);
      const float y = (part[i] + part[2048 + i]) + part[4096 + i];
      const float rs = rbf(1.f / (1.f + expf(-__ldcg(&g_r[tok]))));
      g_upd[c * DM + q * 256 + (i & 255)] = __float2bfloat16(rbf(y) * rs);
    }
  }
}
struct RecParams { const bf16* mem0; unsigned char* win; };
struct WMaps { CUtensorMap q, k, v; };
#ifndef KB
#define KB 8
#endif
#ifndef WPF
#define WPF 7
#endif
#ifndef WPA
#define WPA 3
#endif
#ifndef XPF
#define XPF 4
#endif
#define RF_FAT 208
#define RF_CTL 88
#define WSPL 1
#define NPROBE 3
#define DLY_TB 700
#define DLY_SIDE 16000
#define KU 32
#define KD 4
#ifndef DLYS
#define DLYS 560, 400, 270, 400, 720, 300, 1248, 850, 500
#endif
#define NTUNE 9
#define TUNE_NAMES {"OM3", "XL", "S", "XD", "WO", "V", "OK", "OKS", "ORR"}
__constant__ int g_tune[NTUNE] = {DLYS};
#define DLY_M3 g_tune[0]
#define DLY_XL g_tune[1]
#define DLY_S g_tune[2]
#define DLY_XD g_tune[3]
#define DLY_WO g_tune[4]
#define DLY_V g_tune[5]
#define DLY_K g_tune[6]
#define DLY_KS g_tune[7]
#define DLY_RR g_tune[8]
#ifdef PRO
__device__ unsigned g_pro[NCTA][16];
#define PT(i, c) do { if (c) g_pro[cta][i] = gt32(); } while (0)
#else
#define PT(i, c)
#endif
#ifdef PER
__device__ unsigned g_pk[NCTA][64], g_pclk[NCTA][64], g_per[NCTA][64], g_end[8] = {0, 0, 0, 0, 0, 0, 0, 100000};
#endif
#define STR2(x) #x
#define STR(x) STR2(x)

static __device__ __forceinline__ void cp16p(uint32_t dst, const void* src, uint32_t v) {
  asm volatile("{\n.reg .pred q;\nsetp.ne.u32 q, %2, 0;\n@q cp.async.cg.shared.global [%0], [%1], 16;\n}" :: "r"(dst), "l"(src), "r"(v) : "memory"); }
static __device__ __forceinline__ void red_bf2(void* p, uint32_t v) {
  asm volatile("red.relaxed.gpu.global.add.noftz.bf16x2 [%0], %1;" :: "l"(p), "r"(v) : "memory"); }
static __device__ __forceinline__ void red_bf2p4(void* p, uint32_t v, uint32_t e) {
  asm volatile("{\n.reg .pred q;\nsetp.lt.u32 q, %2, 4;\n@q red.relaxed.gpu.global.add.noftz.bf16x2 [%0], %1;\n}" :: "l"(p), "r"(v), "r"(e) : "memory"); }
static __device__ __forceinline__ void eta2(void* p, uint32_t t, uint32_t first, uint32_t l16) {
  asm volatile("{\n.reg .pred q;\nsetp.lt.u32 q, %3, 32;\n@q red.relaxed.gpu.global.max.u32 [%0+4], %1;\n@q red.relaxed.gpu.global.add.u32 [%0], %2;\n}" :: "l"(p), "r"(t), "r"(first), "r"(l16) : "memory"); }
static __device__ __forceinline__ void sts16(uint32_t a, uint32_t x) { asm volatile("{\n.reg .b16 h;\ncvt.u16.u32 h, %1;\nst.shared.u16 [%0], h;\n}" :: "r"(a), "r"(x) : "memory"); }
static __device__ __forceinline__ uint32_t cnt_word(uint32_t L) { return (L & 17u) | ((L & 6u) << 1) | ((L & 8u) >> 2); }
static __device__ __forceinline__ uint32_t cnt_line(uint32_t l) { return (l & 17u) | ((l & 12u) >> 1) | ((l & 2u) << 2); }
static __device__ __forceinline__ int m3_check(uint32_t sb, const unsigned char* p3, const unsigned char* pd, int dq, uint32_t l16, uint32_t mc, int hf, int s) {
  const uint32_t md = l16 + (sb + SM_MEM + hf * 8192), dd = l16 + (sb + SM_RD + hf * 256), dc = (l16 >> 2) + (sb + SM_RD + hf * 256);
  int n = 0;
  uint32_t c0 = 0, c1 = 0, d0 = 0, d1 = 0;
#pragma unroll 1
  do {
    if (n) {
      const int src = cnt_word(l16 >> 4);
      const uint32_t m0 = __ballot_sync(~0u, (__shfl_sync(~0u, c0, src) >> 16) != 0x4200u) >> (l16 >> 7), m1 = __ballot_sync(~0u, (__shfl_sync(~0u, c1, src) >> 16) != 0x4200u) >> (l16 >> 7);
      const uint32_t m2 = __ballot_sync(~0u, (d0 >> 16) != 0x4200u), m3 = __ballot_sync(~0u, (d1 >> 16) != 0x4200u);
#pragma unroll
      for (int i = 0; i < 8; i++) { cp16p(md + i * 512, p3 + i * 1024, m0 & (1u << (4 * i))); cp16p(md + 4096 + i * 512, p3 + dq + i * 1024, m1 & (1u << (4 * i))); }
      cp16p(dd, pd, l16 < 256u ? (((l16 & 128u) ? m3 : m2) >> ((l16 >> 2) & 28u)) & 15u : 0u);
      sts32(sb + SM_Z + 40, s);
    }
    n++;
    asm volatile("cp.async.commit_group;\ncp.async.wait_group 0;" ::: "memory");
    __syncwarp();
    c0 = lds32(mc); c1 = lds32(mc + 4096); d0 = lds32(dc); d1 = lds32(dc + 128);
  } while (__any_sync(~0u, (x3(c0, c1, 0x42000000u) | x3(d0, d1, 0x42000000u)) >= (n < SPIN_LIMIT ? 0x10000u : ~0u)));
  sts16(mc + 2, d0); sts16(mc + 4098, d1);
  mbar_arrive(sb + SM_BAR + MB_MEM + hf * 8);
  return n - 1;
}

__global__ void __cluster_dims__(2, 1, 1) __launch_bounds__(384, 1)
rec_kernel(const __grid_constant__ CUtensorMap tmx, const __grid_constant__ CUtensorMap tmw, const __grid_constant__ WMaps W, RecParams P, const __grid_constant__ SideParams SP) {
  extern __shared__ __align__(1024) unsigned char smem[];
  asm volatile("griddepcontrol.launch_dependents;");
  const uint32_t sb = smem_u32(smem);
  const int tid = threadIdx.x, lane = tid & 31, t128 = tid & 127;
  const int wg = __shfl_sync(~0u, tid >> 7, 0), wq = __shfl_sync(~0u, (tid >> 5) & 3, 0);
  const int r = blockIdx.x & 1, pp = blockIdx.x >> 1;
  const int mi = lane >> 3, r8 = lane & 7;
  const uint32_t xb16 = __shfl_sync(~0u, (((sb + SM_X + (tid >> 7) * 32768 + r * 16384) & 0x3FFFF) >> 4) | (1u << 16), 0);
  const uint32_t va16 = __shfl_sync(~0u, (((sb + SM_WVS + (tid >> 7) * 16384) & 0x3FFFF) >> 4) | (64u << 16), 0);
#if defined(PER) || defined(PRO)
  const uint32_t tstart = gt32();
#endif

  if (tid == 0) {
    mbar_init(sb + SM_BAR + MB_F, 1); mbar_init(sb + SM_BAR + MB_F + 8, 1); mbar_init(sb + SM_BAR + MB_XE0, 2); mbar_init(sb + SM_BAR + MB_XE1, 2); mbar_init(sb + SM_BAR + MB_INIT, 2);
    mbar_init(sb + SM_BAR + MB_MEM, 32); mbar_init(sb + SM_BAR + MB_MEM + 8, 32); for (int i = 0; i < 8; i++) mbar_init(sb + SM_BAR + MB_W + i * 8, 1);
    mbar_init(sb + SM_BAR + MB_XF, 8); mbar_init(sb + SM_BAR + MB_X0, 1); mbar_init(sb + SM_BAR + MB_WO, 1); mbar_init(sb + SM_BAR + MB_VR, 5);
    sts32(sb + SM_Z + 40, ~0u);
    asm volatile("fence.mbarrier_init.release.cluster;" ::: "memory");
  }
  if (tid >= 64 && tid < 96) {
    const uint32_t l16 = lane * 16, qa = ((l16 & 0x30u) << 3) | ((l16 & 0x10u) << 2) | ((l16 >> 3) & 0x30u) | ((l16 >> 4) & 4u);
    sts128(sb + SM_QA + l16, qa + (sb + SM_QKP), (qa ^ 64u) + (sb + SM_QKP), 0u, 0u);
  }
  if (tid == 32) {
    asm volatile("prefetch.tensormap [%0];" :: "l"(&W.q) : "memory"); asm volatile("prefetch.tensormap [%0];" :: "l"(&W.k) : "memory");
    asm volatile("prefetch.tensormap [%0];" :: "l"(&W.v) : "memory"); asm volatile("prefetch.tensormap [%0];" :: "l"(&tmx) : "memory");
  }
  if (tid >= 256 && tid < 320) {
    unsigned char* pl = P.win + r * W_2 + (W_UP | (1u << 19) | ((pp >> 5) << 14)) + (pp & 31) * 128 + wq * 4096;
    stg_r1(pl + lane * 4, 0u);
    uint32_t best = 1u << 30;
    if (lane == 0) {
#pragma unroll 1
      for (int rep = 0; rep < NPROBE; rep++) {
        uint32_t dt;
        asm volatile("{\n.reg .u32 a, b, v;\nmov.u32 a, %%clock;\natom.relaxed.gpu.global.exch.b32 v, [%1], 0;\n"
                     "st.volatile.shared.u32 [%2], v;\nmov.u32 b, %%clock;\nsub.u32 %0, b, a;\n}" : "=r"(dt) : "l"(pl), "r"(sb + SM_SIDE + wq * 4) : "memory");
        best = min(best, dt);
      }
    }
    if (lane == 0) sts32(sb + SM_SIDE + wq * 4, best);
    bar_sync(B_P, 64);
    if (wq == 0) {
      const uint2 bt = lds64(sb + SM_SIDE);
      if (lane < 8 && (r == 0 || pp == 0)) stg_r1(&g_side[(r ? 66 : pp) * 32 + lane], 2u | (bt.x < bt.y ? 1u : 0u));
      spin(DLY_TB);
      uint32_t a, b, c; int n = 0;
#pragma unroll 1
      do {
        a = ldg_r1(&g_side[lane * 32]); b = ldg_r1(&g_side[(32 + lane) * 32]); c = ldg_r1(&g_side[(64 + min(lane, 2)) * 32]);
      } while (!__all_sync(~0u, a & b & c & 2u) && ++n < SPIN_LIMIT);
      a = __ballot_sync(~0u, a & 1u); b = __ballot_sync(~0u, b & 1u); c = __ballot_sync(~0u, c & 1u);
      const uint32_t pol2 = (a ^ (c >> 2)) & 1u;
      c &= 3u;
      const unsigned long long ab = ((unsigned long long)b << 32) | a;
      const int sd = pp < 64 ? (int)(ab >> pp) & 1 : (int)(c >> (pp - 64)) & 1;
      const int n1 = __popcll(ab) + __popc(c), n0 = 66 - n1;
      const int below1 = pp < 64 ? __popcll(ab & ((1ull << pp) - 1)) : __popcll(ab) + (pp == 65 ? (int)(c & 1u) : 0);
      const int rk = sd ? below1 : pp - below1;
      const int k0 = (n0 & 1) ? n0 - 1 : n0 >= n1 ? n0 - 2 : n0, k1 = 64 - k0;
      const int role = rk >= (sd ? k1 : k0) ? 64 + ((n0 & 1) ? sd : rk - (sd ? k1 : k0)) : sd ? k0 + rk : rk;
      __syncwarp();
      if (lane == 0) sts128(sb + SM_SIDE, 2 * k0, 0u, pol2, role * 2 + r);
#ifdef PER
      if (lane == 0) { atomicMax(&g_end[6], gt32()); atomicMin(&g_end[7], max(bt.x, bt.y) - min(bt.x, bt.y)); }
#endif
    }
  }
  __syncthreads();
  const int cta = __shfl_sync(~0u, (int)lds32(sb + SM_SIDE + 12), 0), h = cta >> 2, j = cta & 3, p = j >> 1;
  const int sw = (cta >= __shfl_sync(~0u, (int)lds32(sb + SM_SIDE), 0) ? 1 : 0) ^ r;
  if (cta >= NCTA) {
    spin(DLY_SIDE);
#ifndef NOSIDE
    side_work(SP, smem, cta - NCTA);
#endif
#ifdef PER
    if (threadIdx.x == 0) atomicMax(&g_end[1], gt32());
#endif
    return;
  }
#ifdef PER
  if (threadIdx.x == 0) g_per[cta][63] = tstart;
#endif
#ifdef PRO
  if (tid == 0) { g_pro[cta][0] = tstart; g_pro[cta][1] = gt32(); }
#endif
  asm volatile("barrier.cluster.arrive.relaxed.aligned;" ::: "memory");
#define WLOAD(i0, i1) _Pragma("unroll 1") for (int u = i0; u < i1; u++) {        \
    const int g2 = u >> 2, i = u & 3, k = g2 * 512 + ((i * 128 + r * 256) & 511); \
    const uint32_t mb = sb + SM_BAR + MB_W + u * 8; \
    mbar_expect_tx(mb, i < 2 ? 32768 : 16384); \
    tma_load_2d(sb + g2 * 65536 + i * 8192, &W.q, h * DH + j * 32, k, mb); \
    tma_load_2d(sb + g2 * 65536 + 32768 + i * 8192, &W.k, h * DH + j * 32, k, mb); \
    if (i < 2) tma_load_2d(sb + (i ? SM_WVS : SM_VST) + g2 * 16384, &W.v, h * DH + p * 64, k, mb); }
  if (tid == 288) {
    mbar_expect_tx(sb + SM_BAR + MB_X0, 32768);
#pragma unroll 1
    for (int i = 0; i < 2; i++)
      asm volatile("cp.async.bulk.tensor.3d.shared::cluster.global.mbarrier::complete_tx::bytes [%0], [%1, {%3, %3, %4}], [%2];"
                   :: "r"(sb + SM_MEM + i * 16384), "l"(&tmx), "r"(sb + SM_BAR + MB_X0), "r"(0), "r"(i * 4) : "memory");
    WLOAD(0, 4 + WSPL);
  }
  __syncwarp();
  asm volatile("barrier.cluster.wait.acquire.aligned;" ::: "memory");
#define SIDES() const uint4 sm2 = lds128(sb + SM_SIDE); const int nlo = sm2.x; const uint32_t me = cta >= nlo

#define XLOAD(t, sg) tma_load_mc(sb + SM_X + ((t) * 8 + r * 4) * 4096, &tmx, (sg) * SEG, (t) * 8 + r * 4, sb + SM_BAR + MB_F + (t) * 8)
#define F0LOAD() do { mbar_wait(sb + SM_BAR + MB_XE0, s & 1); \
    if (l16 == 0) XLOAD(0, s + 2); \
    __syncwarp(); } while (0)
  if (wg < 2) {
    asm volatile("setmaxnreg.inc.sync.aligned.u32 " STR(RF_FAT) ";");
    uint32_t w[32][4], wv[8][4];
    uint32_t lm = ((mi >> 1) * 8 + r8) * 128 + (((wq * 2 + (mi & 1)) ^ r8) << 4), l16 = lane * 16;
    lm = __shfl_sync(~0u, lm, lane); l16 = __shfl_sync(~0u, l16, lane);
    {
      const uint32_t lq0 = sb + wg * 65536 + (wq >> 1) * 32768 + ((mi >> 1) * 8 + r8) * 64 + ((((wq & 1) * 2 + (mi & 1)) ^ (r8 >> 1)) << 4);
      const uint32_t f = wq < 2 ? 0x3D003D00u : 0x3F803F80u;
#pragma unroll
      for (int i = 0; i < 4; i++) {
        mbar_wait(sb + SM_BAR + MB_W + (wg * 4 + i) * 8, 0);
        if (i == 3) PT(2 + wg, t128 == 0);
#pragma unroll
        for (int kk = 8 * i; kk < 8 * i + 8; kk++) ldmatrix_x4_trans(w[kk], lq0 + kk * 1024);
        if (i == 0) {
#pragma unroll
          for (int kk = 0; kk < 8; kk++) ldmatrix_x4_trans(wv[kk], sb + SM_VST + wg * 16384 + kk * 2048 + lm);
        }
#pragma unroll
        for (int kk = 32 * i; kk < 32 * i + 32; kk++) w[kk >> 2][kk & 3] = mulb2v(w[kk >> 2][kk & 3], f);
      }
    }
    if (wg == 0) bar_sync(B_V, 160);
    else bar_arrive(B_P, 160);
    const int w8 = wg * 4 + wq;
    const int cw = sw ^ wg;
    const uint32_t xh16 = xb16 ^ 1024u;
    const uint32_t rsb = mapa(sb, r ^ 1);
#define MT (l16 + (sb + SM_MEM + wg * 8192))
#define WA (lm + (sb + SM_WVS + wg * 16384))
#define WOF(f) (lm + (sb + SM_WOS + wg * 32768 + ((f) & 1) * 16384 + ((f) >> 1) * 2048))
#define TH(base) (l16 + (sb + (base) + w8 * 512))
#define TQ(base) (l16 + (sb + (base) + wq * 512))
#define DUMP(base) _Pragma("unroll") for (int n = 0; n < 4; n++) sts128f(TQ((base) + n * 2048), d[4 * n], d[4 * n + 1], d[4 * n + 2], d[4 * n + 3])
#define INIT(base) _Pragma("unroll") for (int n = 0; n < 4; n++) { const float4 t = lds128f(TQ((base) + n * 2048)); d[4 * n] = t.x; d[4 * n + 1] = t.y; d[4 * n + 2] = t.z; d[4 * n + 3] = t.w; }
#define XQK(first, b0, b1) do { wg_fence(); XR<0, 16, 0, 32, first>::run(d, w, b0); XR<0, 16, 16, 32, 0>::run(d, w, b1); wg_commit(); wg_wait0(); } while (0)
#define XVS(first, b0) do { wg_fence(); XS<8, 8, 16, first>::run(d, va16, b0); XR<0, 8, 0, 8, 0>::run(d, wv, b0); wg_commit(); wg_wait0(); } while (0)
#define XREL(mb) do { if (wq == 0 && l16 == 0) { mbar_arrive_cluster_rlx(rsb + SM_BAR + (mb)); mbar_arrive(sb + SM_BAR + (mb)); } } while (0)
#define XFOUT() do { \
          _Pragma("unroll") for (int hf = 0; hf < 2; hf++) \
            stsm4t(l16 + (sb + SM_XF + (wq * 2 + hf) * 512), pack_bf16(d[8 * hf], d[8 * hf + 1]), pack_bf16(d[8 * hf + 2], d[8 * hf + 3]), \
                   pack_bf16(d[8 * hf + 4], d[8 * hf + 5]), pack_bf16(d[8 * hf + 6], d[8 * hf + 7])); \
          __syncwarp(); \
          if (l16 < 32) mbar_arrive(sb + SM_BAR + MB_XF); } while (0)
#define VDUMP(base) _Pragma("unroll") for (int n = 0; n < 2; n++) sts128(TQ((base) + n * 2048), pack_bf16(d[8 * n], d[8 * n + 1]), pack_bf16(d[8 * n + 2], d[8 * n + 3]), pack_bf16(d[8 * n + 4], d[8 * n + 5]), pack_bf16(d[8 * n + 6], d[8 * n + 7]))

    if (wg == 0) {
      float d[16];
      const uint32_t x0 = (((sb + SM_MEM + r * 16384) & 0x3FFFF) >> 4) | (1u << 16), x1 = (((sb + SM_MEM + (r ^ 1) * 16384) & 0x3FFFF) >> 4) | (1u << 16);
      mbar_wait(sb + SM_BAR + MB_X0, 0);
      XQK(1, x0, x1);
      DUMP(SM_CQ);
      XVS(1, x0);
      bar_arrive(B_X2, 256);
      VDUMP(SM_CV);
      bar_sync(B_CQ, 256);
    } else {
      float d[16];
      bar_sync(B_CQ, 256);
      INIT(SM_CQ);
      mbar_wait(sb + SM_BAR + MB_F + 8, 0);
      PT(4, t128 == 0);
      XQK(0, xb16, xh16);
      XFOUT();
      PT(5, t128 == 0);
    }
    if (wg == 0) mbar_wait(sb + SM_BAR + MB_F, 0);
    for (int s = -1;; s++) {
      if (s >= 0) {
        OPAQUE_R(lm); OPAQUE_R(l16);
        {
          uint32_t sa[4][4];
#pragma unroll
          for (int i = 0; i < 2; i++) ldmatrix_x4_trans(sa[i], WA + i * 2048);
          float a[2][4], v[2][4]; uint4 c[4]; uint2 qa;
          FENCE();
          mbar_wait(sb + SM_BAR + MB_MEM + wg * 8, s & 1);
#define QP(i) ((i) >= 12 ? (i) - 8 : (i) % 3 == 1 ? (i) / 3 : 8 + (i) - ((i) + 2) / 3)
#pragma unroll
          for (int i = 0; i < 3; i++) c[i] = ldsm4t(MT + QP(i) * 512);
#pragma unroll
          for (int i = 0; i < 16; i++) {
            if (i + 3 < 16) c[(i + 3) & 3] = ldsm4t(MT + QP(i + 3) * 512);
            if (i == 13) qa = lds64(l16 + (sb + SM_QA));
            if (i == 0) {
              mma4z(a[0], w[2 * QP(i)][0], w[2 * QP(i)][1], w[2 * QP(i)][2], w[2 * QP(i)][3], c[i & 3].x, c[i & 3].y);
              mma4z(a[1], w[2 * QP(i) + 1][0], w[2 * QP(i) + 1][1], w[2 * QP(i) + 1][2], w[2 * QP(i) + 1][3], c[i & 3].z, c[i & 3].w);
            } else {
              mma_16816(a[0], w[2 * QP(i)], c[i & 3].x, c[i & 3].y);
              mma_16816(a[1], w[2 * QP(i) + 1], c[i & 3].z, c[i & 3].w);
            }
            if (QP(i) == 0) {
              mma4z(v[0], wv[0][0], wv[0][1], wv[0][2], wv[0][3], c[i & 3].x, c[i & 3].y);
              mma4z(v[1], wv[1][0], wv[1][1], wv[1][2], wv[1][3], c[i & 3].z, c[i & 3].w);
            } else if (QP(i) < 4) {
              mma_16816(v[0], wv[2 * (QP(i) & 3)], c[i & 3].x, c[i & 3].y);
              mma_16816(v[1], wv[2 * (QP(i) & 3) + 1], c[i & 3].z, c[i & 3].w);
            }
            if (i == 12) {
              mma_16816(v[0], sa[0], c[0].x, c[0].y); mma_16816(v[1], sa[1], c[0].z, c[0].w);
            }
            if (i == 13) { ldmatrix_x4_trans(sa[0], WA + 2 * 2048); ldmatrix_x4_trans(sa[1], WA + 3 * 2048); ldmatrix_x4_trans(sa[2], WA + 4 * 2048); }
            FENCE();
          }
#pragma unroll
          for (int i = 0; i < 4; i++) sts32(((i & 1) ? qa.y : qa.x) + (w8 * 512 + (i >> 1) * 8), f2u(a[0][i] + a[1][i]));
          bar_arrive(B_QK, 288);
          bar_arrive(B_QK1, 288);
          FENCE();
          uint32_t sc2[4];
          ldmatrix_x4_trans(sa[3], WA + 5 * 2048); ldmatrix_x4_trans(sc2, WA + 6 * 2048);
          mma_16816(v[0], sa[0], c[1].x, c[1].y); mma_16816(v[1], sa[1], c[1].z, c[1].w);
          FENCE();
          ldmatrix_x4_trans(sa[0], WA + 7 * 2048);
          FENCE();
          mma_16816(v[0], sa[2], c[2].x, c[2].y); mma_16816(v[1], sa[3], c[2].z, c[2].w);
          mma_16816(v[0], sc2, c[3].x, c[3].y); mma_16816(v[1], sa[0], c[3].z, c[3].w);
          FENCE();
          sts128f(TH(SM_VP), v[0][0] + v[1][0], v[0][1] + v[1][1], v[0][2] + v[1][2], v[0][3] + v[1][3]);
          bar_arrive(B_V, 320);
        }
        if (s == NSEG - 1) break;
        OPAQUE_R(lm); OPAQUE_R(l16);
        uint32_t wo[WPF][4];
        {
          float d[16];
#define XOUT(g) _Pragma("unroll") for (int n = 0; n < 2; n++) sts128f(TQ(SM_CQ + ((g) * 2 + n) * 2048), d[8 - 8 * (g) + 4 * n], d[9 - 8 * (g) + 4 * n], d[10 - 8 * (g) + 4 * n], d[11 - 8 * (g) + 4 * n])
#define XIN(g) do { \
            const float4 t0 = lds128f(TQ(SM_CQ + (2 - 2 * (g)) * 2048)), t1 = lds128f(TQ(SM_CQ + (3 - 2 * (g)) * 2048)); \
            stsm4t(l16 + (sb + SM_XF + (wq * 2 + (g)) * 512), pack_bf16(d[8 * (g)] + t0.x, d[8 * (g) + 1] + t0.y), pack_bf16(d[8 * (g) + 2] + t0.z, d[8 * (g) + 3] + t0.w), \
                   pack_bf16(d[8 * (g) + 4] + t1.x, d[8 * (g) + 5] + t1.y), pack_bf16(d[8 * (g) + 6] + t1.z, d[8 * (g) + 7] + t1.w)); } while (0)
          if (wg == 0) {
            INIT(SM_CW);
            bar_sync(B_PUB, 320);
            wg_fence();
            XR<KB, 16, 0, 32, 0>::run(d, w, xb16); XR<0, 16, 16, 32, 0>::run(d, w, xh16);
            wg_commit(); wg_wait0();
            TSF(13, 1);
            OPAQUE_R(l16);
            XOUT(0);
            bar_arrive(B_G1, 256);
            XREL(MB_XE0);
            bar_sync(B_CQ, 256);
            XIN(0);
#pragma unroll
            for (int f = 0; f < WPA; f++) ldmatrix_x4_trans(wo[f], WOF(f));
          } else {
            const uint32_t ok = mbar_test(sb + SM_BAR + MB_F + 8, (s + 1) & 1);
            bar_sync(B_PUB, 320);
            if (!ok) mbar_wait(sb + SM_BAR + MB_F + 8, (s + 1) & 1);
            wg_fence();
            XR<0, 16, 0, 32, 1>::run(d, w, xb16); XR<0, 16, 16, 32, 0>::run(d, w, xh16);
            wg_commit();
#pragma unroll
            for (int f = 0; f < WPA; f++) ldmatrix_x4_trans(wo[f], WOF(f));
            wg_wait0();
            TSF(31, 5);
            OPAQUE_R(l16);
            XOUT(1);
            bar_arrive(B_CQ, 256);
            bar_sync(B_G1, 256);
            XIN(1);
          }
          __syncwarp();
          if (l16 == 0) mbar_arrive(sb + SM_BAR + MB_XF);
          TSF(3, 5);
        }
#pragma unroll
        for (int f = WPA; f < WPF; f++) ldmatrix_x4_trans(wo[f], WOF(f));
        unsigned char* pa = P.win + (w_ar(s) + (j * 32 + cw * 16 + wq * 2) * 256 + (l16 >> 2));
        uint32_t ce = (l16 >> 4) - 4 * (cw * 4 + wq);
        OPAQUE_L(pa); OPAQUE_R(ce);
        FENCE();
        bar_sync(wg ? B_O : B_O2, wg ? 192 : 224);
        uint4 ob[2];
        ob[0] = ldsm4(l16 + (sb + SM_OF)); ob[1] = ldsm4(l16 + (sb + SM_OF + 512));
        float acc[2][4]; uint32_t f0ok;
#pragma unroll
        for (int f = 0; f < 16; f++) {
          const int ks = f >> 1;
          const uint32_t b0 = (ks & 1) ? ob[(ks >> 1) & 1].z : ob[(ks >> 1) & 1].x, b1 = (ks & 1) ? ob[(ks >> 1) & 1].w : ob[(ks >> 1) & 1].y;
          if (f < 2) mma4z(acc[f], wo[f][0], wo[f][1], wo[f][2], wo[f][3], b0, b1);
          else mma_16816(acc[f % 2], wo[f < WPF ? f : 2 + (f - WPF) % (WPF - 2)], b0, b1);
          if (f - 1 >= 2 && f - 1 + (WPF - 2) < 16) {
            const int nf = f - 1 + (WPF - 2);
            ldmatrix_x4_trans(wo[2 + (nf - WPF) % (WPF - 2)], WOF(nf));
          }
          if (f == 4 || f == 8) ob[((f >> 2) - 1) & 1] = ldsm4(l16 + (sb + SM_OF + (1 + (f >> 2)) * 512));
          if (f == 12) f0ok = mbar_test(sb + SM_BAR + MB_F, (s + 1) & 1);
          if (f < 15) FENCE();
        }
        if (!wg) bar_arrive(B_CV, 256);
        red_bf2(pa, pack_bf16(acc[0][0], ce == 0 ? 1.f : acc[0][1])); red_bf2(pa + 256, pack_bf16(acc[0][2], ce == 1 ? 1.f : acc[0][3]));
        red_bf2(pa + 2048, pack_bf16(acc[1][0], ce == 2 ? 1.f : acc[1][1])); red_bf2(pa + 2304, pack_bf16(acc[1][2], ce == 3 ? 1.f : acc[1][3]));
        red_bf2p4(pa + (W_DS + (wq & 1) * 256), pack_bf16(ce == 0 ? acc[0][1] : ce == 1 ? acc[0][3] : ce == 2 ? acc[1][1] : acc[1][3], 1.f), ce);
        TSF(4, 1); TSF(2, 6);
        if (wg) bar_sync(B_CV, 256);
        else if (!f0ok) mbar_wait(sb + SM_BAR + MB_F, (s + 1) & 1);
      }
      OPAQUE_R(lm); OPAQUE_R(l16);
      {
        float d[16];
        const uint32_t cv = TQ(SM_CV + ((s ^ wg) & 1) * 4096);
        TSF(9, 1);
        wg_fence();
        XR<0, 1, 0, 8, 1>::run(d, wv, xb16); XS<8, 8, 9, 0>::run(d, va16, xb16); XR<1, 2, 0, 8, 0>::run(d, wv, xb16); XS<9, 8, 10, 0>::run(d, va16, xb16);
        XR<2, 3, 0, 8, 0>::run(d, wv, xb16); XS<10, 8, 11, 0>::run(d, va16, xb16); XR<3, 4, 0, 8, 0>::run(d, wv, xb16); XS<11, 8, 12, 0>::run(d, va16, xb16);
        XR<4, 5, 0, 8, 0>::run(d, wv, xb16); XS<12, 8, 13, 0>::run(d, va16, xb16); XR<5, 6, 0, 8, 0>::run(d, wv, xb16); XS<13, 8, 14, 0>::run(d, va16, xb16);
        XR<6, 7, 0, 8, 0>::run(d, wv, xb16); XS<14, 8, 15, 0>::run(d, va16, xb16); XR<7, 8, 0, 8, 0>::run(d, wv, xb16); XS<15, 8, 16, 0>::run(d, va16, xb16);
        wg_commit(); wg_wait0();
        uint32_t q[8];
#pragma unroll
        for (int i = 0; i < 8; i++) q[i] = pack_bf16(d[2 * i], d[2 * i + 1]);
        if (wg == 0) {
          sts128(cv, q[0], q[1], q[2], q[3]); sts128(cv + 2048, q[4], q[5], q[6], q[7]);
          wg_fence(); XR<0, KB, 0, 32, 1>::run(d, w, xb16); wg_commit(); wg_wait0();
          OPAQUE_R(l16);
          DUMP(SM_CW);
          TSF(5, 1);
        } else {
          const uint4 o = lds128(cv + (r ^ 1) * 2048), k = lds128(cv + r * 2048);
          XREL(MB_XE1);
          st_async4(l16 + (rsb + SM_VR + wq * 512), u2f(addb2(r ? q[0] : q[4], o.x)), u2f(addb2(r ? q[1] : q[5], o.y)), u2f(addb2(r ? q[2] : q[6], o.z)), u2f(addb2(r ? q[3] : q[7], o.w)),
                    rsb + SM_BAR + MB_VR);
          sts128(TQ(SM_VL), addb2(r ? q[4] : q[0], k.x), addb2(r ? q[5] : q[1], k.y), addb2(r ? q[6] : q[2], k.z), addb2(r ? q[7] : q[3], k.w));
          __syncwarp();
          if (l16 == 0) mbar_arrive(sb + SM_BAR + MB_VR);
          TSF(28, 5);
        }
      }
    }
  } else {
    asm volatile("setmaxnreg.dec.sync.aligned.u32 " STR(RF_CTL) ";");
    const int g = lane >> 2, tq = lane & 3;
    if (wq == 0) {
      if (lane < 12) asm volatile("prefetch.global.L2 [%0];" :: "l"(SP.x + (size_t)(cta * 12 + lane) * 64));
      __syncwarp();
      {
        SIDES();
        const uint32_t o[6] = {w_blk(w_h1(cta), me), w_blk(w_h1(cta) ^ H1_V, me), w_blk(w_mvx(cta, 0), me ^ sm2.z), w_blk(w_mvx(cta, 1), me ^ sm2.z),
                               w_blk(w_mxa(cta, 0), me ^ sm2.z), w_blk(w_mxa(cta, 1), me ^ sm2.z)};
#pragma unroll
        for (int i = 0; i < 24; i++) stg_r4(P.win + (o[i >> 2] + (i & 3) * 512 + lane * 16), 0u, 0u, 0u, 0u);
#pragma unroll
        for (int i = 0; i < 6; i++) stg_r1(P.win + (w_ar(i >> 1) + cta * 256 + (i & 1) * W_DS + lane * 4), 0u);
        __threadfence();
        __syncwarp();
      }
      {
        const uint32_t wv = movm(*reinterpret_cast<const uint32_t*>(P.mem0 + g * DM + cta * 8 + tq * 2));
        const bool sp = lane == cnt_word(cta & 31);
        stg_r1(P.win + (w_ar(-1) + cta * 256 + lane * 4), sp ? (wv & 0xffffu) | 0x42000000u : wv);
        if (sp) stg_r1(P.win + (w_ar(-1) + ((cta & ~9) + ((cta >> 1) & 1)) * 256 + W_DS + lane * 4), (wv >> 16) | 0x42000000u);
      }
      bar_sync(B_V, 160);
      if (lane == 0) {
        fence_async_smem(); mbar_arrive_cluster_rlx(mapa(sb + SM_BAR + MB_INIT, 0)); mbar_arrive_cluster_rlx(mapa(sb + SM_BAR + MB_INIT, 1));
        mbar_wait(sb + SM_BAR + MB_INIT, 0);
        mbar_expect_tx(sb + SM_BAR + MB_F, 32768);
        mbar_expect_tx(sb + SM_BAR + MB_F + 8, 32768);
        XLOAD(1, 0); XLOAD(0, 1);
        WLOAD(4 + WSPL, 8);
      }
      __syncwarp();
#ifdef PER
      if (lane == 0) atomicMax(&g_end[5], gt32());
#endif
    }
    bar_sync(B_X2, 256);
    SIDES();
    uint32_t l16 = __shfl_sync(~0u, lane * 16, lane);
    const uint32_t me2 = me ^ sm2.z;
    const float sc = 32.f * 0.08838834764831845f * 1.4426950408889634f;
    uint32_t ls = l16 + sb;
#define PVM(o, zs, p0, p2, MID) do { \
        FENCE(); \
        mma4z(zs, 0x3F803F80u, 0x3F803F80u, 0x3F803F80u, 0x3F803F80u, p0.x, p0.y); \
        FENCE(); \
        _Pragma("unroll") for (int t = 0; t < 4; t++) mma4z(o[t], va[2 * t].x, va[2 * t].y, va[2 * t].z, va[2 * t].w, p0.x, p0.y); \
        FENCE(); \
        mma4(zs, 0x3F803F80u, 0x3F803F80u, 0x3F803F80u, 0x3F803F80u, p0.z, p0.w); \
        _Pragma("unroll") for (int t = 0; t < 2; t++) mma4(o[t], va[2 * t + 1].x, va[2 * t + 1].y, va[2 * t + 1].z, va[2 * t + 1].w, p0.z, p0.w); \
        FENCE(); MID; \
        mma_1688(zs, 0x3F803F80u, 0x3F803F80u, p2); \
        _Pragma("unroll") for (int t = 2; t < 4; t++) mma4(o[t], va[2 * t + 1].x, va[2 * t + 1].y, va[2 * t + 1].z, va[2 * t + 1].w, p0.z, p0.w); \
        mma_1688(o[0], vm[0].x, vm[0].y, p2); mma_1688(o[1], vm[0].z, vm[0].w, p2); mma_1688(o[2], vm[1].x, vm[1].y, p2); mma_1688(o[3], vm[1].z, vm[1].w, p2); } while (0)
#define PVE(o, z, dst) do { \
        const float i0 = rcpf(z[0]), i1 = rcpf(z[1]); \
        _Pragma("unroll") for (int u = 0; u < 2; u++) \
          stsm4t(ls + (dst) + u * 1024, pack_bf16(o[2 * u][0] * i0, o[2 * u][1] * i1), pack_bf16(o[2 * u][2] * i0, o[2 * u][3] * i1), \
                 pack_bf16(o[2 * u + 1][0] * i0, o[2 * u + 1][1] * i1), pack_bf16(o[2 * u + 1][2] * i0, o[2 * u + 1][3] * i1)); } while (0)
    const uint32_t lq = (l16 ^ ((l16 >> 1) & 64u)) + sb, l12 = (l16 >> 2) * 3;
#define M3PTR(sl) \
            const uint32_t tf = me ^ 1 ^ r, m3i = w_ar(sl) + (wq & 1) * 16384 + (l16 & 0x70u) + ((l16 & 0x180u) << 1); \
            const unsigned char* p0f = P.win + (m3i + r * 8192 + tf * 4096); const unsigned char* p0n = P.win + (m3i + r * 8192 + (tf ^ 1) * 4096); \
            const unsigned char* p1f = P.win + (m3i + (r ^ 1) * 8192 + (tf ^ 1) * 4096); const unsigned char* p1n = P.win + (m3i + (r ^ 1) * 8192 + tf * 4096); \
            const unsigned char* pd = P.win + (w_ar(sl) + (wq & 1) * 16384 + (((l16 >> 7) ^ r) & 1u) * 8192 + ((l16 & 64u) * 4 + (l16 & 48u) * 2 + (l16 & 16u)) * 16 + W_DS + (l16 & 0x70u)); \
            uint32_t mf = ls + SM_MEM + (wq & 1) * 8192 + tf * 2048, mn = ls + SM_MEM + (wq & 1) * 8192 + (tf ^ 1) * 2048, nr = l16 < 256u ? 1u + (((l16 >> 6) ^ (l16 >> 7) ^ tf) & 1u) : 0u; \
            OPAQUE_L(p0f); OPAQUE_L(p0n); OPAQUE_L(p1f); OPAQUE_L(p1n); OPAQUE_L(pd); OPAQUE_R(mf); OPAQUE_R(mn); OPAQUE_R(nr); FENCE()
#define M3REQ() \
            _Pragma("unroll") for (int i = 0; i < 4; i++) { cp16(mn + 4096 + i * 512, p1f + i * 1024); cp16(mf + i * 512, p0f + i * 1024); } \
            cp16p(ls + SM_RD + (wq & 1) * 256, pd, nr & 1u); \
            _Pragma("unroll") for (int i = 0; i < 4; i++) { cp16(mf + 4096 + i * 512, p1n + i * 1024); cp16(mn + i * 512, p0n + i * 1024); } \
            cp16p(ls + SM_RD + (wq & 1) * 256, pd, nr & 2u)
    if (wq >= 2) { M3PTR(-1); M3REQ(); }
    if (wq == 0) {
      bar_sync(B_P, 160);
      if (l16 == 0) {
        fence_async_smem();
        mbar_expect_tx(sb + SM_BAR + MB_WO, 65536);
        for (int i = 0; i < 8; i++) tma_load_2d(sb + SM_WOS + i * 8192, &tmw, j * 256 + ((i >> 1) ^ (2 * sw)) * 64, h * DH + (i & 1) * 64, sb + SM_BAR + MB_WO);
      }
      __syncwarp();
    }
#define ETA(k, first) ETAT(gt32() + (k), first)
#define ETAT(tm, first) do { unsigned char* pt = P.win + (w_ar(s) + (W_DS + 256) + (cta >> 5) * 8192 + ((cta >> 4) & 1) * 2048 + (l16 & 16u) * 256); \
          asm volatile("{\n.reg .pred q;\nsetp.lt.u32 q, %2, 32;\n@q red.relaxed.gpu.global.max.u32 [%0+4], %1;\n}" :: "l"(pt), "r"(tm), "r"(l16) : "memory"); \
          if (first) asm volatile("{\n.reg .pred q;\nsetp.lt.u32 q, %1, 32;\n@q red.relaxed.gpu.global.add.u32 [%0], 1;\n}" :: "l"(pt), "r"(l16) : "memory"); } while (0)
    if (wq == 1) {
      const uint32_t xin = w_blk(w_mxa(cta, 0), me2) + l16;
      const uint32_t lsq = sb + ((l16 & 0x70u) | ((l16 & 0x80u) << 1) | ((l16 & 0x100u) >> 1));
      mbar_wait(sb + SM_BAR + MB_MEM, 0); mbar_wait(sb + SM_BAR + MB_MEM + 8, 0);
      for (int s = 0; s < NSEG; s++) {
        const uint32_t t2 = ((s >> 1) & 1) ^ 1;
        mbar_wait(sb + SM_BAR + MB_XF, s & 1);
        {
        uint4 kx[4], qx[4];
#pragma unroll
        for (int i = 0; i < 4; i++) { kx[i] = ldsm4(ls + (SM_XF + (4 + i) * 512)); qx[i] = ldsm4(lsq + (SM_XF + i * 512)); }
        const uint32_t db = w_blk(w_mxa(h * 4, s), me2) + l16 - 512;
        {
          float S[2][4][4];
#pragma unroll
          for (int mt = 0; mt < 2; mt++) {
            const uint4 q0 = qx[mt];
            mma4z(S[mt][0], q0.x, q0.y, q0.z, q0.w, kx[0].x, kx[0].y); mma4z(S[mt][1], q0.x, q0.y, q0.z, q0.w, kx[0].z, kx[0].w);
            mma4z(S[mt][2], q0.x, q0.y, q0.z, q0.w, kx[1].x, kx[1].y); mma4z(S[mt][3], q0.x, q0.y, q0.z, q0.w, kx[1].z, kx[1].w);
          }
#pragma unroll
          for (int mt = 0; mt < 2; mt++) {
            const uint4 q1 = qx[2 + mt];
            mma4(S[mt][0], q1.x, q1.y, q1.z, q1.w, kx[2].x, kx[2].y); mma4(S[mt][1], q1.x, q1.y, q1.z, q1.w, kx[2].z, kx[2].w);
            mma4(S[mt][2], q1.x, q1.y, q1.z, q1.w, kx[3].x, kx[3].y); mma4(S[mt][3], q1.x, q1.y, q1.z, q1.w, kx[3].z, kx[3].w);
          }
          FENCE();
          if (s > 0) bar_arrive(B_O2, 224);
          FENCE();
#pragma unroll
          for (int u = 0; u < 4; u++) {
            const int mt = u >> 1, c = 2 * (u & 1);
            const uint32_t m0 = tagw(pack_f16(S[mt][0][c], S[mt][0][c + 1]), t2), m1 = pack_f16(S[mt][1][c], S[mt][1][c + 1]),
                           m2 = pack_f16(S[mt][2][c], S[mt][2][c + 1]), m3 = pack_f16(S[mt][3][c], S[mt][3][c + 1]);
            const int e = u ^ j;
            if (e) stg_r4(P.win + (db + mt * 16384 + (u & 1) * 2048 + e * 512), m0, m1, m2, m3);
            else sts128(ls + SM_XS, m0, m1, m2, m3);
          }
        }
        TS(15);
        float sx[10];
        const unsigned char* pa = P.win + (xin + ((s & 1) << 20));
        uint4 xv[3];
        if (s > 0) spin(DLY_XD);
#pragma unroll
        for (int i = 0; i < 3; i++) xv[i] = ldg_r4(pa + i * 512);
        FENCE();
        int n = 0; float mx;
#pragma unroll 1
        while (__any_sync(~0u, (x3(xv[0].x, xv[1].x, t2) | (xv[2].x ^ t2)) & 1u) && ++n < SPIN_LIMIT) {
#pragma unroll
          for (int i = 0; i < 3; i++) xv[i] = ldg_r4(pa + i * 512);
        }
        {
          const uint4 v3 = lds128(ls + SM_XS);
          sum_h4(sx[2], sx[3], xv[0].x, xv[1].x, xv[2].x, v3.x); sum_h4(sx[4], sx[5], xv[0].y, xv[1].y, xv[2].y, v3.y);
          sum_h4(sx[6], sx[7], xv[0].z, xv[1].z, xv[2].z, v3.z); sum_h4(sx[8], sx[9], xv[0].w, xv[1].w, xv[2].w, v3.w);
          const int row = 8 * j + g - 2 * tq;
#pragma unroll
          for (int i = 0; i < 8; i++) if ((i >> 1) * 8 + (i & 1) > row) sx[2 + i] = -INFINITY;
        }
        mx = fmaxf(fmaxf(fmaxf(sx[2], sx[3]), fmaxf(sx[4], sx[5])), fmaxf(fmaxf(sx[6], sx[7]), fmaxf(sx[8], sx[9])));
        sts32(ls - l12 + SM_XS + 512, f2u(mx));
        {
          if (l16 == 0) mbar_expect_tx(sb + SM_BAR + MB_VR, 2048);
          unsigned char* d = P.win + (w_blk(w_mvx(cta, s), me2) + l16);
          OPAQUE_L(d); FENCE();
          mbar_wait(sb + SM_BAR + MB_VR, s & 1);
#pragma unroll
          for (int t = 0; t < 4; t++) {
            const uint4 a0 = lds128(ls + (SM_VL + t * 512)), a1 = lds128(ls + (SM_VR + t * 512));
            stg_r4(d + t * 512, tagw(addb2(a0.x, a1.x), t2), addb2(a0.y, a1.y), addb2(a0.z, a1.z), addb2(a0.w, a1.w));
          }
          TS(23);
        }
        unsigned char* pm = P.win + (db + 2048 + j * 128 - l12);
        const unsigned char* py = pa + 1536 - l12;
        OPAQUE_L(pm); OPAQUE_L(py);
        if (s > 0) bar_sync(B_PXF, 96);
        FENCE();
        bar_sync(B_QK1, 288);
        uint32_t kb[2][2];
#pragma unroll
        for (int t = 0; t < 2; t++) {
          const float4 u = lds128f(lq + (SM_QKP + (2 + t) * 512)), v4 = lds128f(lq + (SM_QKP + 2048 + (2 + t) * 512));
          kb[t][0] = pack_bf16(u.x + v4.x, u.y + v4.y); kb[t][1] = pack_bf16(u.z + v4.z, u.w + v4.w);
        }
        float S[2][4];
#pragma unroll
        for (int mt = 0; mt < 2; mt++) mma4z(S[mt], qx[mt].x, qx[mt].y, qx[mt].z, qx[mt].w, kb[0][0], kb[0][1]);
#pragma unroll
        for (int mt = 0; mt < 2; mt++) mma4(S[mt], qx[2 + mt].x, qx[2 + mt].y, qx[2 + mt].z, qx[2 + mt].w, kb[1][0], kb[1][1]);
        PT(14, s == 0 && l16 == 0);
        if (s == 0) mbar_wait(sb + SM_BAR + MB_WO, 0);
        PT(15, s == 0 && l16 == 0);
        if (s < NSEG - 1) bar_arrive(B_PUB, 320);
        FENCE();
#pragma unroll
        for (int u = 0; u < 4; u++) stg_r1(pm + (u >> 1) * 16384 + (u & 1) * 2048, tagw(pack_f16(S[u >> 1][2 * (u & 1)], S[u >> 1][2 * (u & 1) + 1]), t2));
        TS(30);
        FENCE();
        spin(DLY_XL);
        uint32_t xy[4];
#pragma unroll
        for (int i = 0; i < 4; i++) xy[i] = ldg_r1(py + i * 128);
        FENCE();

        n = 0;
#pragma unroll 1
        while (__any_sync(~0u, (x3(xy[0], xy[1], t2) | x3(xy[2], xy[3], t2)) & 1u) && ++n < SPIN_LIMIT) {
#pragma unroll
          for (int i = 0; i < 4; i++) xy[i] = ldg_r1(py + i * 128);
        }
        sum_h4(sx[0], sx[1], xy[0], xy[1], xy[2], xy[3]);
        mx = fmaxf(mx, fmaxf(sx[0], sx[1]));
        mx = fmaxf(fmaxf(mx, __shfl_xor_sync(~0u, mx, 1)), fmaxf(__shfl_xor_sync(~0u, mx, 2), __shfl_xor_sync(~0u, mx, 3)));
#pragma unroll
        for (int i = 0; i < 10; i++) sx[i] = ex2(fmaf(sx[i], sc, -sc * mx));
        sts128(ls + SM_PX, pack_bf16(sx[2], sx[3]), pack_bf16(sx[4], sx[5]), pack_bf16(sx[6], sx[7]), pack_bf16(sx[8], sx[9]));
        sts32(ls - l12 + SM_PX + 512, pack_bf16(sx[0], sx[1]));
        bar_arrive(B_PX, 96);
        TS(1);
        }
      }
    } else {
      const uint32_t ho = (wq & 1) * 512 + l16, hv = wq == 0 ? 0u : H1_V;
      uint32_t ow = w_blk(w_h1(cta) ^ hv, me) + ho, or0 = w_blk(w_h1(cta ^ 1) ^ hv, me) + ho, or1 = w_blk(w_h1((cta ^ 2) & ~1) ^ hv, me) + ho;
#define PTRS() OPAQUE_R(ow); OPAQUE_R(or0); OPAQUE_R(or1); \
      unsigned char* pw0 = P.win + ow; const unsigned char* pr0 = P.win + or0; const unsigned char* pr1 = P.win + or1; \
      OPAQUE_L(pw0); OPAQUE_L(pr0); OPAQUE_L(pr1); FENCE()
      if (wq == 0) {
        const uint32_t xcnt = me ? NCTA - nlo : nlo, xrank = (me ? cta - nlo : cta) + lane * xcnt;
        int kd = DLY_K;
        mbar_wait(sb + SM_BAR + MB_XE1, 0);
        if (l16 == 0) { mbar_expect_tx(sb + SM_BAR + MB_F + 8, 32768); XLOAD(1, 1); }
        __syncwarp();
        for (int s = 0; s < NSEG - 1; s++) {
          const uint32_t tg = (s & 1) ^ 1;
          mbar_wait(sb + SM_BAR + MB_XF, s & 1);
          uint4 xf[4];
#pragma unroll
          for (int i = 0; i < 4; i++) xf[i] = ldsm4(ls + (SM_XF + (4 + i) * 512));
          PTRS();
          unsigned char* pw1 = pw0 + 512 - l12; OPAQUE_L(pw1);
          bar_sync(B_QK, 288);
          float4 u[4], v4[4];
#pragma unroll
          for (int t = 0; t < 4; t++) { u[t] = lds128f(lq + (SM_QKP + t * 512)); v4[t] = lds128f(lq + (SM_QKP + 2048 + t * 512)); }
          FENCE();
          uint32_t f[4][2], m[5];
#pragma unroll
          for (int t = 0; t < 2; t++) { f[t][0] = pack_bf16(u[t].x + v4[t].x, u[t].y + v4[t].y); f[t][1] = pack_bf16(u[t].z + v4[t].z, u[t].w + v4[t].w); }
          float S[5][4], T[5][4];
          mma4z(S[1], f[0][0], f[1][0], f[0][1], f[1][1], xf[0].x, xf[0].y); mma4z(T[1], f[0][0], f[1][0], f[0][1], f[1][1], xf[2].x, xf[2].y);
          mma4z(S[2], f[0][0], f[1][0], f[0][1], f[1][1], xf[0].z, xf[0].w); mma4z(T[2], f[0][0], f[1][0], f[0][1], f[1][1], xf[2].z, xf[2].w);
          FENCE();
#pragma unroll
          for (int t = 2; t < 4; t++) { f[t][0] = packv(u[t].x, v4[t].x, u[t].y, v4[t].y); f[t][1] = packv(u[t].z, v4[t].z, u[t].w, v4[t].w); }
          mma4z(S[3], f[0][0], f[1][0], f[0][1], f[1][1], xf[1].x, xf[1].y); mma4z(T[3], f[0][0], f[1][0], f[0][1], f[1][1], xf[3].x, xf[3].y);
          mma4z(S[4], f[0][0], f[1][0], f[0][1], f[1][1], xf[1].z, xf[1].w); mma4z(T[4], f[0][0], f[1][0], f[0][1], f[1][1], xf[3].z, xf[3].w);
          FENCE();
          mma4z(S[0], f[0][0], f[1][0], f[0][1], f[1][1], f[2][0], f[2][1]); mma4z(T[0], f[0][0], f[1][0], f[0][1], f[1][1], f[3][0], f[3][1]);
          bar_arrive(B_PUB, 320);
          FENCE();
#pragma unroll
          for (int i = 1; i < 5; i++) m[i] = pack_f16(S[i][0] + T[i][2], S[i][1] + T[i][3]);
          stg_r4(pw0, tagw(m[1], tg), m[2], m[3], m[4]);
          m[0] = pack_f16(S[0][0] + T[0][2], S[0][1] + T[0][3]);
          stg_r1(pw1, tagw(m[0], tg));
          TS(6); PT(11, s == 0 && l16 == 0);
          FENCE();
          const uint32_t ts = clk32();
          uint32_t te = gt32() + kd;
          const unsigned char* py0 = pr0 + 512 - l12; const unsigned char* py1 = pr1 + 512 - l12;
          OPAQUE_L(py0); OPAQUE_L(py1);
          unsigned char* pt = P.win + (w_ar(s) + (W_DS + 256) + (cta >> 5) * 8192 + ((cta >> 4) & 1) * 2048 + (l16 & 16u) * 256);
          OPAQUE_L(pt);
          if (l16 == 0) mbar_expect_tx(sb + SM_BAR + MB_F, s < NSEG - 2 ? 32768 : 0);
          FENCE();
          while (clk32() - ts < (uint32_t)DLY_S) {}
          {
            float sx[10]; uint32_t x, x1, x2, x3_; int n = 0; bool bad;
#pragma unroll 1
            do {
              uint4 v[3]; uint32_t y[3], t[5];
              v[0] = ldg_r4(pr0); v[1] = ldg_r4(pr1); v[2] = ldg_r4(pr1 + 2048);
              y[0] = ldg_r1(py0); y[1] = ldg_r1(py1); y[2] = ldg_r1(py1 + 2048);
              if (n) te = gt32() + DLY_KS;
              eta2(pt, te, n == 0, l16);
              n++;
              FENCE();
#define Q3(o, a, b, c) hadd2(hadd2(o, a), hadd2(b, c))
              t[1] = Q3(m[1], v[0].x, v[1].x, v[2].x); t[2] = Q3(m[2], v[0].y, v[1].y, v[2].y); t[3] = Q3(m[3], v[0].z, v[1].z, v[2].z); t[4] = Q3(m[4], v[0].w, v[1].w, v[2].w);
              t[0] = Q3(m[0], y[0], y[1], y[2]);
              bad = __any_sync(~0u, or3(x3(v[0].x, v[1].x, tg), x3(v[2].x, y[0], tg), x3(y[1], y[2], tg)) & (n < SPIN_LIMIT ? 1u : 0u));
              x = hmax2(hmax2(hmax2(t[1], t[2]), hmax2(t[3], t[4])), t[0]);
              const float2 xm = __half22float2(*reinterpret_cast<__half2*>(&x));
              x = f2u(fmaxf(xm.x, xm.y) * -sc);
              x1 = shfl_x(x, 1); x2 = shfl_x(x, 2); x3_ = shfl_x(x, 3);
              FENCE();
#pragma unroll
              for (int i = 1; i < 6; i++) h2f(sx[2 * (i % 5)], sx[2 * (i % 5) + 1], t[i % 5]);
              FENCE();
            } while (bad);
            const float mx = fminf(fminf(u2f(x), u2f(x1)), fminf(u2f(x2), u2f(x3_)));
#pragma unroll
            for (int i = 2; i < 12; i++) sx[i % 10] = ex2v(sx[i % 10], sc, mx);
#pragma unroll
            for (int i = 1; i < 6; i++) m[i % 5] = pack_bf16(sx[2 * (i % 5)], sx[2 * (i % 5) + 1]);
            sts128(ls + SM_PF, m[1], m[2], m[3], m[4]);
            sts32(ls - l12 + SM_PF + 512, m[0]);
            TV(19, n - 1);
          }
          TS(12);
          bar_sync(B_P, 96);
          PT(12, s == 0 && l16 == 0);
          OPAQUE_R(l16);
          {
            const unsigned char* pe = P.win + w_blk(w_ar(s) + (W_DS + 256) + (l16 & 0x60u) * 256 + (l16 & 16u) * 128, me);
            const uint32_t tp = gt32() + DLY_M3;
            if (s < NSEG - 2) F0LOAD();
            ETAT(tp, 0);
            uint32_t tg0; int n = 0;
#pragma unroll 1
            for (;;) {
              const uint2 e = ldg_r2(pe);
              tg0 = __reduce_max_sync(~0u, e.y);
              if (tg0 - tp >= 4096u) tg0 = tp;
              if ((!__any_sync(~0u, e.x != 16u) && (int)(tg0 - gt32()) < DLY_RR) || ++n >= SPIN_LIMIT) break;
            }
            sts32(sb + SM_Z + 32, tg0);
            TV(16, tg0); TV(7, kd - DLY_K);
            bar_arrive(B_GO, 96);
          }
          if (s < NSEG - 2) {
            mbar_wait(sb + SM_BAR + MB_XE1, (s + 1) & 1);
            if (l16 == 0) mbar_expect_tx(sb + SM_BAR + MB_F + 8, 32768);
            mbar_wait(sb + SM_BAR + MB_MEM, (s + 1) & 1); mbar_wait(sb + SM_BAR + MB_MEM + 8, (s + 1) & 1);
            if (l16 == 0) XLOAD(1, s + 2);
            __syncwarp();
          }
          if (XPF && s + XPF < NSEG) {
            for (uint32_t i = xrank; i < 512; i += 32 * xcnt)
              asm volatile("prefetch.global.L2 [%0];" :: "l"(SP.x + (size_t)(s + XPF) * (SEG * DM) + i * 64));
            __syncwarp();
          }
          stg_2(P.win + (w_ar(s + 2) + cta * 256 + (l16 >> 8) * W_DS + ((l16 >> 1) & 127u)), 0u, 0u);
          kd = lds32(sb + SM_Z + 40) == (uint32_t)(s + 1) ? min(kd + KU, DLY_K + 256) : max(kd - KD, DLY_K);
          kd = __shfl_sync(~0u, kd, l16 >> 4);
#ifdef PER
          if (l16 == 0) { g_per[cta][s] = gt32(); g_pclk[cta][s] = clk32(); g_pk[cta][s] = kd - DLY_K; }
#endif
        }
        bar_sync(B_QK, 288);
      } else {
        const int mt = wq - 2;
        const uint32_t lt = ls + mt * 1024;
        const uint32_t vi0 = w_blk(w_mvx(h * 4, 0), me2) + mt * 1024;
        const int m3d = r ? -8192 : 8192;
#ifdef PROF
        const uint32_t epoch = gt32(); TST(-1, 30 + mt, l16, epoch);
#endif
        float ox[4][4], zx[4];
#pragma unroll
        for (int i = 0; i < 16; i++) ox[i >> 2][i & 3] = zx[i & 3] = 1.f;
        for (int s = 0;; s++) {
          const uint32_t tg = (s & 1) ^ 1, t2 = ((s >> 1) & 1) ^ 1;
          {
            OPAQUE_R(l16);
            const uint32_t m3i = (mt * 2 + r) * 8192 + (l16 & 0x70u) + ((l16 & 0x180u) << 1);
            const uint32_t m3j = (mt * 2 + (r ^ (l16 >> 7 & 1))) * 8192 + ((l16 & 64u) * 4 + (l16 & 48u) * 2 + (l16 & 16u)) * 16 + W_DS + (l16 & 0x70u);
            uint32_t m3c = sb + SM_MEM + mt * 8192 + cnt_line(l16 >> 4) * 128 + (l16 >> 2);
            const unsigned char* p3 = P.win + (m3i + w_ar(s - 1)); const unsigned char* pd = P.win + (m3j + w_ar(s - 1));
            OPAQUE_L(pd); OPAQUE_R(m3c);
#define XEPI() do {        \
              PVE(ox, zx, SM_OX + mt * 512); \
              __syncwarp(); \
              const uint32_t oa = sb + SM_OX + mt * 512 + ((l16 & 48u) << 3) + ((l16 >> 2) & 0x70u); \
              const uint4 a = lds128(oa), b = lds128(oa + 1024); \
              unsigned char* o = reinterpret_cast<unsigned char*>(g_ox + (size_t)((s - 1) * SEG + 8 * j) * (NH * DH) + h * DH + mt * 32) + ((l16 >> 6) * (NH * DH * 2) + (l16 & 48u)); \
              stg_4(o, a); stg_4(o + 128, b); \
              TST(s - 1, 18, l16 | mt, TCLK()); } while (0)
            if (s > 0) XEPI();
            if (s == NSEG) break;
            if (s > 0) {
              M3PTR(s - 1);
              bar_sync(B_GO, 96);
              const uint32_t tg0 = lds32(sb + SM_Z + 32);
              while (tg0 - gt32() - 1u < 8192u) {}
              M3REQ();
            }
            FENCE();
            const int n = m3_check(sb, p3, pd, m3d, l16, m3c, mt, s);
            FENCE();
            TST(s, mt ? 21 : 0, l16, TCLK());
            TST(s, mt ? 22 : 17, l16, n);
            PT(6 + s, s < 5 && (l16 | mt) == 0);
          }
          uint4 va[8], vm[2], p0, q0; uint32_t p2, q2;
          const unsigned char* a0 = P.win + (vi0 + ((s & 1) << 20) + l16);
#define VALD() _Pragma("unroll") for (int i = 0; i < 4; i++) { va[i] = ldg_r4(a0 + (i >> 1) * 512 + (i & 1) * 2048); va[4 + i] = ldg_r4(a0 + 16384 + (i >> 1) * 512 + (i & 1) * 2048); }
          spin(DLY_WO);
          VALD();
          {
          PTRS();
          bar_sync(B_V, 320);
            const float4 u0 = lds128f(lt + SM_VP), w0 = lds128f(lt + SM_VP + 2048), u1 = lds128f(lt + SM_VP + 512), w1 = lds128f(lt + SM_VP + 2560);
            const uint32_t m0 = tagw(pack_bf16(u0.x + w0.x, u0.y + w0.y), tg), m1 = pack_bf16(u0.z + w0.z, u0.w + w0.w),
                           m2 = pack_bf16(u1.x + w1.x, u1.y + w1.y), m3 = pack_bf16(u1.z + w1.z, u1.w + w1.w);
            stg_r4(pw0, m0, m1, m2, m3);
            if (wq == 2) TS(10);
            FENCE();
            const uint32_t tv = clk32();
            while (clk32() - tv < (uint32_t)DLY_V) {}
            uint4 v[3]; int n = 0; uint32_t bada = 0;
#pragma unroll 1
            do {
              v[0] = ldg_r4(pr0); v[1] = ldg_r4(pr1); v[2] = ldg_r4(pr1 + 2048);
              if (n) {
                TST(s, __any_sync(~0u, bada & 1u) ? 26 : 24, l16, epoch);
                if (__any_sync(~0u, bada & 1u)) { VALD(); }
                if (s < NSEG - 1) ETA(DLY_KS - 192, 0);
              }
              n++;
              FENCE();
              bada = or3(x3(va[0].x, va[1].x, t2), x3(va[2].x, va[3].x, t2), x3(va[4].x, va[5].x, t2)) | x3(va[6].x, va[7].x, t2);
            } while (__any_sync(~0u, or3(bada, x3(v[0].x, v[1].x, tg), v[2].x ^ tg) & 1u) && n < SPIN_LIMIT);
            const uint4 A = make_uint4(addb2(m0, v[0].x), addb2(m1, v[0].y), addb2(m2, v[0].z), addb2(m3, v[0].w));
            const uint4 B = make_uint4(addb2(v[1].x, v[2].x), addb2(v[1].y, v[2].y), addb2(v[1].z, v[2].z), addb2(v[1].w, v[2].w));
            vm[0] = p ? B : A; vm[1] = p ? A : B;
            TST(s, 11, l16 | mt, TCLK()); TST(s, 29, l16 | (mt ^ 1), TCLK());
          }
          FENCE();
          if (s < NSEG - 1) {
          bar_sync(B_P, 96);
          p0 = lds128(ls + SM_PF); p2 = lds32(ls - l12 + SM_PF + 512);
          float o[4][4], z[4];
          PVM(o, z, p0, p2, );
          PVE(o, z, SM_OF + mt * 512);
          bar_arrive(B_O, 192);
          }
          FENCE();
          TST(s, 8, l16 | mt, TCLK());
          bar_sync(B_PX, 96);
          q0 = lds128(ls + SM_PX); q2 = lds32(ls - l12 + SM_PX + 512);
          PVM(ox, zx, q0, q2, if (s < NSEG - 1) bar_arrive(B_O2, 224));
          FENCE();
          if (s < NSEG - 1) bar_arrive(B_PXF, 96);
        }
      }
    }
  }
  asm volatile("barrier.cluster.arrive.relaxed.aligned;\nbarrier.cluster.wait.aligned;" ::: "memory");
#ifdef PER
  if (threadIdx.x == 0) atomicMax(&g_end[0], gt32());
#endif
}
#ifndef PW
#define PW 2
#endif
#ifndef G2_ST
#define G2_ST 6
#endif
#define G2_TB (G2_ST * 32768 + 1024)
#define G2_SMEM (G2_TB + 32768)
static __device__ __forceinline__ void wgmma_n128_ta(float (&d)[64], uint64_t da, uint64_t db) {
  asm volatile(
      "wgmma.mma_async.sync.aligned.m64n128k16.f32.bf16.bf16 "
      "{%0,%1,%2,%3,%4,%5,%6,%7,%8,%9,%10,%11,%12,%13,%14,%15,%16,%17,%18,%19,%20,%21,%22,%23,%24,%25,%26,%27,%28,%29,%30,%31,"
      "%32,%33,%34,%35,%36,%37,%38,%39,%40,%41,%42,%43,%44,%45,%46,%47,%48,%49,%50,%51,%52,%53,%54,%55,%56,%57,%58,%59,%60,%61,%62,%63}, "
      "%64, %65, 1, 1, 1, 1, 0;"
      : "+f"(d[0]), "+f"(d[1]), "+f"(d[2]), "+f"(d[3]), "+f"(d[4]), "+f"(d[5]), "+f"(d[6]), "+f"(d[7]), "+f"(d[8]), "+f"(d[9]), "+f"(d[10]), "+f"(d[11]),
        "+f"(d[12]), "+f"(d[13]), "+f"(d[14]), "+f"(d[15]), "+f"(d[16]), "+f"(d[17]), "+f"(d[18]), "+f"(d[19]), "+f"(d[20]), "+f"(d[21]), "+f"(d[22]), "+f"(d[23]),
        "+f"(d[24]), "+f"(d[25]), "+f"(d[26]), "+f"(d[27]), "+f"(d[28]), "+f"(d[29]), "+f"(d[30]), "+f"(d[31]), "+f"(d[32]), "+f"(d[33]), "+f"(d[34]), "+f"(d[35]),
        "+f"(d[36]), "+f"(d[37]), "+f"(d[38]), "+f"(d[39]), "+f"(d[40]), "+f"(d[41]), "+f"(d[42]), "+f"(d[43]), "+f"(d[44]), "+f"(d[45]), "+f"(d[46]), "+f"(d[47]),
        "+f"(d[48]), "+f"(d[49]), "+f"(d[50]), "+f"(d[51]), "+f"(d[52]), "+f"(d[53]), "+f"(d[54]), "+f"(d[55]), "+f"(d[56]), "+f"(d[57]), "+f"(d[58]), "+f"(d[59]),
        "+f"(d[60]), "+f"(d[61]), "+f"(d[62]), "+f"(d[63])
      : "l"(da), "l"(db));
}
__global__ void __cluster_dims__(2, 1, 1) __launch_bounds__(384, 1)
gemm2_kernel(const __grid_constant__ CUtensorMap tmo, const __grid_constant__ CUtensorMap tmw, const bf16* __restrict__ x, bf16* __restrict__ out, unsigned char* win) {
  extern __shared__ __align__(1024) unsigned char smem[];
  const uint32_t sb = smem_u32(smem), bars = sb + G2_ST * 32768;
  const int tid = threadIdx.x, lane = tid & 31, warp = tid >> 5;
  const int r = blockIdx.x & 1, n0 = (blockIdx.x & 7) * 128, m0 = (blockIdx.x >> 3) * 128;
  if (tid == 0) {
    for (int i = 0; i < G2_ST; i++) { mbar_init(bars + i * 8, 1); mbar_init(bars + 64 + i * 8, 4); }
    asm volatile("fence.mbarrier_init.release.cluster;" ::: "memory");
  }
  if (tid == 32) { asm volatile("prefetch.tensormap [%0];" :: "l"(&tmw) : "memory"); asm volatile("prefetch.tensormap [%0];" :: "l"(&tmo) : "memory"); }
  __syncthreads();
  asm volatile("barrier.cluster.arrive.relaxed.aligned;" ::: "memory");
#define LW(kt, st) do { tma_load_2d(sb + (st) * 32768, &tmw, n0, (kt) * 64, bars + (st) * 8); tma_load_2d(sb + (st) * 32768 + 8192, &tmw, n0 + 64, (kt) * 64, bars + (st) * 8); } while (0)
#define LO(kt, st) asm volatile("cp.async.bulk.tensor.2d.shared::cluster.global.mbarrier::complete_tx::bytes.multicast::cluster [%0], [%1, {%3, %4}], [%2], %5;" \
                     :: "r"(sb + (st) * 32768 + 16384 + r * 8192), "l"(&tmo), "r"(bars + (st) * 8), "r"((kt) * 64), "r"(m0 + r * 64), "h"((uint16_t)3) : "memory")
  if (tid == 256) for (int kt = 0; kt < G2_ST; kt++) { mbar_expect_tx(bars + kt * 8, 32768); if (kt < PW) LW(kt, kt); }
  __syncwarp();
  asm volatile("barrier.cluster.wait.acquire.aligned;" ::: "memory");
  if (warp == 8) {
    if (lane == 0) {
      asm volatile("griddepcontrol.wait;" ::: "memory");
      for (int kt = 0; kt < G2_ST; kt++) { LO(kt, kt); if (kt >= PW) LW(kt, kt); }
      for (int kt = G2_ST; kt < 64; kt++) {
        const int st = kt % G2_ST;
        mbar_wait(bars + 64 + st * 8, ((kt / G2_ST) - 1) & 1);
        mbar_expect_tx(bars + st * 8, 32768);
        LO(kt, st); LW(kt, st);
      }
    }
  } else if (warp > 8) {
    const int t = tid - 288, ch = t & 15;
    asm volatile("griddepcontrol.wait;" ::: "memory");
#ifdef PER
    if (t == 0) atomicMax(&g_end[3], gt32());
#endif
    int idx[8];
#pragma unroll
    for (int c = 0; c < 8; c++) idx[c] = g_idx[c];
    const int gi = blockIdx.x * 96 + t;
    if (gi < 67) g_side[gi * 32] = 0u;
    if (gi == 0) g_sbar = 0u;
#pragma unroll 4
    for (int row = t >> 4; row < 128; row += 6) {
      const int tok = m0 + row;
      const uint4 xv = *reinterpret_cast<const uint4*>(x + (size_t)tok * DM + n0 + ch * 8);
      const float g = g_gate[tok], omg = rbf(1.f - g);
      int sel = -1;
#pragma unroll
      for (int c = 0; c < 8; c++) if (idx[c] == tok) sel = c;
      uint4 uv = make_uint4(0u, 0u, 0u, 0u);
      if (sel >= 0) uv = *reinterpret_cast<const uint4*>(g_upd + sel * DM + n0 + ch * 8);
      const uint32_t x4[4] = {xv.x, xv.y, xv.z, xv.w}, u4[4] = {uv.x, uv.y, uv.z, uv.w};
      uint32_t o4[4];
#pragma unroll
      for (int e = 0; e < 4; e++) {
        const float b0 = rbf(u2f(x4[e] << 16) + u2f(u4[e] << 16)), b1 = rbf(u2f(x4[e] & 0xffff0000u) + u2f(u4[e] & 0xffff0000u));
        o4[e] = pack_bf16(omg * b0, omg * b1);
      }
      sts128(sb + G2_TB + row * 256 + ch * 16, o4[0], o4[1], o4[2], o4[3]);
      if (ch == 0) sts32(bars + 512 + row * 4, __float_as_uint(g));
    }
    bar_arrive(2, 352);
  } else {
    const int wg = warp >> 2;
    float d[64];
#pragma unroll
    for (int i = 0; i < 64; i++) d[i] = 0.f;
    const uint32_t e0 = mapa(bars + 64, 0), e1 = mapa(bars + 64, 1);
#ifdef PER
    if (threadIdx.x == 0) { mbar_wait(bars, 0); atomicMax(&g_end[4], gt32()); }
    __syncwarp();
#endif
    for (int kt = 0; kt < 64; kt++) {
      const int st = kt % G2_ST;
      mbar_wait(bars + st * 8, (kt / G2_ST) & 1);
      wg_fence();
#pragma unroll
      for (int kk = 0; kk < 4; kk++)
        wgmma_n128_ta(d, make_desc(sb + st * 32768 + wg * 8192 + kk * 2048, 1024, 1024), make_desc(sb + st * 32768 + 16384 + kk * 32, 16, 1024));
      wg_commit();
      asm volatile("wgmma.wait_group.sync.aligned 1;" ::: "memory");
      if (kt > 0 && (tid & 127) == 0) { const int ps = (kt - 1) % G2_ST; mbar_arrive_cluster_rlx(e0 + ps * 8); mbar_arrive_cluster_rlx(e1 + ps * 8); }
    }
    wg_wait0();
#ifdef PER
    if (threadIdx.x == 0) atomicMax(&g_end[5], gt32());
#endif
    bar_sync(1, 256);
#pragma unroll
    for (int jj = 0; jj < 8; jj++) {
      const uint32_t q0 = pack_bf16(d[8 * jj], d[8 * jj + 1]), q1 = pack_bf16(d[8 * jj + 2], d[8 * jj + 3]);
      const uint32_t q2 = pack_bf16(d[8 * jj + 4], d[8 * jj + 5]), q3 = pack_bf16(d[8 * jj + 6], d[8 * jj + 7]);
      stsm4t(sb + (jj * 16 + (lane >> 4) * 8 + (lane & 7)) * 272 + (warp * 16 + ((lane >> 3) & 1) * 8) * 2, q0, q1, q2, q3);
    }
    bar_sync(2, 352);
#pragma unroll
    for (int it = 0; it < 8; it++) {
      const int row = it * 16 + (tid >> 4), ch = tid & 15, tok = m0 + row;
      const uint4 av = lds128(sb + row * 272 + ch * 16), tv = lds128(sb + G2_TB + row * 256 + ch * 16);
      const float g = u2f(lds32(bars + 512 + row * 4));
      const uint32_t a4[4] = {av.x, av.y, av.z, av.w}, t4[4] = {tv.x, tv.y, tv.z, tv.w};
      uint32_t o4[4];
#pragma unroll
      for (int e = 0; e < 4; e++)
        o4[e] = pack_bf16(rbf(g * u2f(a4[e] << 16)) + u2f(t4[e] << 16), rbf(g * u2f(a4[e] & 0xffff0000u)) + u2f(t4[e] & 0xffff0000u));
      *reinterpret_cast<uint4*>(out + (size_t)tok * DM + n0 + ch * 8) = make_uint4(o4[0], o4[1], o4[2], o4[3]);
    }
  }
  asm volatile("barrier.cluster.arrive.relaxed.aligned;\nbarrier.cluster.wait.aligned;" ::: "memory");
#ifdef PER
  if (threadIdx.x == 0) atomicMax(&g_end[2], gt32());
#endif
}
#ifndef WPROM
#define WPROM CU_TENSOR_MAP_L2_PROMOTION_L2_128B
#endif
#ifndef PDL
#define PDL 1
#endif
typedef CUresult (*PFN_encodeTiled)(CUtensorMap*, CUtensorMapDataType, cuuint32_t, void*, const cuuint64_t*, const cuuint64_t*,
                                    const cuuint32_t*, const cuuint32_t*, CUtensorMapInterleave, CUtensorMapSwizzle,
                                    CUtensorMapL2promotion, CUtensorMapFloatOOBfill);

extern "C" void kernel_launch(void* const* d_in, const int* in_sizes, int n_in, void* d_out, int out_size) {
  const bf16* x = (const bf16*)d_in[0];
  const bf16* mem0 = (const bf16*)d_in[1];
  const bf16* Wq = (const bf16*)d_in[2];
  const bf16* Wk = (const bf16*)d_in[3];
  const bf16* Wv = (const bf16*)d_in[4];
  const bf16* Wo = (const bf16*)d_in[5];
  const bf16* w_r = (const bf16*)d_in[8];
  const bf16* w_gate = (const bf16*)d_in[9];
  const bf16* w_up = (const bf16*)d_in[10];
  const bf16* w_down = (const bf16*)d_in[11];
  const bf16* gate_w = (const bf16*)d_in[12];
  bf16* out = (bf16*)d_out;

  static PFN_encodeTiled encode = nullptr;
  if (!encode) {
    void* fn = nullptr; cudaDriverEntryPointQueryResult st;
    cudaGetDriverEntryPoint("cuTensorMapEncodeTiled", &fn, cudaEnableDefault, &st);
    encode = (PFN_encodeTiled)fn;
    cudaFuncSetAttribute(rec_kernel, cudaFuncAttributeMaxDynamicSharedMemorySize, SM_TOTAL);
    cudaFuncSetAttribute(gemm2_kernel, cudaFuncAttributeMaxDynamicSharedMemorySize, G2_SMEM);
  }
  CUtensorMap tmx;
  {
    cuuint64_t gd[3] = {64, S_TOK, DM / 64};
    cuuint64_t gs[2] = {DM * 2, 128};
    cuuint32_t bx[3] = {64, SEG, 4};
    cuuint32_t es[3] = {1, 1, 1};
    encode(&tmx, CU_TENSOR_MAP_DATA_TYPE_BFLOAT16, 3, (void*)x, gd, gs, bx, es, CU_TENSOR_MAP_INTERLEAVE_NONE,
           CU_TENSOR_MAP_SWIZZLE_128B, CU_TENSOR_MAP_L2_PROMOTION_L2_128B, CU_TENSOR_MAP_FLOAT_OOB_FILL_NONE);
  }
  bf16* ox;
  cudaGetSymbolAddress((void**)&ox, g_ox);
  CUtensorMap tmo, tmw;
  {
    cuuint64_t gd[2] = {NH * DH, S_TOK}; cuuint64_t gs[1] = {NH * DH * 2}; cuuint32_t bx[2] = {64, 64}; cuuint32_t es[2] = {1, 1};
    encode(&tmo, CU_TENSOR_MAP_DATA_TYPE_BFLOAT16, 2, (void*)ox, gd, gs, bx, es, CU_TENSOR_MAP_INTERLEAVE_NONE,
           CU_TENSOR_MAP_SWIZZLE_128B, CU_TENSOR_MAP_L2_PROMOTION_L2_128B, CU_TENSOR_MAP_FLOAT_OOB_FILL_NONE);
    cuuint64_t gd2[2] = {DM, NH * DH}; cuuint64_t gs2[1] = {DM * 2}; cuuint32_t bx2[2] = {64, 64};
    encode(&tmw, CU_TENSOR_MAP_DATA_TYPE_BFLOAT16, 2, (void*)Wo, gd2, gs2, bx2, es, CU_TENSOR_MAP_INTERLEAVE_NONE,
           CU_TENSOR_MAP_SWIZZLE_128B, CU_TENSOR_MAP_L2_PROMOTION_L2_128B, CU_TENSOR_MAP_FLOAT_OOB_FILL_NONE);
  }
  unsigned char* win;
  cudaGetSymbolAddress((void**)&win, g_win);
  win = (unsigned char*)(((uintptr_t)win + (2u << 20) - 1) & ~(uintptr_t)((2u << 20) - 1));
  WMaps W;
  {
    cuuint64_t gd[2] = {NH * DH, DM}; cuuint64_t gs[1] = {NH * DH * 2}; cuuint32_t b32[2] = {32, 128}, b64[2] = {64, 128}; cuuint32_t es[2] = {1, 1};
    encode(&W.q, CU_TENSOR_MAP_DATA_TYPE_BFLOAT16, 2, (void*)Wq, gd, gs, b32, es, CU_TENSOR_MAP_INTERLEAVE_NONE,
           CU_TENSOR_MAP_SWIZZLE_64B, WPROM, CU_TENSOR_MAP_FLOAT_OOB_FILL_NONE);
    encode(&W.k, CU_TENSOR_MAP_DATA_TYPE_BFLOAT16, 2, (void*)Wk, gd, gs, b32, es, CU_TENSOR_MAP_INTERLEAVE_NONE,
           CU_TENSOR_MAP_SWIZZLE_64B, WPROM, CU_TENSOR_MAP_FLOAT_OOB_FILL_NONE);
    encode(&W.v, CU_TENSOR_MAP_DATA_TYPE_BFLOAT16, 2, (void*)Wv, gd, gs, b64, es, CU_TENSOR_MAP_INTERLEAVE_NONE,
           CU_TENSOR_MAP_SWIZZLE_128B, WPROM, CU_TENSOR_MAP_FLOAT_OOB_FILL_NONE);
  }
  RecParams P{mem0, win};
  SideParams SP{x, w_r, w_gate, w_up, w_down, gate_w, Wo};
  rec_kernel<<<NCTA + 4, 384, SM_TOTAL, cudaStreamPerThread>>>(tmx, tmw, W, P, SP);
  {
    cudaLaunchConfig_t cfg = {};
    cfg.gridDim = dim3(NCTA); cfg.blockDim = dim3(384); cfg.dynamicSmemBytes = G2_SMEM; cfg.stream = cudaStreamPerThread;
    cudaLaunchAttribute at[1];
    at[0].id = cudaLaunchAttributeProgrammaticStreamSerialization; at[0].val.programmaticStreamSerializationAllowed = 1;
    cfg.attrs = at; cfg.numAttrs = PDL;
    cudaLaunchKernelEx(&cfg, gemm2_kernel, tmo, tmw, x, out, win);
  }
}
```

```cpp
#include <cuda_runtime.h>
#include <cuda_bf16.h>
#include <cuda_fp16.h>
#include <cuda.h>
#include <stdint.h>

typedef __nv_bfloat16 bf16;

#define S_TOK 2048
#define DM 1024
#define NH 32
#define DH 128
#define SEG 32
#define NSEG 64
#define FF 3584
#define NCTA 128

static __device__ bf16 g_ox[(size_t)S_TOK * NH * DH];
static __device__ float g_gate[S_TOK];
static __device__ float g_r[S_TOK];
static __device__ int g_idx[8];
static __device__ bf16 g_upd[8 * DM];

static __device__ __forceinline__ float rbf(float v) { return __bfloat162float(__float2bfloat16(v)); }
static __device__ __forceinline__ uint32_t smem_u32(const void* p) { return (uint32_t)__cvta_generic_to_shared(p); }
static __device__ __forceinline__ uint32_t pack_bf16(float lo, float hi) {
  __nv_bfloat162 v = __floats2bfloat162_rn(lo, hi);
  return *reinterpret_cast<uint32_t*>(&v);
}

static __device__ __forceinline__ void wg_fence() { asm volatile("wgmma.fence.sync.aligned;" ::: "memory"); }
static __device__ __forceinline__ void wg_commit() { asm volatile("wgmma.commit_group.sync.aligned;" ::: "memory"); }
static __device__ __forceinline__ void wg_wait0() { asm volatile("wgmma.wait_group.sync.aligned 0;" ::: "memory"); }
static __device__ __forceinline__ void fence_async_smem() { asm volatile("fence.proxy.async.shared::cta;" ::: "memory"); }

static __device__ __forceinline__ uint64_t make_desc(uint32_t addr, uint32_t lbo, uint32_t sbo) {
  uint64_t d = 0;
  d |= (uint64_t)((addr & 0x3FFFF) >> 4);
  d |= (uint64_t)((lbo >> 4) & 0x3FFF) << 16;
  d |= (uint64_t)((sbo >> 4) & 0x3FFF) << 32;
  d |= (uint64_t)1 << 62;
  return d;
}

#define DESC_HI(sbo) (((sbo) >> 4) | (1u << 30))
template <int OFF, int SCALE>
static __device__ __forceinline__ void wgmma_n32_ra(float (&d)[16], const uint32_t (&a)[4], uint32_t base16) {
  asm volatile(
      "{\n.reg .b32 t;\n.reg .b64 dd;\nadd.u32 t, %20, %21;\nmov.b64 dd, {t, %22};\n"
      "wgmma.mma_async.sync.aligned.m64n32k16.f32.bf16.bf16 "
      "{%0,%1,%2,%3,%4,%5,%6,%7,%8,%9,%10,%11,%12,%13,%14,%15}, {%16,%17,%18,%19}, dd, %23, 1, 1, 0;\n}"
      : "+f"(d[0]), "+f"(d[1]), "+f"(d[2]), "+f"(d[3]), "+f"(d[4]), "+f"(d[5]), "+f"(d[6]), "+f"(d[7]),
        "+f"(d[8]), "+f"(d[9]), "+f"(d[10]), "+f"(d[11]), "+f"(d[12]), "+f"(d[13]), "+f"(d[14]), "+f"(d[15])
      : "r"(a[0]), "r"(a[1]), "r"(a[2]), "r"(a[3]), "r"(base16), "n"(OFF >> 4), "n"(DESC_HI(1024)), "n"(SCALE));
}
template <int AOFF, int BOFF, int SCALE>
static __device__ __forceinline__ void wgmma_n32_ss_ta(float (&d)[16], uint32_t abase16, uint32_t bbase16) {
  asm volatile(
      "{\n.reg .b32 t, u;\n.reg .b64 da, db;\nadd.u32 t, %16, %18;\nmov.b64 da, {t, %20};\nadd.u32 u, %17, %19;\nmov.b64 db, {u, %20};\n"
      "wgmma.mma_async.sync.aligned.m64n32k16.f32.bf16.bf16 "
      "{%0,%1,%2,%3,%4,%5,%6,%7,%8,%9,%10,%11,%12,%13,%14,%15}, da, db, %21, 1, 1, 1, 0;\n}"
      : "+f"(d[0]), "+f"(d[1]), "+f"(d[2]), "+f"(d[3]), "+f"(d[4]), "+f"(d[5]), "+f"(d[6]), "+f"(d[7]),
        "+f"(d[8]), "+f"(d[9]), "+f"(d[10]), "+f"(d[11]), "+f"(d[12]), "+f"(d[13]), "+f"(d[14]), "+f"(d[15])
      : "r"(abase16), "r"(bbase16), "n"(AOFF >> 4), "n"(BOFF >> 4), "n"(DESC_HI(1024)), "n"(SCALE));
}
static __device__ __forceinline__ void ldmatrix_x4_trans(uint32_t (&r)[4], uint32_t addr) {
  asm volatile("ldmatrix.sync.aligned.m8n8.x4.trans.shared.b16 {%0,%1,%2,%3}, [%4];"
               : "=r"(r[0]), "=r"(r[1]), "=r"(r[2]), "=r"(r[3]) : "r"(addr) : "memory");
}
static __device__ __forceinline__ void mma_16816(float (&d)[4], const uint32_t (&a)[4], uint32_t b0, uint32_t b1) {
  asm volatile("mma.sync.aligned.m16n8k16.row.col.f32.bf16.bf16.f32 {%0,%1,%2,%3}, {%4,%5,%6,%7}, {%8,%9}, {%0,%1,%2,%3};"
               : "+f"(d[0]), "+f"(d[1]), "+f"(d[2]), "+f"(d[3])
               : "r"(a[0]), "r"(a[1]), "r"(a[2]), "r"(a[3]), "r"(b0), "r"(b1));
}

static __device__ __forceinline__ uint32_t mapa(uint32_t addr, uint32_t rank) {
  uint32_t r; asm volatile("mapa.shared::cluster.u32 %0, %1, %2;" : "=r"(r) : "r"(addr), "r"(rank)); return r;
}

static __device__ __forceinline__ void mbar_init(uint32_t bar, int cnt) {
  asm volatile("mbarrier.init.shared::cta.b64 [%0], %1;" :: "r"(bar), "r"(cnt) : "memory");
}
static __device__ __forceinline__ void mbar_expect_tx(uint32_t bar, uint32_t bytes) {
  asm volatile("mbarrier.arrive.expect_tx.shared::cta.b64 _, [%0], %1;" :: "r"(bar), "r"(bytes) : "memory");
}
static __device__ __forceinline__ void tma_load_2d(uint32_t dst, const CUtensorMap* tm, int c0, int c1, uint32_t bar) {
  asm volatile("cp.async.bulk.tensor.2d.shared::cluster.global.mbarrier::complete_tx::bytes [%0], [%1, {%3, %4}], [%2];"
               :: "r"(dst), "l"(tm), "r"(bar), "r"(c0), "r"(c1) : "memory");
}

static __device__ unsigned char g_win[6 << 20];
static __device__ unsigned int g_side[67 * 32];
static __device__ unsigned int g_err;
#define W_UP (1u << 20)
#define W_2 (2u << 20)
static __device__ __forceinline__ uint32_t w_blk(uint32_t off, uint32_t side) { return off | (((__popc((off >> 12) & 0xb3u) ^ side) & 1u) << 12); }
static __device__ __forceinline__ uint32_t w_h1(int c) { return W_UP | (1u << 13) | ((c >> 1) << 14) | ((c & 1) << 11); }
#define W_DS 0x30000u
static __device__ __forceinline__ uint32_t w_ar(int s) { return ((s & 1) << 15) | ((s & 2) << 17); }
static __device__ __forceinline__ uint32_t w_mvx(int c, int s) { return W_2 | ((s & 1) << 20) | ((c >> 1) << 14) | ((c & 1) << 11); }
static __device__ __forceinline__ uint32_t w_mxa(int c, int s) { return W_2 | ((s & 1) << 20) | (1u << 13) | ((c >> 1) << 14) | ((c & 1) << 11); }
#define H1_V (1u << 13)

#define SPIN_LIMIT (1 << 18)

#define SM_X 0
#define SM_WOS 65536
#define SM_WVS 131072
#define SM_MEM 163840
#define SM_QKP 180224
#define SM_VP 184320
#define SM_CW 188416
#define SM_VST 196608
#define SM_VR 196608
#define SM_CQ 200704
#define SM_CV 208896
#define SM_XF 217088
#define SM_VL 221184
#define SM_OF 225280
#define SM_OX 227328
#define SM_PF 229376
#define SM_PX 230016
#define SM_RD 198656
#define SM_QA 230656
#define SM_XS 231168
#define SM_BAR 231808
#define SM_Z 231936
#define SM_TOTAL 232128
#define MB_F 0
#define MB_XE0 16
#define MB_XE1 112
#define MB_INIT 24
#define MB_MEM 32
#define MB_W 256
#define MB_XF 64
#define MB_VR 72
#define MB_X0 80
#define MB_WO 88
#define SM_SIDE (SM_BAR + 96)
#define B_QK 1
#define B_V 2
#define B_P 3
#define B_O 4
#define B_O2 5
#define B_PUB 6
#define B_CQ 7
#define B_QK1 8
#define B_PXF 10
#define B_CV 15
#define B_X2 11
#define B_PX 12
#define B_GO 14
#define B_G1 13

#ifdef PROF
__device__ unsigned int g_ts[NCTA][80][32];
#ifdef GT
#define TCLK() gt32()
#else
#define TCLK() clk32()
#endif
#ifndef TMASK
#define TMASK 0xffffffffu
#endif
#define TST(st, i, c, v) do { if ((TMASK >> (i)) & 1u) asm volatile("{\n.reg .pred q;\nsetp.eq.u32 q, %2, 0;\n@q st.global.u32 [%0], %1;\n}" :: "l"(&g_ts[cta][(st) + 1][i]), "r"((uint32_t)(v)), "r"((uint32_t)(c)) : "memory"); } while (0)
#define TS(i) TST(s, i, l16, TCLK())
#define TV(i, v) TST(s, i, l16, v)
#define TSF(i, w) TST(s, i, l16 | (w8 ^ (w)), TCLK())
#define TSP(i, w) TST(s - 1, i, l16 | (w8 ^ (w)), TCLK())
#define TVF(i, v) TV(i, v)
#else
#define TST(a, b, c, d)
#define TSF(i, w)
#define TSP(i, w)
#define TVF(i, v)
#define TS(i)
#define TV(i, v)
#endif

static __device__ __forceinline__ void bar_sync(int id, int n) { asm volatile("bar.sync %0, %1;" :: "r"(id), "r"(n) : "memory"); }
static __device__ __forceinline__ void bar_arrive(int id, int n) { asm volatile("bar.arrive %0, %1;" :: "r"(id), "r"(n) : "memory"); }
static __device__ __forceinline__ uint4 ldg_r4(const void* p) { uint4 v;
  asm volatile("ld.relaxed.gpu.global.v4.u32 {%0,%1,%2,%3}, [%4];" : "=r"(v.x), "=r"(v.y), "=r"(v.z), "=r"(v.w) : "l"(p) : "memory"); return v; }
static __device__ __forceinline__ uint32_t ldg_r1(const void* p) { uint32_t v;
  asm volatile("ld.relaxed.gpu.global.u32 %0, [%1];" : "=r"(v) : "l"(p) : "memory"); return v; }
static __device__ __forceinline__ void stg_r4(void* p, uint32_t a, uint32_t b, uint32_t c, uint32_t d) {
  asm volatile("st.relaxed.gpu.global.v4.u32 [%0], {%1,%2,%3,%4};" :: "l"(p), "r"(a), "r"(b), "r"(c), "r"(d) : "memory"); }
static __device__ __forceinline__ uint2 ldg_r2(const void* p) { uint2 v;
  asm volatile("ld.relaxed.gpu.global.v2.u32 {%0,%1}, [%2];" : "=r"(v.x), "=r"(v.y) : "l"(p) : "memory"); return v; }
static __device__ __forceinline__ void stg_4(void* p, const uint4& v) {
  asm volatile("st.global.v4.u32 [%0], {%1,%2,%3,%4};" :: "l"(p), "r"(v.x), "r"(v.y), "r"(v.z), "r"(v.w) : "memory"); }
static __device__ __forceinline__ uint32_t f2u(float v) { return __float_as_uint(v); }
static __device__ __forceinline__ void stg_2(void* p, uint32_t a, uint32_t b) {
  asm volatile("st.global.v2.u32 [%0], {%1,%2};" :: "l"(p), "r"(a), "r"(b) : "memory"); }
static __device__ __forceinline__ void stg_r1(void* p, uint32_t a) {
  asm volatile("st.relaxed.gpu.global.u32 [%0], %1;" :: "l"(p), "r"(a) : "memory"); }
static __device__ __forceinline__ void sts128(uint32_t a, uint32_t x, uint32_t y, uint32_t z, uint32_t w) {
  asm volatile("st.shared.v4.u32 [%0], {%1,%2,%3,%4};" :: "r"(a), "r"(x), "r"(y), "r"(z), "r"(w) : "memory"); }
static __device__ __forceinline__ void sts128f(uint32_t a, float x, float y, float z, float w) {
  asm volatile("st.shared.v4.f32 [%0], {%1,%2,%3,%4};" :: "r"(a), "f"(x), "f"(y), "f"(z), "f"(w) : "memory"); }
static __device__ __forceinline__ uint4 lds128(uint32_t a) { uint4 v;
  asm volatile("ld.shared.v4.u32 {%0,%1,%2,%3}, [%4];" : "=r"(v.x), "=r"(v.y), "=r"(v.z), "=r"(v.w) : "r"(a) : "memory"); return v; }
static __device__ __forceinline__ float4 lds128f(uint32_t a) { float4 v;
  asm volatile("ld.shared.v4.f32 {%0,%1,%2,%3}, [%4];" : "=f"(v.x), "=f"(v.y), "=f"(v.z), "=f"(v.w) : "r"(a) : "memory"); return v; }
static __device__ __forceinline__ void sts32(uint32_t a, uint32_t x) { asm volatile("st.shared.u32 [%0], %1;" :: "r"(a), "r"(x) : "memory"); }
static __device__ __forceinline__ uint2 lds64(uint32_t a) { uint2 v;
  asm volatile("ld.shared.v2.u32 {%0,%1}, [%2];" : "=r"(v.x), "=r"(v.y) : "r"(a) : "memory"); return v; }
static __device__ __forceinline__ void st_async4(uint32_t ra, float x, float y, float z, float w, uint32_t rbar) {
  asm volatile("st.async.weak.shared::cluster.mbarrier::complete_tx::bytes.v4.f32 [%0], {%1,%2,%3,%4}, [%5];"
               :: "r"(ra), "f"(x), "f"(y), "f"(z), "f"(w), "r"(rbar) : "memory"); }
static __device__ __forceinline__ void stsm4t(uint32_t a, uint32_t x, uint32_t y, uint32_t z, uint32_t w) {
  asm volatile("stmatrix.sync.aligned.m8n8.x4.trans.shared.b16 [%0], {%1,%2,%3,%4};" :: "r"(a), "r"(x), "r"(y), "r"(z), "r"(w) : "memory"); }
static __device__ __forceinline__ uint32_t hmax2(uint32_t a, uint32_t b) { uint32_t d;
  asm("max.f16x2 %0, %1, %2;" : "=r"(d) : "r"(a), "r"(b)); return d; }
static __device__ __forceinline__ uint32_t hadd2(uint32_t a, uint32_t b) { uint32_t d;
  asm("add.rn.f16x2 %0, %1, %2;" : "=r"(d) : "r"(a), "r"(b)); return d; }
static __device__ __forceinline__ uint32_t packv(float a, float b, float c, float d) { uint32_t r;
  asm volatile("{\n.reg .f32 x, y;\nadd.f32 x, %1, %2;\nadd.f32 y, %3, %4;\ncvt.rn.bf16x2.f32 %0, y, x;\n}" : "=r"(r) : "f"(a), "f"(b), "f"(c), "f"(d)); return r; }
static __device__ __forceinline__ uint32_t packh(float a, float b, float c, float d) { uint32_t r;
  asm volatile("{\n.reg .f32 x, y;\nadd.f32 x, %1, %2;\nadd.f32 y, %3, %4;\ncvt.rn.satfinite.f16x2.f32 %0, y, x;\n}" : "=r"(r) : "f"(a), "f"(b), "f"(c), "f"(d)); return r; }
static __device__ __forceinline__ float ex2v(float a, float b, float c) { float y;
  asm volatile("{\n.reg .f32 x;\nfma.rn.f32 x, %1, %2, %3;\nex2.approx.ftz.f32 %0, x;\n}" : "=f"(y) : "f"(a), "f"(b), "f"(c)); return y; }
static __device__ __forceinline__ uint32_t shfl_x(uint32_t a, int m) { uint32_t d;
  asm volatile("shfl.sync.bfly.b32 %0, %1, %2, 0x1f, 0xffffffff;" : "=r"(d) : "r"(a), "r"(m)); return d; }
static __device__ __forceinline__ void h2f(float& lo, float& hi, uint32_t a) {
  asm volatile("{\n.reg .b16 l, h;\nmov.b32 {l, h}, %2;\ncvt.f32.f16 %0, l;\ncvt.f32.f16 %1, h;\n}" : "=f"(lo), "=f"(hi) : "r"(a)); }
static __device__ __forceinline__ uint4 ldsm4(uint32_t a) { uint4 v;
  asm volatile("ldmatrix.sync.aligned.m8n8.x4.shared.b16 {%0,%1,%2,%3}, [%4];" : "=r"(v.x), "=r"(v.y), "=r"(v.z), "=r"(v.w) : "r"(a) : "memory"); return v; }
static __device__ __forceinline__ uint4 ldsm4t(uint32_t a) { uint4 v;
  asm volatile("ldmatrix.sync.aligned.m8n8.x4.trans.shared.b16 {%0,%1,%2,%3}, [%4];" : "=r"(v.x), "=r"(v.y), "=r"(v.z), "=r"(v.w) : "r"(a) : "memory"); return v; }
static __device__ __forceinline__ uint32_t movm(uint32_t a) { uint32_t d;
  asm volatile("movmatrix.sync.aligned.m8n8.trans.b16 %0, %1;" : "=r"(d) : "r"(a)); return d; }
static __device__ __forceinline__ float u2f(uint32_t v) { return __uint_as_float(v); }
static __device__ __forceinline__ uint32_t tagw(uint32_t w, uint32_t t) { uint32_t d;
  asm("lop3.b32 %0, %1, %2, 1, 0xd8;" : "=r"(d) : "r"(w), "r"(t)); return d; }
static __device__ __forceinline__ uint32_t pack_f16(float lo, float hi) { uint32_t d;
  asm("cvt.rn.satfinite.f16x2.f32 %0, %1, %2;" : "=r"(d) : "f"(hi), "f"(lo)); return d; }
static __device__ __forceinline__ void sum_h4(float& lo, float& hi, uint32_t a, uint32_t b, uint32_t c, uint32_t d) {
  const float2 x = __half22float2(*reinterpret_cast<__half2*>(&a)), y = __half22float2(*reinterpret_cast<__half2*>(&b));
  const float2 z = __half22float2(*reinterpret_cast<__half2*>(&c)), w = __half22float2(*reinterpret_cast<__half2*>(&d));
  lo = (x.x + y.x) + (z.x + w.x); hi = (x.y + y.y) + (z.y + w.y);
}
static __device__ __forceinline__ uint32_t lds32(uint32_t a) { uint32_t v; asm volatile("ld.shared.u32 %0, [%1];" : "=r"(v) : "r"(a) : "memory"); return v; }
static __device__ __forceinline__ uint32_t addb2(uint32_t a, uint32_t b) { uint32_t d;
  asm("add.rn.bf16x2 %0, %1, %2;" : "=r"(d) : "r"(a), "r"(b)); return d; }
static __device__ __forceinline__ uint32_t mulb2(uint32_t a, uint32_t b) { uint32_t d;
  asm("mul.rn.bf16x2 %0, %1, %2;" : "=r"(d) : "r"(a), "r"(b)); return d; }
static __device__ __forceinline__ uint32_t mulb2v(uint32_t a, uint32_t b) { uint32_t d;
  asm volatile("mul.rn.bf16x2 %0, %1, %2;" : "=r"(d) : "r"(a), "r"(b)); return d; }
static __device__ __forceinline__ uint32_t x3(uint32_t a, uint32_t b, uint32_t t) { uint32_t d;
  asm("lop3.b32 %0, %1, %2, %3, 0x7e;" : "=r"(d) : "r"(a), "r"(b), "r"(t)); return d; }
static __device__ __forceinline__ uint32_t or3(uint32_t a, uint32_t b, uint32_t c) { uint32_t d;
  asm("lop3.b32 %0, %1, %2, %3, 0xfe;" : "=r"(d) : "r"(a), "r"(b), "r"(c)); return d; }
static __device__ __forceinline__ float ex2(float x) { float y; asm("ex2.approx.ftz.f32 %0, %1;" : "=f"(y) : "f"(x)); return y; }
static __device__ __forceinline__ float rcpf(float x) { float y; asm("rcp.approx.ftz.f32 %0, %1;" : "=f"(y) : "f"(x)); return y; }
static __device__ __forceinline__ void mbar_wait(uint32_t bar, int parity) {
  asm volatile("{\n.reg .pred p, q;\n.reg .u32 n;\nmbarrier.try_wait.parity.shared::cta.b64 p, [%0], %1;\n@p bra W_DONE;\nmov.u32 n, 0;\n"
               "W_LOOP:\nmbarrier.try_wait.parity.shared::cta.b64 p, [%0], %1;\nadd.u32 n, n, 1;\nsetp.lt.and.u32 q, n, %2, !p;\n@q bra W_LOOP;\nW_DONE:\n}"
               :: "r"(bar), "r"(parity), "n"(SPIN_LIMIT) : "memory");
}
static __device__ __forceinline__ uint32_t mbar_test(uint32_t bar, int parity) { uint32_t ok;
  asm volatile("{\n.reg .pred p;\nmbarrier.test_wait.parity.shared::cta.b64 p, [%1], %2;\nselp.u32 %0, 1, 0, p;\n}" : "=r"(ok) : "r"(bar), "r"(parity) : "memory"); return ok; }
static __device__ __forceinline__ void mbar_arrive(uint32_t bar) {
  asm volatile("mbarrier.arrive.shared::cta.b64 _, [%0];" :: "r"(bar) : "memory"); }
static __device__ __forceinline__ void mbar_arrive_cluster_rlx(uint32_t raddr) {
  asm volatile("mbarrier.arrive.relaxed.cluster.shared::cluster.b64 _, [%0];" :: "r"(raddr) : "memory"); }
static __device__ __forceinline__ void tma_load_mc(uint32_t dst, const CUtensorMap* tm, int c1, int c2, uint32_t bar) {
#ifdef NOTMA
  if ((NOTMA >> (c2 >> 3)) & 1) asm volatile("mbarrier.complete_tx.relaxed.cta.shared::cta.b64 [%0], 32768;" :: "r"(bar) : "memory"); else
#endif
  asm volatile("cp.async.bulk.tensor.3d.shared::cluster.global.mbarrier::complete_tx::bytes.multicast::cluster [%0], [%1, {%3, %4, %5}], [%2], %6;"
               :: "r"(dst), "l"(tm), "r"(bar), "r"(0), "r"(c1), "r"(c2), "h"((uint16_t)3) : "memory"); }
static __device__ __forceinline__ void cp16(uint32_t dst, const void* src) {
  asm volatile("cp.async.cg.shared.global [%0], [%1], 16;" :: "r"(dst), "l"(src) : "memory"); }
static __device__ __forceinline__ void mma_1688(float (&d)[4], uint32_t a0, uint32_t a1, uint32_t b0) {
  asm volatile("mma.sync.aligned.m16n8k8.row.col.f32.bf16.bf16.f32 {%0,%1,%2,%3}, {%4,%5}, {%6}, {%0,%1,%2,%3};"
               : "+f"(d[0]), "+f"(d[1]), "+f"(d[2]), "+f"(d[3]) : "r"(a0), "r"(a1), "r"(b0)); }
static __device__ __forceinline__ void mma4(float (&d)[4], uint32_t a0, uint32_t a1, uint32_t a2, uint32_t a3, uint32_t b0, uint32_t b1) {
  asm volatile("mma.sync.aligned.m16n8k16.row.col.f32.bf16.bf16.f32 {%0,%1,%2,%3}, {%4,%5,%6,%7}, {%8,%9}, {%0,%1,%2,%3};"
               : "+f"(d[0]), "+f"(d[1]), "+f"(d[2]), "+f"(d[3]) : "r"(a0), "r"(a1), "r"(a2), "r"(a3), "r"(b0), "r"(b1)); }
static __device__ __forceinline__ void mma4z(float (&d)[4], uint32_t a0, uint32_t a1, uint32_t a2, uint32_t a3, uint32_t b0, uint32_t b1) {
  asm volatile("mma.sync.aligned.m16n8k16.row.col.f32.bf16.bf16.f32 {%0,%1,%2,%3}, {%4,%5,%6,%7}, {%8,%9}, {%10,%10,%10,%10};"
               : "=f"(d[0]), "=f"(d[1]), "=f"(d[2]), "=f"(d[3]) : "r"(a0), "r"(a1), "r"(a2), "r"(a3), "r"(b0), "r"(b1), "f"(0.f)); }
static __device__ __forceinline__ uint32_t clk32() { uint32_t t; asm volatile("mov.u32 %0, %%clock;" : "=r"(t)); return t; }
static __device__ __forceinline__ uint32_t gt32() { uint32_t t; asm volatile("mov.u32 %0, %%globaltimer_lo;" : "=r"(t)); return t; }
static __device__ __forceinline__ void spin(int clk) { if (clk > 0) { uint32_t t = clk32(); while (clk32() - t < (uint32_t)clk) {} } }
static __device__ __forceinline__ void spinv(int clk, uint32_t z) { const uint32_t t = clk32() + (z >> 31); while (clk32() - t < (uint32_t)clk) {} }
#define FENCE() asm volatile("griddepcontrol.launch_dependents;" ::: "memory")
#define OPAQUE_L(p) asm volatile("" : "+l"(p))
#define OPAQUE_R(p) asm volatile("" : "+r"(p))

template <int KK, int K1, int W0, int NW, int FIRST> struct XR {
  static __device__ __forceinline__ void run(float (&d)[16], const uint32_t (&w)[NW][4], uint32_t b16) {
#ifdef NOWG
    if (KK % NOWG == 0)
#endif
    wgmma_n32_ra<(KK >> 2) * 4096 + (KK & 3) * 32, !FIRST>(d, w[W0 + KK], b16);
    XR<KK + 1, K1, W0, NW, 0>::run(d, w, b16);
  }
};
template <int K1, int W0, int NW, int FIRST> struct XR<K1, K1, W0, NW, FIRST> { static __device__ __forceinline__ void run(float (&)[16], const uint32_t (&)[NW][4], uint32_t) {} };
template <int KK, int K0, int K1, int FIRST> struct XS {
  static __device__ __forceinline__ void run(float (&d)[16], uint32_t a16, uint32_t b16) {
#ifdef NOWG
    if (KK % NOWG == 0)
#endif
    wgmma_n32_ss_ta<(KK - K0) * 2048, (KK >> 2) * 4096 + (KK & 3) * 32, !FIRST>(d, a16, b16);
    XS<KK + 1, K0, K1, 0>::run(d, a16, b16);
  }
};
template <int K0, int K1, int FIRST> struct XS<K1, K0, K1, FIRST> { static __device__ __forceinline__ void run(float (&)[16], uint32_t, uint32_t) {} };

static __device__ bf16 g_h[8 * FF];
static __device__ unsigned int g_sbar;
struct SideParams { const bf16* x; const bf16* w_r; const bf16* w_gate; const bf16* w_up; const bf16* w_down; const bf16* gate_w; const bf16* Wo; };

static __device__ __forceinline__ void side_barrier(unsigned int target) {
  __syncthreads();
  if (threadIdx.x == 0) {
    __threadfence();
    atomicAdd(&g_sbar, 1u);
    int n = 0;
    while (*(volatile unsigned int*)&g_sbar < target) { if (++n > (1 << 22)) { g_err = 50; break; } }
    __threadfence();
  }
  __syncthreads();
}
static __device__ __forceinline__ uint4 ldg_nc(const void* p) { uint4 v;
  asm volatile("ld.global.nc.L1::no_allocate.v4.u32 {%0,%1,%2,%3}, [%4];" : "=r"(v.x), "=r"(v.y), "=r"(v.z), "=r"(v.w) : "l"(p)); return v; }
#ifndef SPD
#define SPD 3
#endif
static __device__ __forceinline__ void l2pf(const void* p) { asm volatile("prefetch.global.L2 [%0];" :: "l"(p)); }
static __device__ __forceinline__ void mm8(float (&acc)[8][4], const bf16* W, const bf16* Wn, int ldw, int nk16, uint32_t abase, uint32_t ring, int lane) {
  const int rw = lane >> 3, ch = lane & 7;
  const bf16* wp = W + (size_t)rw * ldw + ch * 8;
  const uint32_t wd = ring + rw * 128, rd = ring + ((rw & 1) * 8 + ch) * 128;
#define MM_LD(k) do { if ((k) < nk16) { const bf16* q = wp + (size_t)(k) * 16 * ldw; \
    _Pragma("unroll") for (int i = 0; i < 4; i++) cp16(wd + ((k) & 3) * 2048 + i * 512 + ((ch ^ (rw + (i & 1) * 4)) << 4), q + (size_t)(4 * i) * ldw); } \
    asm volatile("cp.async.commit_group;" ::: "memory"); } while (0)
  __syncwarp();
  MM_LD(0); MM_LD(1); MM_LD(2);
#pragma unroll 1
  for (int k = 0; k < nk16; k++) {
    if ((k & 1) == 0) {
      const int kp = k + 4 * SPD;
      const bf16* pf = kp < nk16 ? W + (size_t)(kp * 16) * ldw : Wn ? Wn + (size_t)((kp - nk16) * 16) * ldw : nullptr;
      if (pf) l2pf(pf + (size_t)lane * ldw);
    }
    asm volatile("cp.async.wait_group 2;" ::: "memory");
    __syncwarp();
    MM_LD(k + 3);
    const uint32_t a0 = lds32(abase + k * 32), a2 = lds32(abase + k * 32 + 16);
#pragma unroll
    for (int i = 0; i < 4; i++) {
      const uint4 b = ldsm4t(rd + (k & 3) * 2048 + (((2 * i + (rw >> 1)) ^ ch) << 4));
      mma4(acc[2 * i], a0, 0u, a2, 0u, b.x, b.y); mma4(acc[2 * i + 1], a0, 0u, a2, 0u, b.z, b.w);
    }
  }
}
static __device__ __noinline__ void side_work(const SideParams& P, unsigned char* smem, int q) {
  const int tid = threadIdx.x, lane = tid & 31, warp = tid >> 5, g = lane >> 2, t = lane & 3;
  const uint32_t sb = smem_u32(smem);
  unsigned int* cand = reinterpret_cast<unsigned int*>(smem);
  bf16* xs = reinterpret_cast<bf16*>(smem + 1024);
  float* part = reinterpret_cast<float*>(smem + 65536);
  {
    for (int i = tid; i < 256; i += 384) *reinterpret_cast<uint4*>(smem + 1024 + i * 16) = ldg_nc((i < 128 ? P.gate_w : P.w_r - DM) + i * 8);
    __syncthreads();
#pragma unroll 1
    for (int it = warp; it < 64; it += 12) {
      const bf16* xp = P.x + (size_t)(q * 512 + (it >> 1) * 16 + g) * DM + (it & 1) * 512 + t * 8;
      for (int a = it == warp ? 0 : 1; a < 2 && it + 12 * a < 64; a++)
#pragma unroll
        for (int i = 0; i < 4; i++) l2pf(P.x + (size_t)(q * 512 + (it >> 1) * 16 + a * 96 + i * 4 + (lane >> 3)) * DM + (it & 1) * 512 + (lane & 7) * 64);
      const uint32_t xb = sb + 16384 + warp * 16384 + lane * 16;
#pragma unroll
      for (int i = 0; i < 16; i++) { cp16(xb + i * 1024, xp + i * 32); cp16(xb + i * 1024 + 512, xp + 8 * DM + i * 32); }
      asm volatile("cp.async.commit_group;\ncp.async.wait_group 0;" ::: "memory");
      float sg[4] = {0.f, 0.f, 0.f, 0.f}, sr[4] = {0.f, 0.f, 0.f, 0.f};
#pragma unroll
      for (int i = 0; i < 16; i++) {
        const uint4 gw = lds128(sb + 1024 + (it & 1) * 1024 + i * 64 + t * 16), wr = lds128(sb + 3072 + (it & 1) * 1024 + i * 64 + t * 16);
        const uint4 lo = lds128(xb + i * 1024), hi = lds128(xb + i * 1024 + 512);
        mma4(sr, lo.x, hi.x, lo.y, hi.y, wr.x, wr.y); mma4(sr, lo.z, hi.z, lo.w, hi.w, wr.z, wr.w);
        mma4(sg, mulb2(lo.x, gw.x), mulb2(hi.x, gw.x), mulb2(lo.y, gw.y), mulb2(hi.y, gw.y), 0x3F803F80u, 0x3F803F80u);
        mma4(sg, mulb2(lo.z, gw.z), mulb2(hi.z, gw.z), mulb2(lo.w, gw.w), mulb2(hi.w, gw.w), 0x3F803F80u, 0x3F803F80u);
      }
      if (t == 0) {
        float* pp = reinterpret_cast<float*>(smem + 8192) + (it & 1) * 1024 + (it >> 1) * 16 + g;
        pp[0] = sg[0]; pp[8] = sg[2]; pp[512] = sr[0]; pp[520] = sr[2];
      }
    }
    __syncthreads();
    for (int i = tid; i < 512; i += 384) {
      const float* pp = reinterpret_cast<const float*>(smem + 8192);
      g_gate[q * 512 + i] = rbf(1.f / (1.f + expf(-rbf(pp[i] + pp[1024 + i]))));
      g_r[q * 512 + i] = rbf(pp[512 + i] + pp[1536 + i]);
    }
    for (int i = tid; i < 16 * 896; i += 384) part[i] = 0.f;
  }
#define GU(u) (((u) % 28) / 14 ? P.w_up : P.w_gate) + (size_t)((u) / 28) * 512 * FF + q * 896 + ((u) % 14) * 64
  for (int i = lane; i < 64 * SPD; i += 32) l2pf(GU(warp) + (size_t)i * FF);
  side_barrier(4);
  {
    unsigned int key[8];
#pragma unroll
    for (int i = 0; i < 8; i++) {
      const int tok = (warp & 7) * 256 + i * 32 + lane;
      const uint32_t b = __float_as_uint(__ldcg(&g_r[tok]) + 0.f) >> 16;
      key[i] = (((b & 0x8000u) ? (~b & 0xffffu) : (b | 0x8000u)) << 16) | (uint32_t)(2047 - tok);
    }
    for (int pass = 0; pass < 2; pass++) {
      if (pass == 0 ? warp < 8 : warp == 0) {
        for (int c = 0; c < 8; c++) {
          const unsigned int m = __reduce_max_sync(~0u, max(max(max(key[0], key[1]), max(key[2], key[3])), max(max(key[4], key[5]), max(key[6], key[7]))));
#pragma unroll
          for (int i = 0; i < 8; i++) if (key[i] == m) key[i] = 0u;
          if (lane == 0) cand[pass ? 128 + c : warp * 8 + c] = m;
        }
      }
      __syncthreads();
      if (pass == 0 && warp == 0) {
#pragma unroll
        for (int i = 0; i < 8; i++) key[i] = i < 2 ? cand[i * 32 + lane] : 0u;
      }
    }
    if (q == 0 && tid < 8) g_idx[tid] = 2047 - (int)(cand[128 + tid] & 0xffffu);
    for (int i = tid; i < 1024; i += 384) {
      const int c = i >> 7, tok = 2047 - (int)(cand[128 + c] & 0xffffu);
      *reinterpret_cast<uint4*>(xs + c * (FF + 8) + (i & 127) * 8) = ldg_nc(P.x + (size_t)tok * DM + (i & 127) * 8);
    }
    __syncthreads();
  }
  const uint32_t abase = sb + 1024 + g * (FF + 8) * 2 + t * 4, ring = sb + 131072 + warp * 8192;
  for (int u = warp; u < 56; u += 12) {
    const int kh = u / 28, mat = (u % 28) / 14, cb = u % 14;
    float acc[8][4];
#pragma unroll
    for (int i = 0; i < 8; i++) acc[i][0] = acc[i][1] = acc[i][2] = acc[i][3] = 0.f;
    mm8(acc, GU(u), u + 12 < 56 ? GU(u + 12) : nullptr, FF, DM / 32, abase + kh * 1024, ring, lane);
    float* pp = part + (mat * 8 + g) * 896 + cb * 64 + 2 * t;
#pragma unroll
    for (int i = 0; i < 8; i++) { atomicAdd(pp + 8 * i, acc[i][0]); atomicAdd(pp + 8 * i + 1, acc[i][1]); }
  }
  for (int i = lane; i < 64 * SPD; i += 32) l2pf(P.w_down + (size_t)((warp >> 2) * 1216 + i) * DM + q * 256 + (warp & 3) * 64);
  __syncthreads();
  for (int i = tid; i < 8 * 896; i += 384) {
    const float ag = rbf(part[i]), au = rbf(part[8 * 896 + i]);
    g_h[(i / 896) * FF + q * 896 + i % 896] = __float2bfloat16(rbf(ag / (1.f + expf(-ag))) * au);
  }
  side_barrier(8);
  for (int i = tid; i < 8 * FF / 8; i += 384) {
    const int c = i / (FF / 8), o = i % (FF / 8);
    *reinterpret_cast<uint4*>(xs + c * (FF + 8) + o * 8) = __ldcg(reinterpret_cast<const uint4*>(g_h + c * FF + o * 8));
  }
  __syncthreads();
  {
    const int cb = warp & 3, kq = warp >> 2;
    float acc[8][4];
#pragma unroll
    for (int i = 0; i < 8; i++) acc[i][0] = acc[i][1] = acc[i][2] = acc[i][3] = 0.f;
    mm8(acc, P.w_down + (size_t)kq * 1216 * DM + q * 256 + cb * 64, nullptr, DM, kq == 2 ? 72 : 76, abase + kq * 1216 * 2, ring, lane);
#pragma unroll
    for (int i = 0; i < 8; i++) { part[(kq * 8 + g) * 256 + cb * 64 + 2 * t + 8 * i] = acc[i][0]; part[(kq * 8 + g) * 256 + cb * 64 + 2 * t + 8 * i + 1] = acc[i][1]; }
    __syncthreads();
    for (int i = tid; i < 2048; i += 384) {
      const int c = i >> 8, tok = 2047 - (int)(cand[128 + c] & 0xffffu);
      const float y = (part[i] + part[2048 + i]) + part[4096 + i];
      const float rs = rbf(1.f / (1.f + expf(-__ldcg(&g_r[tok]))));
      g_upd[c * DM + q * 256 + (i & 255)] = __float2bfloat16(rbf(y) * rs);
    }
  }
}
struct RecParams { const bf16* mem0; unsigned char* win; };
struct WMaps { CUtensorMap q, k, v; };
#ifndef KB
#define KB 8
#endif
#ifndef WPF
#define WPF 7
#endif
#ifndef WPA
#define WPA 3
#endif
#ifndef XPF
#define XPF 4
#endif
#ifndef O2P
#define O2P 4
#endif
#ifndef XG
#define XG 1
#endif
#ifndef Z0
#define Z0 1
#endif
#ifndef Z1
#define Z1 1
#endif
#ifndef WKP
#define WKP 0
#endif
#ifndef OS
#define OS 1
#endif
#ifndef SO
#define SO 1
#endif
#define RF_FAT 208
#define RF_CTL 88
#define WSPL 1
#define NPROBE 3
#define DLY_TB 700
#define DLY_SIDE 16000
#define KU 32
#define KD 4
#ifndef DLYS
#define DLYS 560, 330, 250, 280, 770, 300, 1248, 850, 460
#endif
#define NTUNE 9
#define TUNE_NAMES {"OM3", "XL", "S", "XD", "WO", "V", "OK", "OKS", "ORR"}
__constant__ int g_tune[NTUNE] = {DLYS};
#define DLY_M3 g_tune[0]
#define DLY_XL g_tune[1]
#define DLY_S g_tune[2]
#define DLY_XD g_tune[3]
#define DLY_WO g_tune[4]
#define DLY_V g_tune[5]
#define DLY_K g_tune[6]
#define DLY_KS g_tune[7]
#define DLY_RR g_tune[8]
#ifdef PRO
__device__ unsigned g_pro[NCTA][16];
#define PT(i, c) do { if (c) g_pro[cta][i] = gt32(); } while (0)
#else
#define PT(i, c)
#endif
#ifdef PER
__device__ unsigned g_pk[NCTA][64], g_pclk[NCTA][64], g_per[NCTA][64], g_end[8] = {0, 0, 0, 0, 0, 0, 0, 100000};
#endif
#define STR2(x) #x
#define STR(x) STR2(x)

static __device__ __forceinline__ void cp16p(uint32_t dst, const void* src, uint32_t v) {
  asm volatile("{\n.reg .pred q;\nsetp.ne.u32 q, %2, 0;\n@q cp.async.cg.shared.global [%0], [%1], 16;\n}" :: "r"(dst), "l"(src), "r"(v) : "memory"); }
static __device__ __forceinline__ void red_bf2(void* p, uint32_t v) {
  asm volatile("red.relaxed.gpu.global.add.noftz.bf16x2 [%0], %1;" :: "l"(p), "r"(v) : "memory"); }
static __device__ __forceinline__ void red_bf2p4(void* p, uint32_t v, uint32_t e) {
  asm volatile("{\n.reg .pred q;\nsetp.lt.u32 q, %2, 4;\n@q red.relaxed.gpu.global.add.noftz.bf16x2 [%0], %1;\n}" :: "l"(p), "r"(v), "r"(e) : "memory"); }
static __device__ __forceinline__ void eta2(void* p, uint32_t t, uint32_t first, uint32_t l16) {
  asm volatile("{\n.reg .pred q;\nsetp.lt.u32 q, %3, 32;\n@q red.relaxed.gpu.global.max.u32 [%0+4], %1;\n@q red.relaxed.gpu.global.add.u32 [%0], %2;\n}" :: "l"(p), "r"(t), "r"(first), "r"(l16) : "memory"); }
static __device__ __forceinline__ void sts16(uint32_t a, uint32_t x) { asm volatile("{\n.reg .b16 h;\ncvt.u16.u32 h, %1;\nst.shared.u16 [%0], h;\n}" :: "r"(a), "r"(x) : "memory"); }
static __device__ __forceinline__ uint32_t cnt_word(uint32_t L) { return (L & 17u) | ((L & 6u) << 1) | ((L & 8u) >> 2); }
static __device__ __forceinline__ uint32_t cnt_line(uint32_t l) { return (l & 17u) | ((l & 12u) >> 1) | ((l & 2u) << 2); }
static __device__ __forceinline__ int m3_check(uint32_t sb, const unsigned char* p3, const unsigned char* pd, int dq, uint32_t l16, uint32_t mc, int hf, int s) {
  const uint32_t md = l16 + (sb + SM_MEM + hf * 8192), dd = l16 + (sb + SM_RD + hf * 256), dc = (l16 >> 2) + (sb + SM_RD + hf * 256);
  int n = 0;
  uint32_t c0 = 0, c1 = 0, d0 = 0, d1 = 0, todo = 1;
#pragma unroll 1
  do {
    if (n) {
      const int src = cnt_word(l16 >> 4);
      const uint32_t m0 = __ballot_sync(~0u, (__shfl_sync(~0u, c0, src) >> 16) != 0x4200u) >> (l16 >> 7), m1 = __ballot_sync(~0u, (__shfl_sync(~0u, c1, src) >> 16) != 0x4200u) >> (l16 >> 7);
      const uint32_t m2 = __ballot_sync(~0u, (d0 >> 16) != 0x4200u), m3 = __ballot_sync(~0u, (d1 >> 16) != 0x4200u);
#pragma unroll
      for (int i = 0; i < 8; i++) { cp16p(md + i * 512, p3 + i * 1024, m0 & (1u << (4 * i))); cp16p(md + 4096 + i * 512, p3 + dq + i * 1024, m1 & (1u << (4 * i))); }
      cp16p(dd, pd, l16 < 256u ? (((l16 & 128u) ? m3 : m2) >> ((l16 >> 2) & 28u)) & 15u : 0u);
      sts32(sb + SM_Z + 40, s);
    }
    n++;
    asm volatile("cp.async.commit_group;\ncp.async.wait_group 0;" ::: "memory");
    __syncwarp();
    asm volatile("{\n.reg .pred p, q;\n.reg .b32 a, b;\n.reg .b16 h, g;\nsetp.ne.u32 p, %4, 0;\n"
                 "@p ld.shared.u32 %2, [%6];\n@p ld.shared.u32 %3, [%6+128];\n@p ld.shared.u32 %0, [%5];\n@p ld.shared.u32 %1, [%5+4096];\n"
                 "lop3.b32 a, %2, %3, 0x42000000, 0x7e;\nlop3.b32 b, %0, %1, 0x42000000, 0x7e;\nor.b32 a, a, b;\nsetp.lt.and.u32 q, a, %8, p;\n"
                 "cvt.u16.u32 h, %2;\ncvt.u16.u32 g, %3;\n@q st.shared.u16 [%5+2], h;\n@q st.shared.u16 [%5+4098], g;\n@q mbarrier.arrive.shared::cta.b64 _, [%7];\n"
                 "@q mov.u32 %4, 0;\n}"
                 : "+r"(c0), "+r"(c1), "+r"(d0), "+r"(d1), "+r"(todo) : "r"(mc), "r"(dc), "r"(sb + SM_BAR + MB_MEM + hf * 8), "r"(n < SPIN_LIMIT ? 0x10000u : ~0u) : "memory");
  } while (__any_sync(~0u, todo));
  return n - 1;
}

__global__ void __cluster_dims__(2, 1, 1) __launch_bounds__(384, 1)
rec_kernel(const __grid_constant__ CUtensorMap tmx, const __grid_constant__ CUtensorMap tmw, const __grid_constant__ WMaps W, RecParams P, const __grid_constant__ SideParams SP) {
  extern __shared__ __align__(1024) unsigned char smem[];
  asm volatile("griddepcontrol.launch_dependents;");
  const uint32_t sb = smem_u32(smem);
  const int tid = threadIdx.x, lane = tid & 31, t128 = tid & 127;
  const int wg = __shfl_sync(~0u, tid >> 7, 0), wq = __shfl_sync(~0u, (tid >> 5) & 3, 0);
  const int r = blockIdx.x & 1, pp = blockIdx.x >> 1;
  const int mi = lane >> 3, r8 = lane & 7;
  const uint32_t xb16 = __shfl_sync(~0u, (((sb + SM_X + (tid >> 7) * 32768 + r * 16384) & 0x3FFFF) >> 4) | (1u << 16), 0);
  const uint32_t va16 = __shfl_sync(~0u, (((sb + SM_WVS + (tid >> 7) * 16384) & 0x3FFFF) >> 4) | (64u << 16), 0);
#if defined(PER) || defined(PRO)
  const uint32_t tstart = gt32();
#endif

  if (tid == 0) {
    mbar_init(sb + SM_BAR + MB_F, 1); mbar_init(sb + SM_BAR + MB_F + 8, 1); mbar_init(sb + SM_BAR + MB_XE0, 2); mbar_init(sb + SM_BAR + MB_XE1, 2); mbar_init(sb + SM_BAR + MB_INIT, 2);
    mbar_init(sb + SM_BAR + MB_MEM, 32); mbar_init(sb + SM_BAR + MB_MEM + 8, 32); for (int i = 0; i < 8; i++) mbar_init(sb + SM_BAR + MB_W + i * 8, 1);
    mbar_init(sb + SM_BAR + MB_XF, 8); mbar_init(sb + SM_BAR + MB_X0, 1); mbar_init(sb + SM_BAR + MB_WO, 1); mbar_init(sb + SM_BAR + MB_VR, 5);
    sts32(sb + SM_Z + 40, ~0u);
    asm volatile("fence.mbarrier_init.release.cluster;" ::: "memory");
  }
  if (tid >= 64 && tid < 96) {
    const uint32_t l16 = lane * 16, qa = ((l16 & 0x30u) << 3) | ((l16 & 0x10u) << 2) | ((l16 >> 3) & 0x30u) | ((l16 >> 4) & 4u);
    sts128(sb + SM_QA + l16, qa + (sb + SM_QKP), (qa ^ 64u) + (sb + SM_QKP), 0u, 0u);
  }
  if (tid == 32) {
    asm volatile("prefetch.tensormap [%0];" :: "l"(&W.q) : "memory"); asm volatile("prefetch.tensormap [%0];" :: "l"(&W.k) : "memory");
    asm volatile("prefetch.tensormap [%0];" :: "l"(&W.v) : "memory"); asm volatile("prefetch.tensormap [%0];" :: "l"(&tmx) : "memory");
  }
  if (tid >= 256 && tid < 320) {
    unsigned char* pl = P.win + r * W_2 + (W_UP | (1u << 19) | ((pp >> 5) << 14)) + (pp & 31) * 128 + wq * 4096;
    stg_r1(pl + lane * 4, 0u);
    uint32_t best = 1u << 30;
    if (lane == 0) {
#pragma unroll 1
      for (int rep = 0; rep < NPROBE; rep++) {
        uint32_t dt;
        asm volatile("{\n.reg .u32 a, b, v;\nmov.u32 a, %%clock;\natom.relaxed.gpu.global.exch.b32 v, [%1], 0;\n"
                     "st.volatile.shared.u32 [%2], v;\nmov.u32 b, %%clock;\nsub.u32 %0, b, a;\n}" : "=r"(dt) : "l"(pl), "r"(sb + SM_SIDE + wq * 4) : "memory");
        best = min(best, dt);
      }
    }
    if (lane == 0) sts32(sb + SM_SIDE + wq * 4, best);
    bar_sync(B_P, 64);
    if (wq == 0) {
      const uint2 bt = lds64(sb + SM_SIDE);
      if (lane < 8 && (r == 0 || pp == 0)) stg_r1(&g_side[(r ? 66 : pp) * 32 + lane], 2u | (bt.x < bt.y ? 1u : 0u));
      spin(DLY_TB);
      uint32_t a, b, c; int n = 0;
#pragma unroll 1
      do {
        a = ldg_r1(&g_side[lane * 32]); b = ldg_r1(&g_side[(32 + lane) * 32]); c = ldg_r1(&g_side[(64 + min(lane, 2)) * 32]);
      } while (!__all_sync(~0u, a & b & c & 2u) && ++n < SPIN_LIMIT);
      a = __ballot_sync(~0u, a & 1u); b = __ballot_sync(~0u, b & 1u); c = __ballot_sync(~0u, c & 1u);
      const uint32_t pol2 = (a ^ (c >> 2)) & 1u;
      c &= 3u;
      const unsigned long long ab = ((unsigned long long)b << 32) | a;
      const int sd = pp < 64 ? (int)(ab >> pp) & 1 : (int)(c >> (pp - 64)) & 1;
      const int n1 = __popcll(ab) + __popc(c), n0 = 66 - n1;
      const int below1 = pp < 64 ? __popcll(ab & ((1ull << pp) - 1)) : __popcll(ab) + (pp == 65 ? (int)(c & 1u) : 0);
      const int rk = sd ? below1 : pp - below1;
      const int k0 = (n0 & 1) ? n0 - 1 : n0 >= n1 ? n0 - 2 : n0, k1 = 64 - k0;
      const int role = rk >= (sd ? k1 : k0) ? 64 + ((n0 & 1) ? sd : rk - (sd ? k1 : k0)) : sd ? k0 + rk : rk;
      __syncwarp();
      if (lane == 0) sts128(sb + SM_SIDE, 2 * k0, 0u, pol2, role * 2 + r);
#ifdef PER
      if (lane == 0) { atomicMax(&g_end[6], gt32()); atomicMin(&g_end[7], max(bt.x, bt.y) - min(bt.x, bt.y)); }
#endif
    }
  }
  __syncthreads();
  const int cta = __shfl_sync(~0u, (int)lds32(sb + SM_SIDE + 12), 0), h = cta >> 2, j = cta & 3, p = j >> 1;
  const int sw = (cta >= __shfl_sync(~0u, (int)lds32(sb + SM_SIDE), 0) ? 1 : 0) ^ r;
  if (cta >= NCTA) {
    spin(DLY_SIDE);
#ifndef NOSIDE
    side_work(SP, smem, cta - NCTA);
#endif
#ifdef PER
    if (threadIdx.x == 0) atomicMax(&g_end[1], gt32());
#endif
    return;
  }
#ifdef PER
  if (threadIdx.x == 0) g_per[cta][63] = tstart;
#endif
#ifdef PRO
  if (tid == 0) { g_pro[cta][0] = tstart; g_pro[cta][1] = gt32(); }
#endif
  asm volatile("barrier.cluster.arrive.relaxed.aligned;" ::: "memory");
#define WLOAD(i0, i1) _Pragma("unroll 1") for (int u = i0; u < i1; u++) {        \
    const int g2 = u >> 2, i = u & 3, k = g2 * 512 + ((i * 128 + r * 256) & 511); \
    const uint32_t mb = sb + SM_BAR + MB_W + u * 8; \
    mbar_expect_tx(mb, i < 2 ? 32768 : 16384); \
    tma_load_2d(sb + g2 * 65536 + i * 8192, &W.q, h * DH + j * 32, k, mb); \
    tma_load_2d(sb + g2 * 65536 + 32768 + i * 8192, &W.k, h * DH + j * 32, k, mb); \
    if (i < 2) tma_load_2d(sb + (i ? SM_WVS : SM_VST) + g2 * 16384, &W.v, h * DH + p * 64, k, mb); }
  if (tid == 288) {
    mbar_expect_tx(sb + SM_BAR + MB_X0, 32768);
#pragma unroll 1
    for (int i = 0; i < 2; i++)
      asm volatile("cp.async.bulk.tensor.3d.shared::cluster.global.mbarrier::complete_tx::bytes [%0], [%1, {%3, %3, %4}], [%2];"
                   :: "r"(sb + SM_MEM + i * 16384), "l"(&tmx), "r"(sb + SM_BAR + MB_X0), "r"(0), "r"(i * 4) : "memory");
    WLOAD(0, 4 + WSPL);
  }
  __syncwarp();
  asm volatile("barrier.cluster.wait.acquire.aligned;" ::: "memory");
#define SIDES() const uint4 sm2 = lds128(sb + SM_SIDE); const int nlo = sm2.x; const uint32_t me = cta >= nlo

#define XLOAD(t, sg) tma_load_mc(sb + SM_X + ((t) * 8 + r * 4) * 4096, &tmx, (sg) * SEG, (t) * 8 + r * 4, sb + SM_BAR + MB_F + (t) * 8)
#define F0LOAD() do { mbar_wait(sb + SM_BAR + MB_XE0, s & 1); \
    if (l16 == 0) XLOAD(0, s + 2); \
    __syncwarp(); } while (0)
  if (wg < 2) {
    asm volatile("setmaxnreg.inc.sync.aligned.u32 " STR(RF_FAT) ";");
    uint32_t w[32][4], wv[8][4];
    uint32_t lm = ((mi >> 1) * 8 + r8) * 128 + (((wq * 2 + (mi & 1)) ^ r8) << 4), l16 = lane * 16;
    lm = __shfl_sync(~0u, lm, lane); l16 = __shfl_sync(~0u, l16, lane);
    {
      const uint32_t lq0 = sb + wg * 65536 + (wq >> 1) * 32768 + ((mi >> 1) * 8 + r8) * 64 + ((((wq & 1) * 2 + (mi & 1)) ^ (r8 >> 1)) << 4);
      const uint32_t f = wq < 2 ? 0x3D003D00u : 0x3F803F80u;
#pragma unroll
      for (int i = 0; i < 4; i++) {
        mbar_wait(sb + SM_BAR + MB_W + (wg * 4 + i) * 8, 0);
        if (i == 3) PT(2 + wg, t128 == 0);
#pragma unroll
        for (int kk = 8 * i; kk < 8 * i + 8; kk++) ldmatrix_x4_trans(w[kk], lq0 + kk * 1024);
        if (i == 0) {
#pragma unroll
          for (int kk = 0; kk < 8; kk++) ldmatrix_x4_trans(wv[kk], sb + SM_VST + wg * 16384 + kk * 2048 + lm);
        }
#pragma unroll
        for (int kk = 32 * i; kk < 32 * i + 32; kk++) w[kk >> 2][kk & 3] = mulb2v(w[kk >> 2][kk & 3], f);
      }
    }
    if (wg == 0) bar_sync(B_V, 160);
    else bar_arrive(B_P, 160);
    const int w8 = wg * 4 + wq;
    const int cw = sw ^ wg;
    const uint32_t xh16 = xb16 ^ 1024u;
    const uint32_t rsb = mapa(sb, r ^ 1);
#define MT (l16 + (sb + SM_MEM + wg * 8192))
#define WA (lm + (sb + SM_WVS + wg * 16384))
#define WOF(f) (lm + (sb + SM_WOS + wg * 32768 + ((f) & 1) * 16384 + ((f) >> 1) * 2048))
#define TH(base) (l16 + (sb + (base) + w8 * 512))
#define TQ(base) (l16 + (sb + (base) + wq * 512))
#define DUMP(base) _Pragma("unroll") for (int n = 0; n < 4; n++) sts128f(TQ((base) + n * 2048), d[4 * n], d[4 * n + 1], d[4 * n + 2], d[4 * n + 3])
#define INIT(base) _Pragma("unroll") for (int n = 0; n < 4; n++) { const float4 t = lds128f(TQ((base) + n * 2048)); d[4 * n] = t.x; d[4 * n + 1] = t.y; d[4 * n + 2] = t.z; d[4 * n + 3] = t.w; }
#define XQK(first, b0, b1) do { wg_fence(); XR<0, 16, 0, 32, first>::run(d, w, b0); XR<0, 16, 16, 32, 0>::run(d, w, b1); wg_commit(); wg_wait0(); } while (0)
#define XVS(first, b0) do { wg_fence(); XS<8, 8, 16, first>::run(d, va16, b0); XR<0, 8, 0, 8, 0>::run(d, wv, b0); wg_commit(); wg_wait0(); } while (0)
#define XREL(mb) do { if (wq == 0 && l16 == 0) { mbar_arrive_cluster_rlx(rsb + SM_BAR + (mb)); mbar_arrive(sb + SM_BAR + (mb)); } } while (0)
#define XFOUT() do { \
          _Pragma("unroll") for (int hf = 0; hf < 2; hf++) \
            stsm4t(l16 + (sb + SM_XF + (wq * 2 + hf) * 512), pack_bf16(d[8 * hf], d[8 * hf + 1]), pack_bf16(d[8 * hf + 2], d[8 * hf + 3]), \
                   pack_bf16(d[8 * hf + 4], d[8 * hf + 5]), pack_bf16(d[8 * hf + 6], d[8 * hf + 7])); \
          __syncwarp(); \
          if (l16 < 32) mbar_arrive(sb + SM_BAR + MB_XF); } while (0)
#define VDUMP(base) _Pragma("unroll") for (int n = 0; n < 2; n++) sts128(TQ((base) + n * 2048), pack_bf16(d[8 * n], d[8 * n + 1]), pack_bf16(d[8 * n + 2], d[8 * n + 3]), pack_bf16(d[8 * n + 4], d[8 * n + 5]), pack_bf16(d[8 * n + 6], d[8 * n + 7]))

    if (wg == 0) {
      float d[16];
      const uint32_t x0 = (((sb + SM_MEM + r * 16384) & 0x3FFFF) >> 4) | (1u << 16), x1 = (((sb + SM_MEM + (r ^ 1) * 16384) & 0x3FFFF) >> 4) | (1u << 16);
      mbar_wait(sb + SM_BAR + MB_X0, 0);
      XQK(1, x0, x1);
      DUMP(SM_CQ);
      XVS(1, x0);
      bar_arrive(B_X2, 256);
      VDUMP(SM_CV);
      bar_sync(B_CQ, 256);
    } else {
      float d[16];
      bar_sync(B_CQ, 256);
      INIT(SM_CQ);
      mbar_wait(sb + SM_BAR + MB_F + 8, 0);
      PT(4, t128 == 0);
      XQK(0, xb16, xh16);
      XFOUT();
      PT(5, t128 == 0);
    }
    if (wg == 0) mbar_wait(sb + SM_BAR + MB_F, 0);
    for (int s = -1;; s++) {
      if (s >= 0) {
        OPAQUE_R(lm); OPAQUE_R(l16);
        {
          uint32_t sa[4][4];
#pragma unroll
          for (int i = 0; i < 2; i++) ldmatrix_x4_trans(sa[i], WA + i * 2048);
          float a[2][4], v[2][4]; uint4 c[4]; uint2 qa;
          FENCE();
          mbar_wait(sb + SM_BAR + MB_MEM + wg * 8, s & 1);
#define QP(i) ((i) >= 12 ? (i) - 8 : (i) % 3 == 1 ? (i) / 3 : 8 + (i) - ((i) + 2) / 3)
#pragma unroll
          for (int i = 0; i < 3; i++) c[i] = ldsm4t(MT + QP(i) * 512);
#pragma unroll
          for (int i = 0; i < 16; i++) {
            if (i + 3 < 16) c[(i + 3) & 3] = ldsm4t(MT + QP(i + 3) * 512);
            if (i == 13) qa = lds64(l16 + (sb + SM_QA));
            if (i == 0) {
              mma4z(a[0], w[2 * QP(i)][0], w[2 * QP(i)][1], w[2 * QP(i)][2], w[2 * QP(i)][3], c[i & 3].x, c[i & 3].y);
              mma4z(a[1], w[2 * QP(i) + 1][0], w[2 * QP(i) + 1][1], w[2 * QP(i) + 1][2], w[2 * QP(i) + 1][3], c[i & 3].z, c[i & 3].w);
            } else {
              mma_16816(a[0], w[2 * QP(i)], c[i & 3].x, c[i & 3].y);
              mma_16816(a[1], w[2 * QP(i) + 1], c[i & 3].z, c[i & 3].w);
            }
            if (QP(i) == 0) {
              mma4z(v[0], wv[0][0], wv[0][1], wv[0][2], wv[0][3], c[i & 3].x, c[i & 3].y);
              mma4z(v[1], wv[1][0], wv[1][1], wv[1][2], wv[1][3], c[i & 3].z, c[i & 3].w);
            } else if (QP(i) < 4) {
              mma_16816(v[0], wv[2 * (QP(i) & 3)], c[i & 3].x, c[i & 3].y);
              mma_16816(v[1], wv[2 * (QP(i) & 3) + 1], c[i & 3].z, c[i & 3].w);
            }
            if (i == 12) {
              mma_16816(v[0], sa[0], c[0].x, c[0].y); mma_16816(v[1], sa[1], c[0].z, c[0].w);
            }
            if (i == 13) { ldmatrix_x4_trans(sa[0], WA + 2 * 2048); ldmatrix_x4_trans(sa[1], WA + 3 * 2048); ldmatrix_x4_trans(sa[2], WA + 4 * 2048); }
            FENCE();
          }
#pragma unroll
          for (int i = 0; i < 4; i++) sts32(((i & 1) ? qa.y : qa.x) + (w8 * 512 + (i >> 1) * 8), f2u(a[0][i] + a[1][i]));
          bar_arrive(B_QK, 288);
          bar_arrive(B_QK1, 288);
          FENCE();
          uint32_t sc2[4];
          ldmatrix_x4_trans(sa[3], WA + 5 * 2048); ldmatrix_x4_trans(sc2, WA + 6 * 2048);
          mma_16816(v[0], sa[0], c[1].x, c[1].y); mma_16816(v[1], sa[1], c[1].z, c[1].w);
          FENCE();
          ldmatrix_x4_trans(sa[0], WA + 7 * 2048);
          FENCE();
          mma_16816(v[0], sa[2], c[2].x, c[2].y); mma_16816(v[1], sa[3], c[2].z, c[2].w);
          mma_16816(v[0], sc2, c[3].x, c[3].y); mma_16816(v[1], sa[0], c[3].z, c[3].w);
          FENCE();
          sts128f(TH(SM_VP), v[0][0] + v[1][0], v[0][1] + v[1][1], v[0][2] + v[1][2], v[0][3] + v[1][3]);
          bar_arrive(B_V, 320);
        }
        if (s == NSEG - 1) break;
        OPAQUE_R(lm); OPAQUE_R(l16);
        uint32_t wo[WPF][4];
        {
          float d[16];
#define XOUT(g) _Pragma("unroll") for (int n = 0; n < 2; n++) sts128f(TQ(SM_CQ + ((g) * 2 + n) * 2048), d[8 - 8 * (g) + 4 * n], d[9 - 8 * (g) + 4 * n], d[10 - 8 * (g) + 4 * n], d[11 - 8 * (g) + 4 * n])
#define XIN(g) do { \
            const float4 t0 = lds128f(TQ(SM_CQ + (2 - 2 * (g)) * 2048)), t1 = lds128f(TQ(SM_CQ + (3 - 2 * (g)) * 2048)); \
            stsm4t(l16 + (sb + SM_XF + (wq * 2 + (g)) * 512), pack_bf16(d[8 * (g)] + t0.x, d[8 * (g) + 1] + t0.y), pack_bf16(d[8 * (g) + 2] + t0.z, d[8 * (g) + 3] + t0.w), \
                   pack_bf16(d[8 * (g) + 4] + t1.x, d[8 * (g) + 5] + t1.y), pack_bf16(d[8 * (g) + 6] + t1.z, d[8 * (g) + 7] + t1.w)); } while (0)
          if (wg == 0) {
            INIT(SM_CW);
            bar_sync(B_PUB, 320);
            wg_fence();
            XR<KB, 16, 0, 32, 0>::run(d, w, xb16); XR<0, 16, 16, 32, 0>::run(d, w, xh16);
            wg_commit(); wg_wait0();
            TSF(13, 1);
            OPAQUE_R(l16);
            XOUT(0);
            bar_arrive(B_G1, 256);
            XREL(MB_XE0);
            bar_sync(B_CQ, 256);
            XIN(0);
#pragma unroll
            for (int f = 0; f < WPA; f++) ldmatrix_x4_trans(wo[f], WOF(f));
          } else {
            const uint32_t ok = mbar_test(sb + SM_BAR + MB_F + 8, (s + 1) & 1);
            bar_sync(B_PUB, 320);
            if (!ok) mbar_wait(sb + SM_BAR + MB_F + 8, (s + 1) & 1);
            wg_fence();
#if WKP
            XR<0, 16, 0, 32, 1>::run(d, w, xb16); XR<0, WKP - 16, 16, 32, 0>::run(d, w, xh16);
            wg_commit(); wg_fence();
            XR<WKP - 16, WKP - 15, 16, 32, 0>::run(d, w, xh16);
#pragma unroll
            for (int f = 0; f < WPA; f++) ldmatrix_x4_trans(wo[f], WOF(f));
            wg_commit(); wg_fence();
            XR<WKP - 15, 16, 16, 32, 0>::run(d, w, xh16);
            wg_commit();
#else
            XR<0, 16, 0, 32, 1>::run(d, w, xb16); XR<0, 16, 16, 32, 0>::run(d, w, xh16);
            wg_commit();
#pragma unroll
            for (int f = 0; f < WPA; f++) ldmatrix_x4_trans(wo[f], WOF(f));
#endif
            wg_wait0();
            TSF(31, 5);
            OPAQUE_R(l16);
            XOUT(1);
            bar_arrive(B_CQ, 256);
            bar_sync(B_G1, 256);
            XIN(1);
          }
          __syncwarp();
          if (l16 == 0) mbar_arrive(sb + SM_BAR + MB_XF);
          TSF(3, 5);
        }
        if (Z1 && s == 0) {
          mbar_wait(sb + SM_BAR + MB_WO, 0);
#pragma unroll
          for (int f = 0; f < WPA; f++) ldmatrix_x4_trans(wo[f], WOF(f));
        }
#pragma unroll
        for (int f = WPA; f < WPF; f++) ldmatrix_x4_trans(wo[f], WOF(f));
        unsigned char* pa = P.win + (w_ar(s) + (j * 32 + cw * 16 + wq * 2) * 256 + (l16 >> 2));
        uint32_t ce = (l16 >> 4) - 4 * (cw * 4 + wq);
        OPAQUE_L(pa); OPAQUE_R(ce);
        FENCE();
        bar_sync(wg ? B_O : B_O2, wg || !XG ? 192 : 224);
        uint4 ob[2];
        ob[0] = ldsm4(l16 + (sb + SM_OF)); ob[1] = ldsm4(l16 + (sb + SM_OF + 512));
        float acc[2][4]; uint32_t f0ok;
#pragma unroll
        for (int f = 0; f < 16; f++) {
          const int ks = f >> 1;
          const uint32_t b0 = (ks & 1) ? ob[(ks >> 1) & 1].z : ob[(ks >> 1) & 1].x, b1 = (ks & 1) ? ob[(ks >> 1) & 1].w : ob[(ks >> 1) & 1].y;
          if (f < 2) mma4z(acc[f], wo[f][0], wo[f][1], wo[f][2], wo[f][3], b0, b1);
          else mma_16816(acc[f % 2], wo[f < WPF ? f : 2 + (f - WPF) % (WPF - 2)], b0, b1);
          if (f - 1 >= 2 && f - 1 + (WPF - 2) < 16) {
            const int nf = f - 1 + (WPF - 2);
            ldmatrix_x4_trans(wo[2 + (nf - WPF) % (WPF - 2)], WOF(nf));
          }
          if (f == 4 || f == 8) ob[((f >> 2) - 1) & 1] = ldsm4(l16 + (sb + SM_OF + (1 + (f >> 2)) * 512));
          if (f == 12) f0ok = mbar_test(sb + SM_BAR + MB_F, (s + 1) & 1);
          if (f < 15) FENCE();
        }
        if (!wg) bar_arrive(B_CV, 256);
        red_bf2(pa, pack_bf16(acc[0][0], ce == 0 ? 1.f : acc[0][1])); red_bf2(pa + 256, pack_bf16(acc[0][2], ce == 1 ? 1.f : acc[0][3]));
        red_bf2(pa + 2048, pack_bf16(acc[1][0], ce == 2 ? 1.f : acc[1][1])); red_bf2(pa + 2304, pack_bf16(acc[1][2], ce == 3 ? 1.f : acc[1][3]));
        red_bf2p4(pa + (W_DS + (wq & 1) * 256), pack_bf16(ce == 0 ? acc[0][1] : ce == 1 ? acc[0][3] : ce == 2 ? acc[1][1] : acc[1][3], 1.f), ce);
        TSF(4, 1); TSF(2, 6);
        if (wg) bar_sync(B_CV, 256);
        else if (!f0ok) mbar_wait(sb + SM_BAR + MB_F, (s + 1) & 1);
      }
      OPAQUE_R(lm); OPAQUE_R(l16);
      {
        float d[16];
        const uint32_t cv = TQ(SM_CV + ((s ^ wg) & 1) * 4096);
        TSF(9, 1);
        wg_fence();
        XR<0, 1, 0, 8, 1>::run(d, wv, xb16); XS<8, 8, 9, 0>::run(d, va16, xb16); XR<1, 2, 0, 8, 0>::run(d, wv, xb16); XS<9, 8, 10, 0>::run(d, va16, xb16);
        XR<2, 3, 0, 8, 0>::run(d, wv, xb16); XS<10, 8, 11, 0>::run(d, va16, xb16); XR<3, 4, 0, 8, 0>::run(d, wv, xb16); XS<11, 8, 12, 0>::run(d, va16, xb16);
        XR<4, 5, 0, 8, 0>::run(d, wv, xb16); XS<12, 8, 13, 0>::run(d, va16, xb16); XR<5, 6, 0, 8, 0>::run(d, wv, xb16); XS<13, 8, 14, 0>::run(d, va16, xb16);
        XR<6, 7, 0, 8, 0>::run(d, wv, xb16); XS<14, 8, 15, 0>::run(d, va16, xb16); XR<7, 8, 0, 8, 0>::run(d, wv, xb16); XS<15, 8, 16, 0>::run(d, va16, xb16);
        wg_commit(); wg_wait0();
        uint32_t q[8];
#pragma unroll
        for (int i = 0; i < 8; i++) q[i] = pack_bf16(d[2 * i], d[2 * i + 1]);
        if (wg == 0) {
          sts128(cv, q[0], q[1], q[2], q[3]); sts128(cv + 2048, q[4], q[5], q[6], q[7]);
          wg_fence(); XR<0, KB, 0, 32, 1>::run(d, w, xb16); wg_commit(); wg_wait0();
          OPAQUE_R(l16);
          DUMP(SM_CW);
          TSF(5, 1);
        } else {
          const uint4 o = lds128(cv + (r ^ 1) * 2048), k = lds128(cv + r * 2048);
          XREL(MB_XE1);
          st_async4(l16 + (rsb + SM_VR + wq * 512), u2f(addb2(r ? q[0] : q[4], o.x)), u2f(addb2(r ? q[1] : q[5], o.y)), u2f(addb2(r ? q[2] : q[6], o.z)), u2f(addb2(r ? q[3] : q[7], o.w)),
                    rsb + SM_BAR + MB_VR);
          sts128(TQ(SM_VL), addb2(r ? q[4] : q[0], k.x), addb2(r ? q[5] : q[1], k.y), addb2(r ? q[6] : q[2], k.z), addb2(r ? q[7] : q[3], k.w));
          __syncwarp();
          if (l16 == 0) mbar_arrive(sb + SM_BAR + MB_VR);
          TSF(28, 5);
        }
      }
    }
  } else {
    asm volatile("setmaxnreg.dec.sync.aligned.u32 " STR(RF_CTL) ";");
    const int g = lane >> 2, tq = lane & 3;
    if (wq == 0) {
      if (lane < 12) asm volatile("prefetch.global.L2 [%0];" :: "l"(SP.x + (size_t)(cta * 12 + lane) * 64));
      __syncwarp();
      {
        SIDES();
        const uint32_t o[6] = {w_blk(w_h1(cta), me), w_blk(w_h1(cta) ^ H1_V, me), w_blk(w_mvx(cta, 0), me ^ sm2.z), w_blk(w_mvx(cta, 1), me ^ sm2.z),
                               w_blk(w_mxa(cta, 0), me ^ sm2.z), w_blk(w_mxa(cta, 1), me ^ sm2.z)};
#pragma unroll
        for (int i = 0; i < 24; i++) stg_r4(P.win + (o[i >> 2] + (i & 3) * 512 + lane * 16), 0u, 0u, 0u, 0u);
#pragma unroll
        for (int i = 0; i < 6; i++) stg_r1(P.win + (w_ar(i >> 1) + cta * 256 + (i & 1) * W_DS + lane * 4), 0u);
        __threadfence();
        __syncwarp();
      }
      {
        const uint32_t wv = movm(*reinterpret_cast<const uint32_t*>(P.mem0 + g * DM + cta * 8 + tq * 2));
        const bool sp = lane == cnt_word(cta & 31);
        stg_r1(P.win + (w_ar(-1) + cta * 256 + lane * 4), sp ? (wv & 0xffffu) | 0x42000000u : wv);
        if (sp) stg_r1(P.win + (w_ar(-1) + ((cta & ~9) + ((cta >> 1) & 1)) * 256 + W_DS + lane * 4), (wv >> 16) | 0x42000000u);
      }
      bar_sync(B_V, 160);
      if (lane == 0) {
        fence_async_smem(); mbar_arrive_cluster_rlx(mapa(sb + SM_BAR + MB_INIT, 0)); mbar_arrive_cluster_rlx(mapa(sb + SM_BAR + MB_INIT, 1));
        mbar_wait(sb + SM_BAR + MB_INIT, 0);
        mbar_expect_tx(sb + SM_BAR + MB_F, 32768);
        mbar_expect_tx(sb + SM_BAR + MB_F + 8, 32768);
        XLOAD(1, 0); XLOAD(0, 1);
        WLOAD(4 + WSPL, 8);
      }
      __syncwarp();
#ifdef PER
      if (lane == 0) atomicMax(&g_end[5], gt32());
#endif
    }
    bar_sync(B_X2, 256);
    SIDES();
    uint32_t l16 = __shfl_sync(~0u, lane * 16, lane);
    const uint32_t me2 = me ^ sm2.z;
    const float sc = 32.f * 0.08838834764831845f * 1.4426950408889634f;
    uint32_t ls = l16 + sb;
#define PVM(o, zs, p0, p2, M1, M2, M3) do { \
        FENCE(); \
        mma4z(zs, 0x3F803F80u, 0x3F803F80u, 0x3F803F80u, 0x3F803F80u, p0.x, p0.y); \
        FENCE(); M1; \
        _Pragma("unroll") for (int t = 0; t < 4; t++) mma4z(o[t], va[2 * t].x, va[2 * t].y, va[2 * t].z, va[2 * t].w, p0.x, p0.y); \
        FENCE(); M2; \
        mma4(zs, 0x3F803F80u, 0x3F803F80u, 0x3F803F80u, 0x3F803F80u, p0.z, p0.w); \
        _Pragma("unroll") for (int t = 0; t < 2; t++) mma4(o[t], va[2 * t + 1].x, va[2 * t + 1].y, va[2 * t + 1].z, va[2 * t + 1].w, p0.z, p0.w); \
        FENCE(); M3; \
        mma_1688(zs, 0x3F803F80u, 0x3F803F80u, p2); \
        _Pragma("unroll") for (int t = 2; t < 4; t++) mma4(o[t], va[2 * t + 1].x, va[2 * t + 1].y, va[2 * t + 1].z, va[2 * t + 1].w, p0.z, p0.w); \
        mma_1688(o[0], vm[0].x, vm[0].y, p2); mma_1688(o[1], vm[0].z, vm[0].w, p2); mma_1688(o[2], vm[1].x, vm[1].y, p2); mma_1688(o[3], vm[1].z, vm[1].w, p2); } while (0)
#define PVE(o, z, dst) do { \
        const float i0 = rcpf(z[0]), i1 = rcpf(z[1]); \
        _Pragma("unroll") for (int u = 0; u < 2; u++) \
          stsm4t(ls + (dst) + u * 1024, pack_bf16(o[2 * u][0] * i0, o[2 * u][1] * i1), pack_bf16(o[2 * u][2] * i0, o[2 * u][3] * i1), \
                 pack_bf16(o[2 * u + 1][0] * i0, o[2 * u + 1][1] * i1), pack_bf16(o[2 * u + 1][2] * i0, o[2 * u + 1][3] * i1)); } while (0)
    const uint32_t lq = (l16 ^ ((l16 >> 1) & 64u)) + sb, l12 = (l16 >> 2) * 3;
#define M3PTR(sl) \
            const uint32_t tf = me ^ 1 ^ r, m3i = w_ar(sl) + (wq & 1) * 16384 + (l16 & 0x70u) + ((l16 & 0x180u) << 1); \
            const unsigned char* p0f = P.win + (m3i + r * 8192 + tf * 4096); const unsigned char* p0n = P.win + (m3i + r * 8192 + (tf ^ 1) * 4096); \
            const unsigned char* p1f = P.win + (m3i + (r ^ 1) * 8192 + (tf ^ 1) * 4096); const unsigned char* p1n = P.win + (m3i + (r ^ 1) * 8192 + tf * 4096); \
            const unsigned char* pd = P.win + (w_ar(sl) + (wq & 1) * 16384 + (((l16 >> 7) ^ r) & 1u) * 8192 + ((l16 & 64u) * 4 + (l16 & 48u) * 2 + (l16 & 16u)) * 16 + W_DS + (l16 & 0x70u)); \
            uint32_t mf = ls + SM_MEM + (wq & 1) * 8192 + tf * 2048, mn = ls + SM_MEM + (wq & 1) * 8192 + (tf ^ 1) * 2048, nr = l16 < 256u ? 1u + (((l16 >> 6) ^ (l16 >> 7) ^ tf) & 1u) : 0u; \
            OPAQUE_L(p0f); OPAQUE_L(p0n); OPAQUE_L(p1f); OPAQUE_L(p1n); OPAQUE_L(pd); OPAQUE_R(mf); OPAQUE_R(mn); OPAQUE_R(nr); FENCE()
#define M3REQ() \
            _Pragma("unroll") for (int i = 0; i < 4; i++) { cp16(mn + 4096 + i * 512, p1f + i * 1024); cp16(mf + i * 512, p0f + i * 1024); } \
            cp16p(ls + SM_RD + (wq & 1) * 256, pd, nr & 1u); \
            _Pragma("unroll") for (int i = 0; i < 4; i++) { cp16(mf + 4096 + i * 512, p1n + i * 1024); cp16(mn + i * 512, p0n + i * 1024); } \
            cp16p(ls + SM_RD + (wq & 1) * 256, pd, nr & 2u)
    if (wq >= 2) { M3PTR(-1); M3REQ(); }
    if (wq == 0) {
      bar_sync(B_P, 160);
      if (l16 == 0) {
        fence_async_smem();
        mbar_expect_tx(sb + SM_BAR + MB_WO, 65536);
        for (int i = 0; i < 8; i++) tma_load_2d(sb + SM_WOS + i * 8192, &tmw, j * 256 + ((i >> 1) ^ (2 * sw)) * 64, h * DH + (i & 1) * 64, sb + SM_BAR + MB_WO);
      }
      __syncwarp();
    }
#define ETA(k, first) ETAT(gt32() + (k), first)
#define ETAT(tm, first) do { unsigned char* pt = P.win + (w_ar(s) + (W_DS + 256) + (cta >> 5) * 8192 + ((cta >> 4) & 1) * 2048 + (l16 & 16u) * 256); \
          asm volatile("{\n.reg .pred q;\nsetp.lt.u32 q, %2, 32;\n@q red.relaxed.gpu.global.max.u32 [%0+4], %1;\n}" :: "l"(pt), "r"(tm), "r"(l16) : "memory"); \
          if (first) asm volatile("{\n.reg .pred q;\nsetp.lt.u32 q, %1, 32;\n@q red.relaxed.gpu.global.add.u32 [%0], 1;\n}" :: "l"(pt), "r"(l16) : "memory"); } while (0)
    if (wq == 1) {
      const uint32_t xin = w_blk(w_mxa(cta, 0), me2) + l16;
      const uint32_t lsq = sb + ((l16 & 0x70u) | ((l16 & 0x80u) << 1) | ((l16 & 0x100u) >> 1));
      mbar_wait(sb + SM_BAR + MB_MEM, 0); mbar_wait(sb + SM_BAR + MB_MEM + 8, 0);
      for (int s = 0; s < NSEG; s++) {
        const uint32_t t2 = ((s >> 1) & 1) ^ 1;
        mbar_wait(sb + SM_BAR + MB_XF, s & 1);
        {
        uint4 kx[4], qx[4];
#pragma unroll
        for (int i = 0; i < 4; i++) { kx[i] = ldsm4(ls + (SM_XF + (4 + i) * 512)); qx[i] = ldsm4(lsq + (SM_XF + i * 512)); }
        const uint32_t db = w_blk(w_mxa(h * 4, s), me2) + l16 - 512;
        {
          float S[2][4][4];
          if (XG == 2 && s > 0) bar_arrive(B_O2, 224);
          FENCE();
#pragma unroll
          for (int mt = 0; mt < 2; mt++) {
            const uint4 q0 = qx[mt];
            mma4z(S[mt][0], q0.x, q0.y, q0.z, q0.w, kx[0].x, kx[0].y); mma4z(S[mt][1], q0.x, q0.y, q0.z, q0.w, kx[0].z, kx[0].w);
            mma4z(S[mt][2], q0.x, q0.y, q0.z, q0.w, kx[1].x, kx[1].y); mma4z(S[mt][3], q0.x, q0.y, q0.z, q0.w, kx[1].z, kx[1].w);
          }
#pragma unroll
          for (int mt = 0; mt < 2; mt++) {
            const uint4 q1 = qx[2 + mt];
            mma4(S[mt][0], q1.x, q1.y, q1.z, q1.w, kx[2].x, kx[2].y); mma4(S[mt][1], q1.x, q1.y, q1.z, q1.w, kx[2].z, kx[2].w);
            mma4(S[mt][2], q1.x, q1.y, q1.z, q1.w, kx[3].x, kx[3].y); mma4(S[mt][3], q1.x, q1.y, q1.z, q1.w, kx[3].z, kx[3].w);
          }
          FENCE();
          if (XG == 1 && s > 0) bar_arrive(B_O2, 224);
          FENCE();
#pragma unroll
          for (int u = 0; u < 4; u++) {
            const int mt = u >> 1, c = 2 * (u & 1);
            const uint32_t m0 = tagw(pack_f16(S[mt][0][c], S[mt][0][c + 1]), t2), m1 = pack_f16(S[mt][1][c], S[mt][1][c + 1]),
                           m2 = pack_f16(S[mt][2][c], S[mt][2][c + 1]), m3 = pack_f16(S[mt][3][c], S[mt][3][c + 1]);
            const int e = u ^ j;
            if (e) stg_r4(P.win + (db + mt * 16384 + (u & 1) * 2048 + e * 512), m0, m1, m2, m3);
            else sts128(ls + SM_XS, m0, m1, m2, m3);
          }
        }
        TS(15);
        float sx[10];
        const unsigned char* pa = P.win + (xin + ((s & 1) << 20));
        uint4 xv[3];
        if (s > 0) spin(DLY_XD);
#pragma unroll
        for (int i = 0; i < 3; i++) xv[i] = ldg_r4(pa + i * 512);
        FENCE();
        int n = 0; float mx;
        auto xsum = [&]() {
#pragma unroll 1
        while (__any_sync(~0u, (x3(xv[0].x, xv[1].x, t2) | (xv[2].x ^ t2)) & 1u) && ++n < SPIN_LIMIT) {
#pragma unroll
          for (int i = 0; i < 3; i++) xv[i] = ldg_r4(pa + i * 512);
        }
        {
          const uint4 v3 = lds128(ls + SM_XS);
          sum_h4(sx[2], sx[3], xv[0].x, xv[1].x, xv[2].x, v3.x); sum_h4(sx[4], sx[5], xv[0].y, xv[1].y, xv[2].y, v3.y);
          sum_h4(sx[6], sx[7], xv[0].z, xv[1].z, xv[2].z, v3.z); sum_h4(sx[8], sx[9], xv[0].w, xv[1].w, xv[2].w, v3.w);
          const int row = 8 * j + g - 2 * tq;
#pragma unroll
          for (int i = 0; i < 8; i++) if ((i >> 1) * 8 + (i & 1) > row) sx[2 + i] = -INFINITY;
        }
        mx = fmaxf(fmaxf(fmaxf(sx[2], sx[3]), fmaxf(sx[4], sx[5])), fmaxf(fmaxf(sx[6], sx[7]), fmaxf(sx[8], sx[9])));
        };
        if (!Z0 || s > 0) xsum();
        else {
#pragma unroll
          for (int i = 2; i < 10; i++) sx[i] = 0.f;
          mx = 0.f;
        }
        sts32(ls - l12 + SM_XS + 512, f2u(mx));
        {
          if (l16 == 0) mbar_expect_tx(sb + SM_BAR + MB_VR, 2048);
          unsigned char* d = P.win + (w_blk(w_mvx(cta, s), me2) + l16);
          OPAQUE_L(d); FENCE();
          mbar_wait(sb + SM_BAR + MB_VR, s & 1);
#pragma unroll
          for (int t = 0; t < 4; t++) {
            const uint4 a0 = lds128(ls + (SM_VL + t * 512)), a1 = lds128(ls + (SM_VR + t * 512));
            stg_r4(d + t * 512, tagw(addb2(a0.x, a1.x), t2), addb2(a0.y, a1.y), addb2(a0.z, a1.z), addb2(a0.w, a1.w));
          }
          TS(23);
        }
        unsigned char* pm = P.win + (db + 2048 + j * 128 - l12);
        const unsigned char* py = pa + 1536 - l12;
        OPAQUE_L(pm); OPAQUE_L(py);
        if (s > 0) bar_sync(B_PXF, 96);
        FENCE();
        bar_sync(B_QK1, 288);
        uint32_t kb[2][2];
#pragma unroll
        for (int t = 0; t < 2; t++) {
          const float4 u = lds128f(lq + (SM_QKP + (2 + t) * 512)), v4 = lds128f(lq + (SM_QKP + 2048 + (2 + t) * 512));
          kb[t][0] = pack_bf16(u.x + v4.x, u.y + v4.y); kb[t][1] = pack_bf16(u.z + v4.z, u.w + v4.w);
        }
        float S[2][4];
#pragma unroll
        for (int mt = 0; mt < 2; mt++) mma4z(S[mt], qx[mt].x, qx[mt].y, qx[mt].z, qx[mt].w, kb[0][0], kb[0][1]);
#pragma unroll
        for (int mt = 0; mt < 2; mt++) mma4(S[mt], qx[2 + mt].x, qx[2 + mt].y, qx[2 + mt].z, qx[2 + mt].w, kb[1][0], kb[1][1]);
        PT(14, s == 0 && l16 == 0);
        if (!Z1 && s == 0) mbar_wait(sb + SM_BAR + MB_WO, 0);
        PT(15, s == 0 && l16 == 0);
        if (s < NSEG - 1) bar_arrive(B_PUB, 320);
        FENCE();
#pragma unroll
        for (int u = 0; u < 4; u++) stg_r1(pm + (u >> 1) * 16384 + (u & 1) * 2048, tagw(pack_f16(S[u >> 1][2 * (u & 1)], S[u >> 1][2 * (u & 1) + 1]), t2));
        TS(30);
        FENCE();
        if (Z0 && s == 0) xsum();
        spin(DLY_XL);
        uint32_t xy[4];
#pragma unroll
        for (int i = 0; i < 4; i++) xy[i] = ldg_r1(py + i * 128);
        FENCE();

        n = 0;
#pragma unroll 1
        while (__any_sync(~0u, (x3(xy[0], xy[1], t2) | x3(xy[2], xy[3], t2)) & 1u) && ++n < SPIN_LIMIT) {
#pragma unroll
          for (int i = 0; i < 4; i++) xy[i] = ldg_r1(py + i * 128);
        }
        sum_h4(sx[0], sx[1], xy[0], xy[1], xy[2], xy[3]);
        mx = fmaxf(mx, fmaxf(sx[0], sx[1]));
        mx = fmaxf(fmaxf(mx, __shfl_xor_sync(~0u, mx, 1)), fmaxf(__shfl_xor_sync(~0u, mx, 2), __shfl_xor_sync(~0u, mx, 3)));
#pragma unroll
        for (int i = 0; i < 10; i++) sx[i] = ex2(fmaf(sx[i], sc, -sc * mx));
        sts128(ls + SM_PX, pack_bf16(sx[2], sx[3]), pack_bf16(sx[4], sx[5]), pack_bf16(sx[6], sx[7]), pack_bf16(sx[8], sx[9]));
        sts32(ls - l12 + SM_PX + 512, pack_bf16(sx[0], sx[1]));
        bar_arrive(B_PX, 96);
        TS(1);
        }
      }
    } else {
      const uint32_t ho = (wq & 1) * 512 + l16, hv = wq == 0 ? 0u : H1_V;
      uint32_t ow = w_blk(w_h1(cta) ^ hv, me) + ho, or0 = w_blk(w_h1(cta ^ 1) ^ hv, me) + ho, or1 = w_blk(w_h1((cta ^ 2) & ~1) ^ hv, me) + ho;
#define PTRS() OPAQUE_R(ow); OPAQUE_R(or0); OPAQUE_R(or1); \
      unsigned char* pw0 = P.win + ow; const unsigned char* pr0 = P.win + or0; const unsigned char* pr1 = P.win + or1; \
      OPAQUE_L(pw0); OPAQUE_L(pr0); OPAQUE_L(pr1); FENCE()
      if (wq == 0) {
        const uint32_t xcnt = me ? NCTA - nlo : nlo, xrank = (me ? cta - nlo : cta) + lane * xcnt;
        int kd = DLY_K;
        mbar_wait(sb + SM_BAR + MB_XE1, 0);
        if (l16 == 0) { mbar_expect_tx(sb + SM_BAR + MB_F + 8, 32768); XLOAD(1, 1); }
        __syncwarp();
        for (int s = 0; s < NSEG - 1; s++) {
          const uint32_t tg = (s & 1) ^ 1;
          mbar_wait(sb + SM_BAR + MB_XF, s & 1);
          uint4 xf[4];
#pragma unroll
          for (int i = 0; i < 4; i++) xf[i] = ldsm4(ls + (SM_XF + (4 + i) * 512));
          PTRS();
          unsigned char* pw1 = pw0 + 512 - l12; OPAQUE_L(pw1);
          bar_sync(B_QK, 288);
          float4 u[4], v4[4];
#pragma unroll
          for (int t = 0; t < 4; t++) { u[t] = lds128f(lq + (SM_QKP + t * 512)); v4[t] = lds128f(lq + (SM_QKP + 2048 + t * 512)); }
          FENCE();
          uint32_t f[4][2], m[5];
#pragma unroll
          for (int t = 0; t < 2; t++) { f[t][0] = pack_bf16(u[t].x + v4[t].x, u[t].y + v4[t].y); f[t][1] = pack_bf16(u[t].z + v4[t].z, u[t].w + v4[t].w); }
          float S[5][4], T[5][4];
          mma4z(S[1], f[0][0], f[1][0], f[0][1], f[1][1], xf[0].x, xf[0].y); mma4z(T[1], f[0][0], f[1][0], f[0][1], f[1][1], xf[2].x, xf[2].y);
          mma4z(S[2], f[0][0], f[1][0], f[0][1], f[1][1], xf[0].z, xf[0].w); mma4z(T[2], f[0][0], f[1][0], f[0][1], f[1][1], xf[2].z, xf[2].w);
          FENCE();
#pragma unroll
          for (int t = 2; t < 4; t++) { f[t][0] = packv(u[t].x, v4[t].x, u[t].y, v4[t].y); f[t][1] = packv(u[t].z, v4[t].z, u[t].w, v4[t].w); }
          mma4z(S[3], f[0][0], f[1][0], f[0][1], f[1][1], xf[1].x, xf[1].y); mma4z(T[3], f[0][0], f[1][0], f[0][1], f[1][1], xf[3].x, xf[3].y);
          mma4z(S[4], f[0][0], f[1][0], f[0][1], f[1][1], xf[1].z, xf[1].w); mma4z(T[4], f[0][0], f[1][0], f[0][1], f[1][1], xf[3].z, xf[3].w);
          FENCE();
          mma4z(S[0], f[0][0], f[1][0], f[0][1], f[1][1], f[2][0], f[2][1]); mma4z(T[0], f[0][0], f[1][0], f[0][1], f[1][1], f[3][0], f[3][1]);
          bar_arrive(B_PUB, 320);
          FENCE();
#if SO
#pragma unroll
          for (int i = 1; i < 5; i++) m[i] = packh(S[i][0], T[i][2], S[i][1], T[i][3]);
          m[1] = tagw(m[1], tg);
          stg_r4(pw0, m[1], m[2], m[3], m[4]);
          FENCE();
          m[0] = tagw(packh(S[0][0], T[0][2], S[0][1], T[0][3]), tg);
          stg_r1(pw1, m[0]);
#else
#pragma unroll
          for (int i = 1; i < 5; i++) m[i] = pack_f16(S[i][0] + T[i][2], S[i][1] + T[i][3]);
          stg_r4(pw0, tagw(m[1], tg), m[2], m[3], m[4]);
          m[0] = pack_f16(S[0][0] + T[0][2], S[0][1] + T[0][3]);
          stg_r1(pw1, tagw(m[0], tg));
#endif
          TS(6); PT(11, s == 0 && l16 == 0);
          FENCE();
          const uint32_t ts = clk32();
          uint32_t te = gt32() + kd;
          const unsigned char* py0 = pr0 + 512 - l12; const unsigned char* py1 = pr1 + 512 - l12;
          OPAQUE_L(py0); OPAQUE_L(py1);
          unsigned char* pt = P.win + (w_ar(s) + (W_DS + 256) + (cta >> 5) * 8192 + ((cta >> 4) & 1) * 2048 + (l16 & 16u) * 256);
          OPAQUE_L(pt);
          if (l16 == 0) mbar_expect_tx(sb + SM_BAR + MB_F, s < NSEG - 2 ? 32768 : 0);
          FENCE();
          while (clk32() - ts < (uint32_t)DLY_S) {}
          {
            float sx[10]; uint32_t x, x1, x2, x3_; int n = 0; bool bad;
#pragma unroll 1
            do {
              uint4 v[3]; uint32_t y[3], t[5];
              v[0] = ldg_r4(pr0); v[1] = ldg_r4(pr1); v[2] = ldg_r4(pr1 + 2048);
              y[0] = ldg_r1(py0); y[1] = ldg_r1(py1); y[2] = ldg_r1(py1 + 2048);
              if (n) te = gt32() + DLY_KS;
              eta2(pt, te, n == 0, l16);
              n++;
              FENCE();
#define Q3(o, a, b, c) hadd2(hadd2(o, a), hadd2(b, c))
              t[1] = Q3(m[1], v[0].x, v[1].x, v[2].x); t[2] = Q3(m[2], v[0].y, v[1].y, v[2].y); t[3] = Q3(m[3], v[0].z, v[1].z, v[2].z); t[4] = Q3(m[4], v[0].w, v[1].w, v[2].w);
              t[0] = Q3(m[0], y[0], y[1], y[2]);
              bad = __any_sync(~0u, or3(x3(v[0].x, v[1].x, tg), x3(v[2].x, y[0], tg), x3(y[1], y[2], tg)) & (n < SPIN_LIMIT ? 1u : 0u));
              x = hmax2(hmax2(hmax2(t[1], t[2]), hmax2(t[3], t[4])), t[0]);
              const float2 xm = __half22float2(*reinterpret_cast<__half2*>(&x));
              x = f2u(fmaxf(xm.x, xm.y) * -sc);
              x1 = shfl_x(x, 1); x2 = shfl_x(x, 2); x3_ = shfl_x(x, 3);
              FENCE();
#if OS
#pragma unroll
              for (int i = 1; i < 6; i++) {
                h2f(sx[2 * (i % 5)], sx[2 * (i % 5) + 1], t[i % 5]);
                sx[2 * (i % 5)] = ex2v(sx[2 * (i % 5)], sc, u2f(x)); sx[2 * (i % 5) + 1] = ex2v(sx[2 * (i % 5) + 1], sc, u2f(x));
              }
              FENCE();
            } while (bad);
            const float cr = ex2(fminf(fminf(u2f(x), u2f(x1)), fminf(u2f(x2), u2f(x3_))) - u2f(x));
#pragma unroll
            for (int i = 1; i < 6; i++) m[i % 5] = pack_bf16(sx[2 * (i % 5)] * cr, sx[2 * (i % 5) + 1] * cr);
#else
#pragma unroll
              for (int i = 1; i < 6; i++) h2f(sx[2 * (i % 5)], sx[2 * (i % 5) + 1], t[i % 5]);
              FENCE();
            } while (bad);
            const float mx = fminf(fminf(u2f(x), u2f(x1)), fminf(u2f(x2), u2f(x3_)));
#pragma unroll
            for (int i = 2; i < 12; i++) sx[i % 10] = ex2v(sx[i % 10], sc, mx);
#pragma unroll
            for (int i = 1; i < 6; i++) m[i % 5] = pack_bf16(sx[2 * (i % 5)], sx[2 * (i % 5) + 1]);
#endif
            sts128(ls + SM_PF, m[1], m[2], m[3], m[4]);
            sts32(ls - l12 + SM_PF + 512, m[0]);
            TV(19, n - 1);
          }
          TS(12);
          bar_sync(B_P, 96);
          PT(12, s == 0 && l16 == 0);
          OPAQUE_R(l16);
          {
            const unsigned char* pe = P.win + w_blk(w_ar(s) + (W_DS + 256) + (l16 & 0x60u) * 256 + (l16 & 16u) * 128, me);
            const uint32_t tp = gt32() + DLY_M3;
            if (s < NSEG - 2) F0LOAD();
            ETAT(tp, 0);
            uint32_t tg0; int n = 0;
#pragma unroll 1
            for (;;) {
              const uint2 e = ldg_r2(pe);
              tg0 = __reduce_max_sync(~0u, e.y);
              if (tg0 - tp >= 4096u) tg0 = tp;
              if ((!__any_sync(~0u, e.x != 16u) && (int)(tg0 - gt32()) < DLY_RR) || ++n >= SPIN_LIMIT) break;
            }
            sts32(sb + SM_Z + 32, tg0);
            TV(16, tg0); TV(7, kd - DLY_K);
            bar_arrive(B_GO, 96);
          }
          if (s < NSEG - 2) {
            mbar_wait(sb + SM_BAR + MB_XE1, (s + 1) & 1);
            if (l16 == 0) mbar_expect_tx(sb + SM_BAR + MB_F + 8, 32768);
            mbar_wait(sb + SM_BAR + MB_MEM, (s + 1) & 1); mbar_wait(sb + SM_BAR + MB_MEM + 8, (s + 1) & 1);
            if (l16 == 0) XLOAD(1, s + 2);
            __syncwarp();
          }
          if (XPF && s + XPF < NSEG) {
            for (uint32_t i = xrank; i < 512; i += 32 * xcnt)
              asm volatile("prefetch.global.L2 [%0];" :: "l"(SP.x + (size_t)(s + XPF) * (SEG * DM) + i * 64));
            __syncwarp();
          }
          stg_2(P.win + (w_ar(s + 2) + cta * 256 + (l16 >> 8) * W_DS + ((l16 >> 1) & 127u)), 0u, 0u);
          kd = lds32(sb + SM_Z + 40) == (uint32_t)(s + 1) ? min(kd + KU, DLY_K + 256) : max(kd - KD, DLY_K);
          kd = __shfl_sync(~0u, kd, l16 >> 4);
#ifdef PER
          if (l16 == 0) { g_per[cta][s] = gt32(); g_pclk[cta][s] = clk32(); g_pk[cta][s] = kd - DLY_K; }
#endif
        }
        bar_sync(B_QK, 288);
      } else {
        const int mt = wq - 2;
        const uint32_t lt = ls + mt * 1024;
        const uint32_t vi0 = w_blk(w_mvx(h * 4, 0), me2) + mt * 1024;
        const int m3d = r ? -8192 : 8192;
#ifdef PROF
        const uint32_t epoch = gt32(); TST(-1, 30 + mt, l16, epoch);
#endif
        float ox[4][4], zx[4];
#pragma unroll
        for (int i = 0; i < 16; i++) ox[i >> 2][i & 3] = zx[i & 3] = 1.f;
        for (int s = 0;; s++) {
          const uint32_t tg = (s & 1) ^ 1, t2 = ((s >> 1) & 1) ^ 1;
          {
            OPAQUE_R(l16);
            const uint32_t m3i = (mt * 2 + r) * 8192 + (l16 & 0x70u) + ((l16 & 0x180u) << 1);
            const uint32_t m3j = (mt * 2 + (r ^ (l16 >> 7 & 1))) * 8192 + ((l16 & 64u) * 4 + (l16 & 48u) * 2 + (l16 & 16u)) * 16 + W_DS + (l16 & 0x70u);
            uint32_t m3c = sb + SM_MEM + mt * 8192 + cnt_line(l16 >> 4) * 128 + (l16 >> 2);
            const unsigned char* p3 = P.win + (m3i + w_ar(s - 1)); const unsigned char* pd = P.win + (m3j + w_ar(s - 1));
            OPAQUE_L(pd); OPAQUE_R(m3c);
#define XEPI() do {        \
              PVE(ox, zx, SM_OX + mt * 512); \
              __syncwarp(); \
              const uint32_t oa = sb + SM_OX + mt * 512 + ((l16 & 48u) << 3) + ((l16 >> 2) & 0x70u); \
              const uint4 a = lds128(oa), b = lds128(oa + 1024); \
              unsigned char* o = reinterpret_cast<unsigned char*>(g_ox + (size_t)((s - 1) * SEG + 8 * j) * (NH * DH) + h * DH + mt * 32) + ((l16 >> 6) * (NH * DH * 2) + (l16 & 48u)); \
              stg_4(o, a); stg_4(o + 128, b); \
              TST(s - 1, 18, l16 | mt, TCLK()); } while (0)
            if (s > 0) XEPI();
            if (s == NSEG) break;
            if (s > 0) {
              M3PTR(s - 1);
              bar_sync(B_GO, 96);
              const uint32_t tg0 = lds32(sb + SM_Z + 32);
              while (tg0 - gt32() - 1u < 8192u) {}
              M3REQ();
            }
            FENCE();
            const int n = m3_check(sb, p3, pd, m3d, l16, m3c, mt, s);
            FENCE();
            TST(s, mt ? 21 : 0, l16, TCLK());
            TST(s, mt ? 22 : 17, l16, n);
            PT(6 + s, s < 5 && (l16 | mt) == 0);
          }
          uint4 va[8], vm[2], p0, q0; uint32_t p2, q2;
          const unsigned char* a0 = P.win + (vi0 + ((s & 1) << 20) + l16);
#define VALD() _Pragma("unroll") for (int i = 0; i < 4; i++) { va[i] = ldg_r4(a0 + (i >> 1) * 512 + (i & 1) * 2048); va[4 + i] = ldg_r4(a0 + 16384 + (i >> 1) * 512 + (i & 1) * 2048); }
          spin(DLY_WO);
          VALD();
          {
          PTRS();
          bar_sync(B_V, 320);
            const float4 u0 = lds128f(lt + SM_VP), w0 = lds128f(lt + SM_VP + 2048), u1 = lds128f(lt + SM_VP + 512), w1 = lds128f(lt + SM_VP + 2560);
            const uint32_t m0 = tagw(pack_bf16(u0.x + w0.x, u0.y + w0.y), tg), m1 = pack_bf16(u0.z + w0.z, u0.w + w0.w),
                           m2 = pack_bf16(u1.x + w1.x, u1.y + w1.y), m3 = pack_bf16(u1.z + w1.z, u1.w + w1.w);
            stg_r4(pw0, m0, m1, m2, m3);
            if (wq == 2) TS(10);
            FENCE();
            const uint32_t tv = clk32();
            while (clk32() - tv < (uint32_t)DLY_V) {}
            uint4 v[3]; int n = 0; uint32_t bada = 0;
#pragma unroll 1
            do {
              v[0] = ldg_r4(pr0); v[1] = ldg_r4(pr1); v[2] = ldg_r4(pr1 + 2048);
              if (n) {
                TST(s, __any_sync(~0u, bada & 1u) ? 26 : 24, l16, epoch);
                if (__any_sync(~0u, bada & 1u)) { VALD(); }
                if (s < NSEG - 1) ETA(DLY_KS - 192, 0);
              }
              n++;
              FENCE();
              bada = or3(x3(va[0].x, va[1].x, t2), x3(va[2].x, va[3].x, t2), x3(va[4].x, va[5].x, t2)) | x3(va[6].x, va[7].x, t2);
            } while (__any_sync(~0u, or3(bada, x3(v[0].x, v[1].x, tg), v[2].x ^ tg) & 1u) && n < SPIN_LIMIT);
            const uint4 A = make_uint4(addb2(m0, v[0].x), addb2(m1, v[0].y), addb2(m2, v[0].z), addb2(m3, v[0].w));
            const uint4 B = make_uint4(addb2(v[1].x, v[2].x), addb2(v[1].y, v[2].y), addb2(v[1].z, v[2].z), addb2(v[1].w, v[2].w));
            vm[0] = p ? B : A; vm[1] = p ? A : B;
            TST(s, 11, l16 | mt, TCLK()); TST(s, 29, l16 | (mt ^ 1), TCLK());
          }
          FENCE();
          if (s < NSEG - 1) {
          bar_sync(B_P, 96);
          p0 = lds128(ls + SM_PF); p2 = lds32(ls - l12 + SM_PF + 512);
          float o[4][4], z[4];
          PVM(o, z, p0, p2, , , );
          PVE(o, z, SM_OF + mt * 512);
          bar_arrive(B_O, 192);
          }
          FENCE();
          TST(s, 8, l16 | mt, TCLK());
          bar_sync(B_PX, 96);
          q0 = lds128(ls + SM_PX); q2 = lds32(ls - l12 + SM_PX + 512);
#define O2A(k) if (O2P == k) { if (s < NSEG - 1) bar_arrive(B_O2, XG ? 224 : 192); FENCE(); }
          O2A(0);
          PVM(ox, zx, q0, q2, O2A(1), O2A(2), O2A(3));
          O2A(4);
          FENCE();
          if (s < NSEG - 1) bar_arrive(B_PXF, 96);
        }
      }
    }
  }
  asm volatile("barrier.cluster.arrive.relaxed.aligned;\nbarrier.cluster.wait.aligned;" ::: "memory");
#ifdef PER
  if (threadIdx.x == 0) atomicMax(&g_end[0], gt32());
#endif
}
#ifndef PW
#define PW 2
#endif
#ifndef G2_MC
#define G2_MC 1
#endif
#ifndef G2_UC
#define G2_UC 0
#endif
#ifndef G2_ST
#define G2_ST 6
#endif
#define G2_TB (G2_ST * 32768 + 1024)
#define G2_SMEM (G2_TB + 32768)
template <int AOFF, int BOFF>
static __device__ __forceinline__ void wgmma_n128_ta(float (&d)[64], uint32_t a16, uint32_t b16) {
  asm volatile(
      "{\n.reg .b32 t, u;\n.reg .b64 da, db;\nadd.u32 t, %64, %66;\nmov.b64 da, {t, %68};\nadd.u32 u, %65, %67;\nmov.b64 db, {u, %68};\n"
      "wgmma.mma_async.sync.aligned.m64n128k16.f32.bf16.bf16 "
      "{%0,%1,%2,%3,%4,%5,%6,%7,%8,%9,%10,%11,%12,%13,%14,%15,%16,%17,%18,%19,%20,%21,%22,%23,%24,%25,%26,%27,%28,%29,%30,%31,"
      "%32,%33,%34,%35,%36,%37,%38,%39,%40,%41,%42,%43,%44,%45,%46,%47,%48,%49,%50,%51,%52,%53,%54,%55,%56,%57,%58,%59,%60,%61,%62,%63}, "
      "da, db, 1, 1, 1, 1, 0;\n}"
      : "+f"(d[0]), "+f"(d[1]), "+f"(d[2]), "+f"(d[3]), "+f"(d[4]), "+f"(d[5]), "+f"(d[6]), "+f"(d[7]), "+f"(d[8]), "+f"(d[9]), "+f"(d[10]), "+f"(d[11]),
        "+f"(d[12]), "+f"(d[13]), "+f"(d[14]), "+f"(d[15]), "+f"(d[16]), "+f"(d[17]), "+f"(d[18]), "+f"(d[19]), "+f"(d[20]), "+f"(d[21]), "+f"(d[22]), "+f"(d[23]),
        "+f"(d[24]), "+f"(d[25]), "+f"(d[26]), "+f"(d[27]), "+f"(d[28]), "+f"(d[29]), "+f"(d[30]), "+f"(d[31]), "+f"(d[32]), "+f"(d[33]), "+f"(d[34]), "+f"(d[35]),
        "+f"(d[36]), "+f"(d[37]), "+f"(d[38]), "+f"(d[39]), "+f"(d[40]), "+f"(d[41]), "+f"(d[42]), "+f"(d[43]), "+f"(d[44]), "+f"(d[45]), "+f"(d[46]), "+f"(d[47]),
        "+f"(d[48]), "+f"(d[49]), "+f"(d[50]), "+f"(d[51]), "+f"(d[52]), "+f"(d[53]), "+f"(d[54]), "+f"(d[55]), "+f"(d[56]), "+f"(d[57]), "+f"(d[58]), "+f"(d[59]),
        "+f"(d[60]), "+f"(d[61]), "+f"(d[62]), "+f"(d[63])
      : "r"(a16), "r"(b16), "n"(AOFF >> 4), "n"(BOFF >> 4), "n"(DESC_HI(1024)));
}
__global__ void __cluster_dims__(G2_MC + 1, 1, 1) __launch_bounds__(384, 1)
gemm2_kernel(const __grid_constant__ CUtensorMap tmo, const __grid_constant__ CUtensorMap tmw, const bf16* __restrict__ x, bf16* __restrict__ out, unsigned char* win) {
  extern __shared__ __align__(1024) unsigned char smem[];
  const uint32_t sb = smem_u32(smem), bars = sb + G2_ST * 32768;
  const int tid = threadIdx.x, lane = tid & 31, warp = __shfl_sync(~0u, tid >> 5, 0);
  const int r = blockIdx.x & 1, n0 = (blockIdx.x & 7) * 128, m0 = (blockIdx.x >> 3) * 128;
  if (tid == 0) {
    for (int i = 0; i < G2_ST; i++) { mbar_init(bars + i * 8, 1); mbar_init(bars + 64 + i * 8, G2_MC ? 4 : 2); }
    asm volatile("fence.mbarrier_init.release.cluster;" ::: "memory");
  }
  if (tid == 32) { asm volatile("prefetch.tensormap [%0];" :: "l"(&tmw) : "memory"); asm volatile("prefetch.tensormap [%0];" :: "l"(&tmo) : "memory"); }
  __syncthreads();
  if (G2_MC) asm volatile("barrier.cluster.arrive.relaxed.aligned;" ::: "memory");
#define LW(kt, st) asm volatile("cp.async.bulk.tensor.3d.shared::cluster.global.mbarrier::complete_tx::bytes [%0], [%1, {%3, %4, %5}], [%2];" \
                     :: "r"(sb + (st) * 32768), "l"(&tmw), "r"(bars + (st) * 8), "r"(0), "r"((kt) * 64), "r"(n0 >> 6) : "memory")
#if G2_MC && !G2_UC
#define LO(kt, st) asm volatile("cp.async.bulk.tensor.2d.shared::cluster.global.mbarrier::complete_tx::bytes.multicast::cluster [%0], [%1, {%3, %4}], [%2], %5;" \
                     :: "r"(sb + (st) * 32768 + 16384 + r * 8192), "l"(&tmo), "r"(bars + (st) * 8), "r"((kt) * 64), "r"(m0 + r * 64), "h"((uint16_t)3) : "memory")
#else
#define LO(kt, st) tma_load_2d(sb + (st) * 32768 + 16384, &tmo, (kt) * 64, m0, bars + (st) * 8)
#endif
  if (tid == 256) for (int kt = 0; kt < G2_ST; kt++) { mbar_expect_tx(bars + kt * 8, 32768); if (kt < PW) LW(kt, kt); }
  __syncwarp();
  if (G2_MC) asm volatile("barrier.cluster.wait.acquire.aligned;" ::: "memory");
  if (warp == 8) {
    if (lane == 0) {
      asm volatile("griddepcontrol.wait;" ::: "memory");
      for (int kt = 0; kt < G2_ST; kt++) { LO(kt, kt); if (kt >= PW) LW(kt, kt); }
#pragma unroll 1
      for (int kt = G2_ST, st = 0, ph = 0; kt < 64; kt++) {
        mbar_wait(bars + 64 + st * 8, ph);
        mbar_expect_tx(bars + st * 8, 32768);
        LO(kt, st); LW(kt, st);
        if (++st == G2_ST) { st = 0; ph ^= 1; }
      }
    }
  } else if (warp > 8) {
    const int t = tid - 288, ch = t & 15;
    asm volatile("griddepcontrol.wait;" ::: "memory");
#ifdef PER
    if (t == 0) atomicMax(&g_end[3], gt32());
#endif
    int idx[8];
#pragma unroll
    for (int c = 0; c < 8; c++) idx[c] = g_idx[c];
    const int gi = blockIdx.x * 96 + t;
    if (gi < 67) g_side[gi * 32] = 0u;
    if (gi == 0) g_sbar = 0u;
#pragma unroll 4
    for (int row = t >> 4; row < 128; row += 6) {
      const int tok = m0 + row;
      const uint4 xv = *reinterpret_cast<const uint4*>(x + (size_t)tok * DM + n0 + ch * 8);
      const float g = g_gate[tok], omg = rbf(1.f - g);
      int sel = -1;
#pragma unroll
      for (int c = 0; c < 8; c++) if (idx[c] == tok) sel = c;
      uint4 uv = make_uint4(0u, 0u, 0u, 0u);
      if (sel >= 0) uv = *reinterpret_cast<const uint4*>(g_upd + sel * DM + n0 + ch * 8);
      const uint32_t x4[4] = {xv.x, xv.y, xv.z, xv.w}, u4[4] = {uv.x, uv.y, uv.z, uv.w};
      uint32_t o4[4];
#pragma unroll
      for (int e = 0; e < 4; e++) {
        const float b0 = rbf(u2f(x4[e] << 16) + u2f(u4[e] << 16)), b1 = rbf(u2f(x4[e] & 0xffff0000u) + u2f(u4[e] & 0xffff0000u));
        o4[e] = pack_bf16(omg * b0, omg * b1);
      }
      sts128(sb + G2_TB + row * 256 + ch * 16, o4[0], o4[1], o4[2], o4[3]);
      if (ch == 0) sts32(bars + 512 + row * 4, __float_as_uint(g));
    }
    bar_arrive(2, 352);
  } else {
    const int wg = warp >> 2;
    float d[64];
#pragma unroll
    for (int i = 0; i < 64; i++) d[i] = 0.f;
    const uint32_t e0 = mapa(bars + 64, 0), e1 = mapa(bars + 64, G2_MC);
#ifdef PER
    if (threadIdx.x == 0) { mbar_wait(bars, 0); atomicMax(&g_end[4], gt32()); }
    __syncwarp();
#endif
    const uint32_t a16 = (((sb + wg * 8192) & 0x3FFFF) >> 4) | (64u << 16), b16 = (((sb + 16384) & 0x3FFFF) >> 4) | (1u << 16);
#pragma unroll 1
    for (int kt = 0, st = 0, ph = 0, ps = -1; kt < 64; kt++) {
      mbar_wait(bars + st * 8, ph);
      wg_fence();
      wgmma_n128_ta<0, 0>(d, a16 + st * 2048, b16 + st * 2048); wgmma_n128_ta<2048, 32>(d, a16 + st * 2048, b16 + st * 2048);
      wgmma_n128_ta<4096, 64>(d, a16 + st * 2048, b16 + st * 2048); wgmma_n128_ta<6144, 96>(d, a16 + st * 2048, b16 + st * 2048);
      wg_commit();
      asm volatile("wgmma.wait_group.sync.aligned 1;" ::: "memory");
      if (ps >= 0 && (tid & 127) == 0) {
        if (G2_MC) { mbar_arrive_cluster_rlx(e0 + ps * 8); mbar_arrive_cluster_rlx(e1 + ps * 8); } else mbar_arrive(bars + 64 + ps * 8);
      }
      ps = st;
      if (++st == G2_ST) { st = 0; ph ^= 1; }
    }
    wg_wait0();
#ifdef PER
    if (threadIdx.x == 0) atomicMax(&g_end[5], gt32());
#endif
    bar_sync(1, 256);
#pragma unroll
    for (int jj = 0; jj < 8; jj++) {
      const uint32_t q0 = pack_bf16(d[8 * jj], d[8 * jj + 1]), q1 = pack_bf16(d[8 * jj + 2], d[8 * jj + 3]);
      const uint32_t q2 = pack_bf16(d[8 * jj + 4], d[8 * jj + 5]), q3 = pack_bf16(d[8 * jj + 6], d[8 * jj + 7]);
      stsm4t(sb + (jj * 16 + (lane >> 4) * 8 + (lane & 7)) * 272 + (warp * 16 + ((lane >> 3) & 1) * 8) * 2, q0, q1, q2, q3);
    }
    bar_sync(2, 352);
#pragma unroll
    for (int it = 0; it < 8; it++) {
      const int row = it * 16 + (tid >> 4), ch = tid & 15, tok = m0 + row;
      const uint4 av = lds128(sb + row * 272 + ch * 16), tv = lds128(sb + G2_TB + row * 256 + ch * 16);
      const float g = u2f(lds32(bars + 512 + row * 4));
      const uint32_t a4[4] = {av.x, av.y, av.z, av.w}, t4[4] = {tv.x, tv.y, tv.z, tv.w};
      uint32_t o4[4];
#pragma unroll
      for (int e = 0; e < 4; e++)
        o4[e] = pack_bf16(rbf(g * u2f(a4[e] << 16)) + u2f(t4[e] << 16), rbf(g * u2f(a4[e] & 0xffff0000u)) + u2f(t4[e] & 0xffff0000u));
      *reinterpret_cast<uint4*>(out + (size_t)tok * DM + n0 + ch * 8) = make_uint4(o4[0], o4[1], o4[2], o4[3]);
    }
  }
  if (G2_MC) asm volatile("barrier.cluster.arrive.relaxed.aligned;\nbarrier.cluster.wait.aligned;" ::: "memory");
#ifdef PER
  if (threadIdx.x == 0) atomicMax(&g_end[2], gt32());
#endif
}
#ifndef WPROM
#define WPROM CU_TENSOR_MAP_L2_PROMOTION_L2_128B
#endif
#ifndef G2_PROM
#define G2_PROM CU_TENSOR_MAP_L2_PROMOTION_L2_128B
#endif
#ifndef PDL
#define PDL 1
#endif
typedef CUresult (*PFN_encodeTiled)(CUtensorMap*, CUtensorMapDataType, cuuint32_t, void*, const cuuint64_t*, const cuuint64_t*,
                                    const cuuint32_t*, const cuuint32_t*, CUtensorMapInterleave, CUtensorMapSwizzle,
                                    CUtensorMapL2promotion, CUtensorMapFloatOOBfill);

extern "C" void kernel_launch(void* const* d_in, const int* in_sizes, int n_in, void* d_out, int out_size) {
  const bf16* x = (const bf16*)d_in[0];
  const bf16* mem0 = (const bf16*)d_in[1];
  const bf16* Wq = (const bf16*)d_in[2];
  const bf16* Wk = (const bf16*)d_in[3];
  const bf16* Wv = (const bf16*)d_in[4];
  const bf16* Wo = (const bf16*)d_in[5];
  const bf16* w_r = (const bf16*)d_in[8];
  const bf16* w_gate = (const bf16*)d_in[9];
  const bf16* w_up = (const bf16*)d_in[10];
  const bf16* w_down = (const bf16*)d_in[11];
  const bf16* gate_w = (const bf16*)d_in[12];
  bf16* out = (bf16*)d_out;

  static PFN_encodeTiled encode = nullptr;
  if (!encode) {
    void* fn = nullptr; cudaDriverEntryPointQueryResult st;
    cudaGetDriverEntryPoint("cuTensorMapEncodeTiled", &fn, cudaEnableDefault, &st);
    encode = (PFN_encodeTiled)fn;
    cudaFuncSetAttribute(rec_kernel, cudaFuncAttributeMaxDynamicSharedMemorySize, SM_TOTAL);
    cudaFuncSetAttribute(gemm2_kernel, cudaFuncAttributeMaxDynamicSharedMemorySize, G2_SMEM);
  }
  CUtensorMap tmx;
  {
    cuuint64_t gd[3] = {64, S_TOK, DM / 64};
    cuuint64_t gs[2] = {DM * 2, 128};
    cuuint32_t bx[3] = {64, SEG, 4};
    cuuint32_t es[3] = {1, 1, 1};
    encode(&tmx, CU_TENSOR_MAP_DATA_TYPE_BFLOAT16, 3, (void*)x, gd, gs, bx, es, CU_TENSOR_MAP_INTERLEAVE_NONE,
           CU_TENSOR_MAP_SWIZZLE_128B, CU_TENSOR_MAP_L2_PROMOTION_L2_128B, CU_TENSOR_MAP_FLOAT_OOB_FILL_NONE);
  }
  bf16* ox;
  cudaGetSymbolAddress((void**)&ox, g_ox);
  CUtensorMap tmo, tmw, tmw3;
  {
    cuuint64_t gd[2] = {NH * DH, S_TOK}; cuuint64_t gs[1] = {NH * DH * 2}; cuuint32_t bx[2] = {64, G2_MC && !G2_UC ? 64 : 128}; cuuint32_t es[3] = {1, 1, 1};
    encode(&tmo, CU_TENSOR_MAP_DATA_TYPE_BFLOAT16, 2, (void*)ox, gd, gs, bx, es, CU_TENSOR_MAP_INTERLEAVE_NONE,
           CU_TENSOR_MAP_SWIZZLE_128B, CU_TENSOR_MAP_L2_PROMOTION_L2_128B, CU_TENSOR_MAP_FLOAT_OOB_FILL_NONE);
    cuuint64_t gd2[2] = {DM, NH * DH}; cuuint64_t gs2[1] = {DM * 2}; cuuint32_t bx2[2] = {64, 64};
    encode(&tmw, CU_TENSOR_MAP_DATA_TYPE_BFLOAT16, 2, (void*)Wo, gd2, gs2, bx2, es, CU_TENSOR_MAP_INTERLEAVE_NONE,
           CU_TENSOR_MAP_SWIZZLE_128B, CU_TENSOR_MAP_L2_PROMOTION_L2_128B, CU_TENSOR_MAP_FLOAT_OOB_FILL_NONE);
  }
  {
    cuuint64_t gd[3] = {64, NH * DH, DM / 64}; cuuint64_t gs[2] = {DM * 2, 128}; cuuint32_t bx[3] = {64, 64, 2}; cuuint32_t es[3] = {1, 1, 1};
    encode(&tmw3, CU_TENSOR_MAP_DATA_TYPE_BFLOAT16, 3, (void*)Wo, gd, gs, bx, es, CU_TENSOR_MAP_INTERLEAVE_NONE,
           CU_TENSOR_MAP_SWIZZLE_128B, G2_PROM, CU_TENSOR_MAP_FLOAT_OOB_FILL_NONE);
  }
  unsigned char* win;
  cudaGetSymbolAddress((void**)&win, g_win);
  win = (unsigned char*)(((uintptr_t)win + (2u << 20) - 1) & ~(uintptr_t)((2u << 20) - 1));
  WMaps W;
  {
    cuuint64_t gd[2] = {NH * DH, DM}; cuuint64_t gs[1] = {NH * DH * 2}; cuuint32_t b32[2] = {32, 128}, b64[2] = {64, 128}; cuuint32_t es[2] = {1, 1};
    encode(&W.q, CU_TENSOR_MAP_DATA_TYPE_BFLOAT16, 2, (void*)Wq, gd, gs, b32, es, CU_TENSOR_MAP_INTERLEAVE_NONE,
           CU_TENSOR_MAP_SWIZZLE_64B, WPROM, CU_TENSOR_MAP_FLOAT_OOB_FILL_NONE);
    encode(&W.k, CU_TENSOR_MAP_DATA_TYPE_BFLOAT16, 2, (void*)Wk, gd, gs, b32, es, CU_TENSOR_MAP_INTERLEAVE_NONE,
           CU_TENSOR_MAP_SWIZZLE_64B, WPROM, CU_TENSOR_MAP_FLOAT_OOB_FILL_NONE);
    encode(&W.v, CU_TENSOR_MAP_DATA_TYPE_BFLOAT16, 2, (void*)Wv, gd, gs, b64, es, CU_TENSOR_MAP_INTERLEAVE_NONE,
           CU_TENSOR_MAP_SWIZZLE_128B, WPROM, CU_TENSOR_MAP_FLOAT_OOB_FILL_NONE);
  }
  RecParams P{mem0, win};
  SideParams SP{x, w_r, w_gate, w_up, w_down, gate_w, Wo};
  rec_kernel<<<NCTA + 4, 384, SM_TOTAL, cudaStreamPerThread>>>(tmx, tmw, W, P, SP);
  {
    cudaLaunchConfig_t cfg = {};
    cfg.gridDim = dim3(NCTA); cfg.blockDim = dim3(384); cfg.dynamicSmemBytes = G2_SMEM; cfg.stream = cudaStreamPerThread;
    cudaLaunchAttribute at[1];
    at[0].id = cudaLaunchAttributeProgrammaticStreamSerialization; at[0].val.programmaticStreamSerializationAllowed = 1;
    cfg.attrs = at; cfg.numAttrs = PDL;
    cudaLaunchKernelEx(&cfg, gemm2_kernel, tmo, tmw3, x, out, win);
  }
}
```

```cpp
#include <cuda_runtime.h>
#include <cuda_bf16.h>
#include <cuda_fp16.h>
#include <cuda.h>
#include <stdint.h>

typedef __nv_bfloat16 bf16;

#define S_TOK 2048
#define DM 1024
#define NH 32
#define DH 128
#define SEG 32
#define NSEG 64
#define FF 3584
#define NCTA 128

static __device__ bf16 g_ox[(size_t)S_TOK * NH * DH];
static __device__ float g_gate[S_TOK];
static __device__ float g_r[S_TOK];
static __device__ int g_idx[8];
static __device__ bf16 g_upd[8 * DM];

static __device__ __forceinline__ float rbf(float v) { return __bfloat162float(__float2bfloat16(v)); }
static __device__ __forceinline__ uint32_t smem_u32(const void* p) { return (uint32_t)__cvta_generic_to_shared(p); }
static __device__ __forceinline__ uint32_t pack_bf16(float lo, float hi) {
  __nv_bfloat162 v = __floats2bfloat162_rn(lo, hi);
  return *reinterpret_cast<uint32_t*>(&v);
}

static __device__ __forceinline__ void wg_fence() { asm volatile("wgmma.fence.sync.aligned;" ::: "memory"); }
static __device__ __forceinline__ void wg_commit() { asm volatile("wgmma.commit_group.sync.aligned;" ::: "memory"); }
static __device__ __forceinline__ void wg_wait0() { asm volatile("wgmma.wait_group.sync.aligned 0;" ::: "memory"); }
static __device__ __forceinline__ void fence_async_smem() { asm volatile("fence.proxy.async.shared::cta;" ::: "memory"); }

static __device__ __forceinline__ uint64_t make_desc(uint32_t addr, uint32_t lbo, uint32_t sbo) {
  uint64_t d = 0;
  d |= (uint64_t)((addr & 0x3FFFF) >> 4);
  d |= (uint64_t)((lbo >> 4) & 0x3FFF) << 16;
  d |= (uint64_t)((sbo >> 4) & 0x3FFF) << 32;
  d |= (uint64_t)1 << 62;
  return d;
}

#define DESC_HI(sbo) (((sbo) >> 4) | (1u << 30))
template <int OFF, int SCALE>
static __device__ __forceinline__ void wgmma_n32_ra(float (&d)[16], const uint32_t (&a)[4], uint32_t base16) {
  asm volatile(
      "{\n.reg .b32 t;\n.reg .b64 dd;\nadd.u32 t, %20, %21;\nmov.b64 dd, {t, %22};\n"
      "wgmma.mma_async.sync.aligned.m64n32k16.f32.bf16.bf16 "
      "{%0,%1,%2,%3,%4,%5,%6,%7,%8,%9,%10,%11,%12,%13,%14,%15}, {%16,%17,%18,%19}, dd, %23, 1, 1, 0;\n}"
      : "+f"(d[0]), "+f"(d[1]), "+f"(d[2]), "+f"(d[3]), "+f"(d[4]), "+f"(d[5]), "+f"(d[6]), "+f"(d[7]),
        "+f"(d[8]), "+f"(d[9]), "+f"(d[10]), "+f"(d[11]), "+f"(d[12]), "+f"(d[13]), "+f"(d[14]), "+f"(d[15])
      : "r"(a[0]), "r"(a[1]), "r"(a[2]), "r"(a[3]), "r"(base16), "n"(OFF >> 4), "n"(DESC_HI(1024)), "n"(SCALE));
}
template <int AOFF, int BOFF, int SCALE>
static __device__ __forceinline__ void wgmma_n32_ss_ta(float (&d)[16], uint32_t abase16, uint32_t bbase16) {
  asm volatile(
      "{\n.reg .b32 t, u;\n.reg .b64 da, db;\nadd.u32 t, %16, %18;\nmov.b64 da, {t, %20};\nadd.u32 u, %17, %19;\nmov.b64 db, {u, %20};\n"
      "wgmma.mma_async.sync.aligned.m64n32k16.f32.bf16.bf16 "
      "{%0,%1,%2,%3,%4,%5,%6,%7,%8,%9,%10,%11,%12,%13,%14,%15}, da, db, %21, 1, 1, 1, 0;\n}"
      : "+f"(d[0]), "+f"(d[1]), "+f"(d[2]), "+f"(d[3]), "+f"(d[4]), "+f"(d[5]), "+f"(d[6]), "+f"(d[7]),
        "+f"(d[8]), "+f"(d[9]), "+f"(d[10]), "+f"(d[11]), "+f"(d[12]), "+f"(d[13]), "+f"(d[14]), "+f"(d[15])
      : "r"(abase16), "r"(bbase16), "n"(AOFF >> 4), "n"(BOFF >> 4), "n"(DESC_HI(1024)), "n"(SCALE));
}
static __device__ __forceinline__ void ldmatrix_x4_trans(uint32_t (&r)[4], uint32_t addr) {
  asm volatile("ldmatrix.sync.aligned.m8n8.x4.trans.shared.b16 {%0,%1,%2,%3}, [%4];"
               : "=r"(r[0]), "=r"(r[1]), "=r"(r[2]), "=r"(r[3]) : "r"(addr) : "memory");
}
static __device__ __forceinline__ void mma_16816(float (&d)[4], const uint32_t (&a)[4], uint32_t b0, uint32_t b1) {
  asm volatile("mma.sync.aligned.m16n8k16.row.col.f32.bf16.bf16.f32 {%0,%1,%2,%3}, {%4,%5,%6,%7}, {%8,%9}, {%0,%1,%2,%3};"
               : "+f"(d[0]), "+f"(d[1]), "+f"(d[2]), "+f"(d[3])
               : "r"(a[0]), "r"(a[1]), "r"(a[2]), "r"(a[3]), "r"(b0), "r"(b1));
}

static __device__ __forceinline__ uint32_t mapa(uint32_t addr, uint32_t rank) {
  uint32_t r; asm volatile("mapa.shared::cluster.u32 %0, %1, %2;" : "=r"(r) : "r"(addr), "r"(rank)); return r;
}

static __device__ __forceinline__ void mbar_init(uint32_t bar, int cnt) {
  asm volatile("mbarrier.init.shared::cta.b64 [%0], %1;" :: "r"(bar), "r"(cnt) : "memory");
}
static __device__ __forceinline__ void mbar_expect_tx(uint32_t bar, uint32_t bytes) {
  asm volatile("mbarrier.arrive.expect_tx.shared::cta.b64 _, [%0], %1;" :: "r"(bar), "r"(bytes) : "memory");
}
static __device__ __forceinline__ void tma_load_2d(uint32_t dst, const CUtensorMap* tm, int c0, int c1, uint32_t bar) {
  asm volatile("cp.async.bulk.tensor.2d.shared::cluster.global.mbarrier::complete_tx::bytes [%0], [%1, {%3, %4}], [%2];"
               :: "r"(dst), "l"(tm), "r"(bar), "r"(c0), "r"(c1) : "memory");
}

static __device__ unsigned char g_win[6 << 20];
static __device__ unsigned int g_side[67 * 32];
static __device__ unsigned int g_err;
#define W_UP (1u << 20)
#define W_2 (2u << 20)
static __device__ __forceinline__ uint32_t w_blk(uint32_t off, uint32_t side) { return off | (((__popc((off >> 12) & 0xb3u) ^ side) & 1u) << 12); }
static __device__ __forceinline__ uint32_t w_h1(int c) { return W_UP | (1u << 13) | ((c >> 1) << 14) | ((c & 1) << 11); }
#define W_DS 0x30000u
static __device__ __forceinline__ uint32_t w_ar(int s) { return ((s & 1) << 15) | ((s & 2) << 17); }
static __device__ __forceinline__ uint32_t w_mvx(int c, int s) { return W_2 | ((s & 1) << 20) | ((c >> 1) << 14) | ((c & 1) << 11); }
static __device__ __forceinline__ uint32_t w_mxa(int c, int s) { return W_2 | ((s & 1) << 20) | (1u << 13) | ((c >> 1) << 14) | ((c & 1) << 11); }
#define H1_V (1u << 13)

#define SPIN_LIMIT (1 << 18)

#define SM_X 0
#define SM_WOS 65536
#define SM_WVS 131072
#define SM_MEM 163840
#define SM_QKP 180224
#define SM_VP 184320
#define SM_CW 188416
#define SM_VST 196608
#define SM_VR 196608
#define SM_CQ 200704
#define SM_CV 208896
#define SM_XF 217088
#define SM_VL 221184
#define SM_OF 225280
#define SM_OX 227328
#define SM_PF 229376
#define SM_PX 230016
#define SM_RD 198656
#define SM_QA 230656
#define SM_XS 231168
#define SM_BAR 231808
#define SM_Z 231936
#define SM_TOTAL 232128
#define MB_F 0
#define MB_XE0 16
#define MB_XE1 112
#define MB_INIT 24
#define MB_MEM 32
#define MB_W 256
#define MB_XF 64
#define MB_VR 72
#define MB_X0 80
#define MB_WO 88
#define SM_SIDE (SM_BAR + 96)
#define B_QK 1
#define B_V 2
#define B_P 3
#define B_O 4
#define B_O2 5
#define B_PUB 6
#define B_CQ 7
#define B_QK1 8
#define B_PXF 10
#define B_CV 15
#define B_X2 11
#define B_PX 12
#define B_GO 14
#define B_G1 13

#ifdef PROF
__device__ unsigned int g_ts[NCTA][80][32];
#ifdef GT
#define TCLK() gt32()
#else
#define TCLK() clk32()
#endif
#ifndef TMASK
#define TMASK 0xffffffffu
#endif
#define TST(st, i, c, v) do { if ((TMASK >> (i)) & 1u) asm volatile("{\n.reg .pred q;\nsetp.eq.u32 q, %2, 0;\n@q st.global.u32 [%0], %1;\n}" :: "l"(&g_ts[cta][(st) + 1][i]), "r"((uint32_t)(v)), "r"((uint32_t)(c)) : "memory"); } while (0)
#define TS(i) TST(s, i, l16, TCLK())
#define TV(i, v) TST(s, i, l16, v)
#define TSF(i, w) TST(s, i, l16 | (w8 ^ (w)), TCLK())
#define TSP(i, w) TST(s - 1, i, l16 | (w8 ^ (w)), TCLK())
#define TVF(i, v) TV(i, v)
#else
#define TST(a, b, c, d)
#define TSF(i, w)
#define TSP(i, w)
#define TVF(i, v)
#define TS(i)
#define TV(i, v)
#endif

static __device__ __forceinline__ void bar_sync(int id, int n) { asm volatile("bar.sync %0, %1;" :: "r"(id), "r"(n) : "memory"); }
static __device__ __forceinline__ void bar_arrive(int id, int n) { asm volatile("bar.arrive %0, %1;" :: "r"(id), "r"(n) : "memory"); }
static __device__ __forceinline__ uint4 ldg_r4(const void* p) { uint4 v;
  asm volatile("ld.relaxed.gpu.global.v4.u32 {%0,%1,%2,%3}, [%4];" : "=r"(v.x), "=r"(v.y), "=r"(v.z), "=r"(v.w) : "l"(p) : "memory"); return v; }
static __device__ __forceinline__ uint32_t ldg_r1(const void* p) { uint32_t v;
  asm volatile("ld.relaxed.gpu.global.u32 %0, [%1];" : "=r"(v) : "l"(p) : "memory"); return v; }
static __device__ __forceinline__ void stg_r4(void* p, uint32_t a, uint32_t b, uint32_t c, uint32_t d) {
  asm volatile("st.relaxed.gpu.global.v4.u32 [%0], {%1,%2,%3,%4};" :: "l"(p), "r"(a), "r"(b), "r"(c), "r"(d) : "memory"); }
static __device__ __forceinline__ uint2 ldg_r2(const void* p) { uint2 v;
  asm volatile("ld.relaxed.gpu.global.v2.u32 {%0,%1}, [%2];" : "=r"(v.x), "=r"(v.y) : "l"(p) : "memory"); return v; }
static __device__ __forceinline__ void stg_4(void* p, const uint4& v) {
  asm volatile("st.global.v4.u32 [%0], {%1,%2,%3,%4};" :: "l"(p), "r"(v.x), "r"(v.y), "r"(v.z), "r"(v.w) : "memory"); }
static __device__ __forceinline__ uint32_t f2u(float v) { return __float_as_uint(v); }
static __device__ __forceinline__ void stg_2(void* p, uint32_t a, uint32_t b) {
  asm volatile("st.global.v2.u32 [%0], {%1,%2};" :: "l"(p), "r"(a), "r"(b) : "memory"); }
static __device__ __forceinline__ void stg_r1(void* p, uint32_t a) {
  asm volatile("st.relaxed.gpu.global.u32 [%0], %1;" :: "l"(p), "r"(a) : "memory"); }
static __device__ __forceinline__ void sts128(uint32_t a, uint32_t x, uint32_t y, uint32_t z, uint32_t w) {
  asm volatile("st.shared.v4.u32 [%0], {%1,%2,%3,%4};" :: "r"(a), "r"(x), "r"(y), "r"(z), "r"(w) : "memory"); }
static __device__ __forceinline__ void sts128f(uint32_t a, float x, float y, float z, float w) {
  asm volatile("st.shared.v4.f32 [%0], {%1,%2,%3,%4};" :: "r"(a), "f"(x), "f"(y), "f"(z), "f"(w) : "memory"); }
static __device__ __forceinline__ uint4 lds128(uint32_t a) { uint4 v;
  asm volatile("ld.shared.v4.u32 {%0,%1,%2,%3}, [%4];" : "=r"(v.x), "=r"(v.y), "=r"(v.z), "=r"(v.w) : "r"(a) : "memory"); return v; }
static __device__ __forceinline__ float4 lds128f(uint32_t a) { float4 v;
  asm volatile("ld.shared.v4.f32 {%0,%1,%2,%3}, [%4];" : "=f"(v.x), "=f"(v.y), "=f"(v.z), "=f"(v.w) : "r"(a) : "memory"); return v; }
static __device__ __forceinline__ void sts32(uint32_t a, uint32_t x) { asm volatile("st.shared.u32 [%0], %1;" :: "r"(a), "r"(x) : "memory"); }
static __device__ __forceinline__ uint2 lds64(uint32_t a) { uint2 v;
  asm volatile("ld.shared.v2.u32 {%0,%1}, [%2];" : "=r"(v.x), "=r"(v.y) : "r"(a) : "memory"); return v; }
static __device__ __forceinline__ void st_async4(uint32_t ra, float x, float y, float z, float w, uint32_t rbar) {
  asm volatile("st.async.weak.shared::cluster.mbarrier::complete_tx::bytes.v4.f32 [%0], {%1,%2,%3,%4}, [%5];"
               :: "r"(ra), "f"(x), "f"(y), "f"(z), "f"(w), "r"(rbar) : "memory"); }
static __device__ __forceinline__ void stsm4t(uint32_t a, uint32_t x, uint32_t y, uint32_t z, uint32_t w) {
  asm volatile("stmatrix.sync.aligned.m8n8.x4.trans.shared.b16 [%0], {%1,%2,%3,%4};" :: "r"(a), "r"(x), "r"(y), "r"(z), "r"(w) : "memory"); }
static __device__ __forceinline__ uint32_t hmax2(uint32_t a, uint32_t b) { uint32_t d;
  asm("max.f16x2 %0, %1, %2;" : "=r"(d) : "r"(a), "r"(b)); return d; }
static __device__ __forceinline__ uint32_t hadd2(uint32_t a, uint32_t b) { uint32_t d;
  asm("add.rn.f16x2 %0, %1, %2;" : "=r"(d) : "r"(a), "r"(b)); return d; }
static __device__ __forceinline__ uint32_t packv(float a, float b, float c, float d) { uint32_t r;
  asm volatile("{\n.reg .f32 x, y;\nadd.f32 x, %1, %2;\nadd.f32 y, %3, %4;\ncvt.rn.bf16x2.f32 %0, y, x;\n}" : "=r"(r) : "f"(a), "f"(b), "f"(c), "f"(d)); return r; }
static __device__ __forceinline__ uint32_t packh(float a, float b, float c, float d) { uint32_t r;
  asm volatile("{\n.reg .f32 x, y;\nadd.f32 x, %1, %2;\nadd.f32 y, %3, %4;\ncvt.rn.satfinite.f16x2.f32 %0, y, x;\n}" : "=r"(r) : "f"(a), "f"(b), "f"(c), "f"(d)); return r; }
static __device__ __forceinline__ float ex2v(float a, float b, float c) { float y;
  asm volatile("{\n.reg .f32 x;\nfma.rn.f32 x, %1, %2, %3;\nex2.approx.ftz.f32 %0, x;\n}" : "=f"(y) : "f"(a), "f"(b), "f"(c)); return y; }
static __device__ __forceinline__ uint32_t shfl_x(uint32_t a, int m) { uint32_t d;
  asm volatile("shfl.sync.bfly.b32 %0, %1, %2, 0x1f, 0xffffffff;" : "=r"(d) : "r"(a), "r"(m)); return d; }
static __device__ __forceinline__ void h2f(float& lo, float& hi, uint32_t a) {
  asm volatile("{\n.reg .b16 l, h;\nmov.b32 {l, h}, %2;\ncvt.f32.f16 %0, l;\ncvt.f32.f16 %1, h;\n}" : "=f"(lo), "=f"(hi) : "r"(a)); }
static __device__ __forceinline__ uint4 ldsm4(uint32_t a) { uint4 v;
  asm volatile("ldmatrix.sync.aligned.m8n8.x4.shared.b16 {%0,%1,%2,%3}, [%4];" : "=r"(v.x), "=r"(v.y), "=r"(v.z), "=r"(v.w) : "r"(a) : "memory"); return v; }
static __device__ __forceinline__ uint4 ldsm4t(uint32_t a) { uint4 v;
  asm volatile("ldmatrix.sync.aligned.m8n8.x4.trans.shared.b16 {%0,%1,%2,%3}, [%4];" : "=r"(v.x), "=r"(v.y), "=r"(v.z), "=r"(v.w) : "r"(a) : "memory"); return v; }
static __device__ __forceinline__ uint32_t movm(uint32_t a) { uint32_t d;
  asm volatile("movmatrix.sync.aligned.m8n8.trans.b16 %0, %1;" : "=r"(d) : "r"(a)); return d; }
static __device__ __forceinline__ float u2f(uint32_t v) { return __uint_as_float(v); }
static __device__ __forceinline__ uint32_t tagw(uint32_t w, uint32_t t) { uint32_t d;
  asm("lop3.b32 %0, %1, %2, 1, 0xd8;" : "=r"(d) : "r"(w), "r"(t)); return d; }
static __device__ __forceinline__ uint32_t pack_f16(float lo, float hi) { uint32_t d;
  asm("cvt.rn.satfinite.f16x2.f32 %0, %1, %2;" : "=r"(d) : "f"(hi), "f"(lo)); return d; }
static __device__ __forceinline__ void sum_h4(float& lo, float& hi, uint32_t a, uint32_t b, uint32_t c, uint32_t d) {
  const float2 x = __half22float2(*reinterpret_cast<__half2*>(&a)), y = __half22float2(*reinterpret_cast<__half2*>(&b));
  const float2 z = __half22float2(*reinterpret_cast<__half2*>(&c)), w = __half22float2(*reinterpret_cast<__half2*>(&d));
  lo = (x.x + y.x) + (z.x + w.x); hi = (x.y + y.y) + (z.y + w.y);
}
static __device__ __forceinline__ uint32_t lds32(uint32_t a) { uint32_t v; asm volatile("ld.shared.u32 %0, [%1];" : "=r"(v) : "r"(a) : "memory"); return v; }
static __device__ __forceinline__ uint32_t addb2(uint32_t a, uint32_t b) { uint32_t d;
  asm("add.rn.bf16x2 %0, %1, %2;" : "=r"(d) : "r"(a), "r"(b)); return d; }
static __device__ __forceinline__ uint32_t mulb2(uint32_t a, uint32_t b) { uint32_t d;
  asm("mul.rn.bf16x2 %0, %1, %2;" : "=r"(d) : "r"(a), "r"(b)); return d; }
static __device__ __forceinline__ uint32_t mulb2v(uint32_t a, uint32_t b) { uint32_t d;
  asm volatile("mul.rn.bf16x2 %0, %1, %2;" : "=r"(d) : "r"(a), "r"(b)); return d; }
static __device__ __forceinline__ uint32_t x3(uint32_t a, uint32_t b, uint32_t t) { uint32_t d;
  asm("lop3.b32 %0, %1, %2, %3, 0x7e;" : "=r"(d) : "r"(a), "r"(b), "r"(t)); return d; }
static __device__ __forceinline__ uint32_t or3(uint32_t a, uint32_t b, uint32_t c) { uint32_t d;
  asm("lop3.b32 %0, %1, %2, %3, 0xfe;" : "=r"(d) : "r"(a), "r"(b), "r"(c)); return d; }
static __device__ __forceinline__ float ex2(float x) { float y; asm("ex2.approx.ftz.f32 %0, %1;" : "=f"(y) : "f"(x)); return y; }
static __device__ __forceinline__ float rcpf(float x) { float y; asm("rcp.approx.ftz.f32 %0, %1;" : "=f"(y) : "f"(x)); return y; }
static __device__ __forceinline__ void mbar_wait(uint32_t bar, int parity) {
  asm volatile("{\n.reg .pred p, q;\n.reg .u32 n;\nmbarrier.try_wait.parity.shared::cta.b64 p, [%0], %1;\n@p bra W_DONE;\nmov.u32 n, 0;\n"
               "W_LOOP:\nmbarrier.try_wait.parity.shared::cta.b64 p, [%0], %1;\nadd.u32 n, n, 1;\nsetp.lt.and.u32 q, n, %2, !p;\n@q bra W_LOOP;\nW_DONE:\n}"
               :: "r"(bar), "r"(parity), "n"(SPIN_LIMIT) : "memory");
}
static __device__ __forceinline__ uint32_t mbar_test(uint32_t bar, int parity) { uint32_t ok;
  asm volatile("{\n.reg .pred p;\nmbarrier.test_wait.parity.shared::cta.b64 p, [%1], %2;\nselp.u32 %0, 1, 0, p;\n}" : "=r"(ok) : "r"(bar), "r"(parity) : "memory"); return ok; }
static __device__ __forceinline__ void mbar_arrive(uint32_t bar) {
  asm volatile("mbarrier.arrive.shared::cta.b64 _, [%0];" :: "r"(bar) : "memory"); }
static __device__ __forceinline__ void mbar_arrive_cluster_rlx(uint32_t raddr) {
  asm volatile("mbarrier.arrive.relaxed.cluster.shared::cluster.b64 _, [%0];" :: "r"(raddr) : "memory"); }
static __device__ __forceinline__ void tma_load_mc(uint32_t dst, const CUtensorMap* tm, int c1, int c2, uint32_t bar) {
#ifdef NOTMA
  if ((NOTMA >> (c2 >> 3)) & 1) asm volatile("mbarrier.complete_tx.relaxed.cta.shared::cta.b64 [%0], 32768;" :: "r"(bar) : "memory"); else
#endif
  asm volatile("cp.async.bulk.tensor.3d.shared::cluster.global.mbarrier::complete_tx::bytes.multicast::cluster [%0], [%1, {%3, %4, %5}], [%2], %6;"
               :: "r"(dst), "l"(tm), "r"(bar), "r"(0), "r"(c1), "r"(c2), "h"((uint16_t)3) : "memory"); }
static __device__ __forceinline__ void cp16(uint32_t dst, const void* src) {
  asm volatile("cp.async.cg.shared.global [%0], [%1], 16;" :: "r"(dst), "l"(src) : "memory"); }
static __device__ __forceinline__ void mma_1688(float (&d)[4], uint32_t a0, uint32_t a1, uint32_t b0) {
  asm volatile("mma.sync.aligned.m16n8k8.row.col.f32.bf16.bf16.f32 {%0,%1,%2,%3}, {%4,%5}, {%6}, {%0,%1,%2,%3};"
               : "+f"(d[0]), "+f"(d[1]), "+f"(d[2]), "+f"(d[3]) : "r"(a0), "r"(a1), "r"(b0)); }
static __device__ __forceinline__ void mma4(float (&d)[4], uint32_t a0, uint32_t a1, uint32_t a2, uint32_t a3, uint32_t b0, uint32_t b1) {
  asm volatile("mma.sync.aligned.m16n8k16.row.col.f32.bf16.bf16.f32 {%0,%1,%2,%3}, {%4,%5,%6,%7}, {%8,%9}, {%0,%1,%2,%3};"
               : "+f"(d[0]), "+f"(d[1]), "+f"(d[2]), "+f"(d[3]) : "r"(a0), "r"(a1), "r"(a2), "r"(a3), "r"(b0), "r"(b1)); }
static __device__ __forceinline__ void mma4z(float (&d)[4], uint32_t a0, uint32_t a1, uint32_t a2, uint32_t a3, uint32_t b0, uint32_t b1) {
  asm volatile("mma.sync.aligned.m16n8k16.row.col.f32.bf16.bf16.f32 {%0,%1,%2,%3}, {%4,%5,%6,%7}, {%8,%9}, {%10,%10,%10,%10};"
               : "=f"(d[0]), "=f"(d[1]), "=f"(d[2]), "=f"(d[3]) : "r"(a0), "r"(a1), "r"(a2), "r"(a3), "r"(b0), "r"(b1), "f"(0.f)); }
static __device__ __forceinline__ uint32_t clk32() { uint32_t t; asm volatile("mov.u32 %0, %%clock;" : "=r"(t)); return t; }
static __device__ __forceinline__ uint32_t gt32() { uint32_t t; asm volatile("mov.u32 %0, %%globaltimer_lo;" : "=r"(t)); return t; }
static __device__ __forceinline__ void spin(int clk) { if (clk > 0) { uint32_t t = clk32(); while (clk32() - t < (uint32_t)clk) {} } }
static __device__ __forceinline__ void spinv(int clk, uint32_t z) { const uint32_t t = clk32() + (z >> 31); while (clk32() - t < (uint32_t)clk) {} }
#define FENCE() asm volatile("griddepcontrol.launch_dependents;" ::: "memory")
#define OPAQUE_L(p) asm volatile("" : "+l"(p))
#define OPAQUE_R(p) asm volatile("" : "+r"(p))

template <int KK, int K1, int W0, int NW, int FIRST> struct XR {
  static __device__ __forceinline__ void run(float (&d)[16], const uint32_t (&w)[NW][4], uint32_t b16) {
#ifdef NOWG
    if (KK % NOWG == 0)
#endif
    wgmma_n32_ra<(KK >> 2) * 4096 + (KK & 3) * 32, !FIRST>(d, w[W0 + KK], b16);
    XR<KK + 1, K1, W0, NW, 0>::run(d, w, b16);
  }
};
template <int K1, int W0, int NW, int FIRST> struct XR<K1, K1, W0, NW, FIRST> { static __device__ __forceinline__ void run(float (&)[16], const uint32_t (&)[NW][4], uint32_t) {} };
template <int KK, int K0, int K1, int FIRST> struct XS {
  static __device__ __forceinline__ void run(float (&d)[16], uint32_t a16, uint32_t b16) {
#ifdef NOWG
    if (KK % NOWG == 0)
#endif
    wgmma_n32_ss_ta<(KK - K0) * 2048, (KK >> 2) * 4096 + (KK & 3) * 32, !FIRST>(d, a16, b16);
    XS<KK + 1, K0, K1, 0>::run(d, a16, b16);
  }
};
template <int K0, int K1, int FIRST> struct XS<K1, K0, K1, FIRST> { static __device__ __forceinline__ void run(float (&)[16], uint32_t, uint32_t) {} };

static __device__ bf16 g_h[8 * FF];
static __device__ unsigned int g_sbar;
struct SideParams { const bf16* x; const bf16* w_r; const bf16* w_gate; const bf16* w_up; const bf16* w_down; const bf16* gate_w; const bf16* Wo; };

static __device__ __forceinline__ void side_barrier(unsigned int target) {
  __syncthreads();
  if (threadIdx.x == 0) {
    __threadfence();
    atomicAdd(&g_sbar, 1u);
    int n = 0;
    while (*(volatile unsigned int*)&g_sbar < target) { if (++n > (1 << 22)) { g_err = 50; break; } }
    __threadfence();
  }
  __syncthreads();
}
static __device__ __forceinline__ uint4 ldg_nc(const void* p) { uint4 v;
  asm volatile("ld.global.nc.L1::no_allocate.v4.u32 {%0,%1,%2,%3}, [%4];" : "=r"(v.x), "=r"(v.y), "=r"(v.z), "=r"(v.w) : "l"(p)); return v; }
#ifndef SPD
#define SPD 3
#endif
static __device__ __forceinline__ void l2pf(const void* p) { asm volatile("prefetch.global.L2 [%0];" :: "l"(p)); }
static __device__ __forceinline__ void mm8(float (&acc)[8][4], const bf16* W, const bf16* Wn, int ldw, int nk16, uint32_t abase, uint32_t ring, int lane) {
  const int rw = lane >> 3, ch = lane & 7;
  const bf16* wp = W + (size_t)rw * ldw + ch * 8;
  const uint32_t wd = ring + rw * 128, rd = ring + ((rw & 1) * 8 + ch) * 128;
#define MM_LD(k) do { if ((k) < nk16) { const bf16* q = wp + (size_t)(k) * 16 * ldw; \
    _Pragma("unroll") for (int i = 0; i < 4; i++) cp16(wd + ((k) & 3) * 2048 + i * 512 + ((ch ^ (rw + (i & 1) * 4)) << 4), q + (size_t)(4 * i) * ldw); } \
    asm volatile("cp.async.commit_group;" ::: "memory"); } while (0)
  __syncwarp();
  MM_LD(0); MM_LD(1); MM_LD(2);
#pragma unroll 1
  for (int k = 0; k < nk16; k++) {
    if ((k & 1) == 0) {
      const int kp = k + 4 * SPD;
      const bf16* pf = kp < nk16 ? W + (size_t)(kp * 16) * ldw : Wn ? Wn + (size_t)((kp - nk16) * 16) * ldw : nullptr;
      if (pf) l2pf(pf + (size_t)lane * ldw);
    }
    asm volatile("cp.async.wait_group 2;" ::: "memory");
    __syncwarp();
    MM_LD(k + 3);
    const uint32_t a0 = lds32(abase + k * 32), a2 = lds32(abase + k * 32 + 16);
#pragma unroll
    for (int i = 0; i < 4; i++) {
      const uint4 b = ldsm4t(rd + (k & 3) * 2048 + (((2 * i + (rw >> 1)) ^ ch) << 4));
      mma4(acc[2 * i], a0, 0u, a2, 0u, b.x, b.y); mma4(acc[2 * i + 1], a0, 0u, a2, 0u, b.z, b.w);
    }
  }
}
static __device__ __noinline__ void side_work(const SideParams& P, unsigned char* smem, int q) {
  const int tid = threadIdx.x, lane = tid & 31, warp = tid >> 5, g = lane >> 2, t = lane & 3;
  const uint32_t sb = smem_u32(smem);
  unsigned int* cand = reinterpret_cast<unsigned int*>(smem);
  bf16* xs = reinterpret_cast<bf16*>(smem + 1024);
  float* part = reinterpret_cast<float*>(smem + 65536);
  {
    for (int i = tid; i < 256; i += 384) *reinterpret_cast<uint4*>(smem + 1024 + i * 16) = ldg_nc((i < 128 ? P.gate_w : P.w_r - DM) + i * 8);
    __syncthreads();
#pragma unroll 1
    for (int it = warp; it < 64; it += 12) {
      const bf16* xp = P.x + (size_t)(q * 512 + (it >> 1) * 16 + g) * DM + (it & 1) * 512 + t * 8;
      for (int a = it == warp ? 0 : 1; a < 2 && it + 12 * a < 64; a++)
#pragma unroll
        for (int i = 0; i < 4; i++) l2pf(P.x + (size_t)(q * 512 + (it >> 1) * 16 + a * 96 + i * 4 + (lane >> 3)) * DM + (it & 1) * 512 + (lane & 7) * 64);
      const uint32_t xb = sb + 16384 + warp * 16384 + lane * 16;
#pragma unroll
      for (int i = 0; i < 16; i++) { cp16(xb + i * 1024, xp + i * 32); cp16(xb + i * 1024 + 512, xp + 8 * DM + i * 32); }
      asm volatile("cp.async.commit_group;\ncp.async.wait_group 0;" ::: "memory");
      float sg[4] = {0.f, 0.f, 0.f, 0.f}, sr[4] = {0.f, 0.f, 0.f, 0.f};
#pragma unroll
      for (int i = 0; i < 16; i++) {
        const uint4 gw = lds128(sb + 1024 + (it & 1) * 1024 + i * 64 + t * 16), wr = lds128(sb + 3072 + (it & 1) * 1024 + i * 64 + t * 16);
        const uint4 lo = lds128(xb + i * 1024), hi = lds128(xb + i * 1024 + 512);
        mma4(sr, lo.x, hi.x, lo.y, hi.y, wr.x, wr.y); mma4(sr, lo.z, hi.z, lo.w, hi.w, wr.z, wr.w);
        mma4(sg, mulb2(lo.x, gw.x), mulb2(hi.x, gw.x), mulb2(lo.y, gw.y), mulb2(hi.y, gw.y), 0x3F803F80u, 0x3F803F80u);
        mma4(sg, mulb2(lo.z, gw.z), mulb2(hi.z, gw.z), mulb2(lo.w, gw.w), mulb2(hi.w, gw.w), 0x3F803F80u, 0x3F803F80u);
      }
      if (t == 0) {
        float* pp = reinterpret_cast<float*>(smem + 8192) + (it & 1) * 1024 + (it >> 1) * 16 + g;
        pp[0] = sg[0]; pp[8] = sg[2]; pp[512] = sr[0]; pp[520] = sr[2];
      }
    }
    __syncthreads();
    for (int i = tid; i < 512; i += 384) {
      const float* pp = reinterpret_cast<const float*>(smem + 8192);
      g_gate[q * 512 + i] = rbf(1.f / (1.f + expf(-rbf(pp[i] + pp[1024 + i]))));
      g_r[q * 512 + i] = rbf(pp[512 + i] + pp[1536 + i]);
    }
    for (int i = tid; i < 16 * 896; i += 384) part[i] = 0.f;
  }
#define GU(u) (((u) % 28) / 14 ? P.w_up : P.w_gate) + (size_t)((u) / 28) * 512 * FF + q * 896 + ((u) % 14) * 64
  for (int i = lane; i < 64 * SPD; i += 32) l2pf(GU(warp) + (size_t)i * FF);
  side_barrier(4);
  {
    unsigned int key[8];
#pragma unroll
    for (int i = 0; i < 8; i++) {
      const int tok = (warp & 7) * 256 + i * 32 + lane;
      const uint32_t b = __float_as_uint(__ldcg(&g_r[tok]) + 0.f) >> 16;
      key[i] = (((b & 0x8000u) ? (~b & 0xffffu) : (b | 0x8000u)) << 16) | (uint32_t)(2047 - tok);
    }
    for (int pass = 0; pass < 2; pass++) {
      if (pass == 0 ? warp < 8 : warp == 0) {
        for (int c = 0; c < 8; c++) {
          const unsigned int m = __reduce_max_sync(~0u, max(max(max(key[0], key[1]), max(key[2], key[3])), max(max(key[4], key[5]), max(key[6], key[7]))));
#pragma unroll
          for (int i = 0; i < 8; i++) if (key[i] == m) key[i] = 0u;
          if (lane == 0) cand[pass ? 128 + c : warp * 8 + c] = m;
        }
      }
      __syncthreads();
      if (pass == 0 && warp == 0) {
#pragma unroll
        for (int i = 0; i < 8; i++) key[i] = i < 2 ? cand[i * 32 + lane] : 0u;
      }
    }
    if (q == 0 && tid < 8) g_idx[tid] = 2047 - (int)(cand[128 + tid] & 0xffffu);
    for (int i = tid; i < 1024; i += 384) {
      const int c = i >> 7, tok = 2047 - (int)(cand[128 + c] & 0xffffu);
      *reinterpret_cast<uint4*>(xs + c * (FF + 8) + (i & 127) * 8) = ldg_nc(P.x + (size_t)tok * DM + (i & 127) * 8);
    }
    __syncthreads();
  }
  const uint32_t abase = sb + 1024 + g * (FF + 8) * 2 + t * 4, ring = sb + 131072 + warp * 8192;
  for (int u = warp; u < 56; u += 12) {
    const int kh = u / 28, mat = (u % 28) / 14, cb = u % 14;
    float acc[8][4];
#pragma unroll
    for (int i = 0; i < 8; i++) acc[i][0] = acc[i][1] = acc[i][2] = acc[i][3] = 0.f;
    mm8(acc, GU(u), u + 12 < 56 ? GU(u + 12) : nullptr, FF, DM / 32, abase + kh * 1024, ring, lane);
    float* pp = part + (mat * 8 + g) * 896 + cb * 64 + 2 * t;
#pragma unroll
    for (int i = 0; i < 8; i++) { atomicAdd(pp + 8 * i, acc[i][0]); atomicAdd(pp + 8 * i + 1, acc[i][1]); }
  }
  for (int i = lane; i < 64 * SPD; i += 32) l2pf(P.w_down + (size_t)((warp >> 2) * 1216 + i) * DM + q * 256 + (warp & 3) * 64);
  __syncthreads();
  for (int i = tid; i < 8 * 896; i += 384) {
    const float ag = rbf(part[i]), au = rbf(part[8 * 896 + i]);
    g_h[(i / 896) * FF + q * 896 + i % 896] = __float2bfloat16(rbf(ag / (1.f + expf(-ag))) * au);
  }
  side_barrier(8);
  for (int i = tid; i < 8 * FF / 8; i += 384) {
    const int c = i / (FF / 8), o = i % (FF / 8);
    *reinterpret_cast<uint4*>(xs + c * (FF + 8) + o * 8) = __ldcg(reinterpret_cast<const uint4*>(g_h + c * FF + o * 8));
  }
  __syncthreads();
  {
    const int cb = warp & 3, kq = warp >> 2;
    float acc[8][4];
#pragma unroll
    for (int i = 0; i < 8; i++) acc[i][0] = acc[i][1] = acc[i][2] = acc[i][3] = 0.f;
    mm8(acc, P.w_down + (size_t)kq * 1216 * DM + q * 256 + cb * 64, nullptr, DM, kq == 2 ? 72 : 76, abase + kq * 1216 * 2, ring, lane);
#pragma unroll
    for (int i = 0; i < 8; i++) { part[(kq * 8 + g) * 256 + cb * 64 + 2 * t + 8 * i] = acc[i][0]; part[(kq * 8 + g) * 256 + cb * 64 + 2 * t + 8 * i + 1] = acc[i][1]; }
    __syncthreads();
    for (int i = tid; i < 2048; i += 384) {
      const int c = i >> 8, tok = 2047 - (int)(cand[128 + c] & 0xffffu);
      const float y = (part[i] + part[2048 + i]) + part[4096 + i];
      const float rs = rbf(1.f / (1.f + expf(-__ldcg(&g_r[tok]))));
      g_upd[c * DM + q * 256 + (i & 255)] = __float2bfloat16(rbf(y) * rs);
    }
  }
}
struct RecParams { const bf16* mem0; unsigned char* win; };
struct WMaps { CUtensorMap q, k, v; };
#ifndef KB
#define KB 8
#endif
#ifndef WPF
#define WPF 7
#endif
#ifndef WPA
#define WPA 3
#endif
#ifndef XPF
#define XPF 4
#endif
#ifndef O2P
#define O2P 4
#endif
#ifndef XG
#define XG 1
#endif
#ifndef Z0
#define Z0 1
#endif
#ifndef Z1
#define Z1 1
#endif
#ifndef WKP
#define WKP 0
#endif
#ifndef OS
#define OS 1
#endif
#ifndef SO
#define SO 1
#endif
#define RF_FAT 208
#define RF_CTL 88
#define WSPL 1
#define NPROBE 3
#define DLY_TB 700
#define DLY_SIDE 16000
#define KU 32
#define KD 4
#ifndef DLYS
#define DLYS 560, 330, 250, 280, 770, 300, 1248, 850, 460
#endif
#define NTUNE 9
#define TUNE_NAMES {"OM3", "XL", "S", "XD", "WO", "V", "OK", "OKS", "ORR"}
__constant__ int g_tune[NTUNE] = {DLYS};
#define DLY_M3 g_tune[0]
#define DLY_XL g_tune[1]
#define DLY_S g_tune[2]
#define DLY_XD g_tune[3]
#define DLY_WO g_tune[4]
#define DLY_V g_tune[5]
#define DLY_K g_tune[6]
#define DLY_KS g_tune[7]
#define DLY_RR g_tune[8]
#ifdef PRO
__device__ unsigned g_pro[NCTA][16];
#define PT(i, c) do { if (c) g_pro[cta][i] = gt32(); } while (0)
#else
#define PT(i, c)
#endif
#ifdef PER
__device__ unsigned g_pk[NCTA][64], g_pclk[NCTA][64], g_per[NCTA][64], g_end[8] = {0, 0, 0, 0, 0, 0, 0, 100000};
#endif
#define STR2(x) #x
#define STR(x) STR2(x)

static __device__ __forceinline__ void cp16p(uint32_t dst, const void* src, uint32_t v) {
  asm volatile("{\n.reg .pred q;\nsetp.ne.u32 q, %2, 0;\n@q cp.async.cg.shared.global [%0], [%1], 16;\n}" :: "r"(dst), "l"(src), "r"(v) : "memory"); }
static __device__ __forceinline__ void red_bf2(void* p, uint32_t v) {
  asm volatile("red.relaxed.gpu.global.add.noftz.bf16x2 [%0], %1;" :: "l"(p), "r"(v) : "memory"); }
static __device__ __forceinline__ void red_bf2p4(void* p, uint32_t v, uint32_t e) {
  asm volatile("{\n.reg .pred q;\nsetp.lt.u32 q, %2, 4;\n@q red.relaxed.gpu.global.add.noftz.bf16x2 [%0], %1;\n}" :: "l"(p), "r"(v), "r"(e) : "memory"); }
static __device__ __forceinline__ void eta2(void* p, uint32_t t, uint32_t first, uint32_t l16) {
  asm volatile("{\n.reg .pred q;\nsetp.lt.u32 q, %3, 32;\n@q red.relaxed.gpu.global.max.u32 [%0+4], %1;\n@q red.relaxed.gpu.global.add.u32 [%0], %2;\n}" :: "l"(p), "r"(t), "r"(first), "r"(l16) : "memory"); }
static __device__ __forceinline__ void sts16(uint32_t a, uint32_t x) { asm volatile("{\n.reg .b16 h;\ncvt.u16.u32 h, %1;\nst.shared.u16 [%0], h;\n}" :: "r"(a), "r"(x) : "memory"); }
static __device__ __forceinline__ uint32_t cnt_word(uint32_t L) { return (L & 17u) | ((L & 6u) << 1) | ((L & 8u) >> 2); }
static __device__ __forceinline__ uint32_t cnt_line(uint32_t l) { return (l & 17u) | ((l & 12u) >> 1) | ((l & 2u) << 2); }
static __device__ __forceinline__ int m3_check(uint32_t sb, const unsigned char* p3, const unsigned char* pd, int dq, uint32_t l16, uint32_t mc, int hf, int s) {
  const uint32_t md = l16 + (sb + SM_MEM + hf * 8192), dd = l16 + (sb + SM_RD + hf * 256), dc = (l16 >> 2) + (sb + SM_RD + hf * 256);
  int n = 0;
  uint32_t c0 = 0, c1 = 0, d0 = 0, d1 = 0, todo = 1;
#pragma unroll 1
  do {
    if (n) {
      const int src = cnt_word(l16 >> 4);
      const uint32_t m0 = __ballot_sync(~0u, (__shfl_sync(~0u, c0, src) >> 16) != 0x4200u) >> (l16 >> 7), m1 = __ballot_sync(~0u, (__shfl_sync(~0u, c1, src) >> 16) != 0x4200u) >> (l16 >> 7);
      const uint32_t m2 = __ballot_sync(~0u, (d0 >> 16) != 0x4200u), m3 = __ballot_sync(~0u, (d1 >> 16) != 0x4200u);
#pragma unroll
      for (int i = 0; i < 8; i++) { cp16p(md + i * 512, p3 + i * 1024, m0 & (1u << (4 * i))); cp16p(md + 4096 + i * 512, p3 + dq + i * 1024, m1 & (1u << (4 * i))); }
      cp16p(dd, pd, l16 < 256u ? (((l16 & 128u) ? m3 : m2) >> ((l16 >> 2) & 28u)) & 15u : 0u);
      sts32(sb + SM_Z + 40, s);
    }
    n++;
    asm volatile("cp.async.commit_group;\ncp.async.wait_group 0;" ::: "memory");
    __syncwarp();
    asm volatile("{\n.reg .pred p, q;\n.reg .b32 a, b;\n.reg .b16 h, g;\nsetp.ne.u32 p, %4, 0;\n"
                 "@p ld.shared.u32 %2, [%6];\n@p ld.shared.u32 %3, [%6+128];\n@p ld.shared.u32 %0, [%5];\n@p ld.shared.u32 %1, [%5+4096];\n"
                 "lop3.b32 a, %2, %3, 0x42000000, 0x7e;\nlop3.b32 b, %0, %1, 0x42000000, 0x7e;\nor.b32 a, a, b;\nsetp.lt.and.u32 q, a, %8, p;\n"
                 "cvt.u16.u32 h, %2;\ncvt.u16.u32 g, %3;\n@q st.shared.u16 [%5+2], h;\n@q st.shared.u16 [%5+4098], g;\n@q mbarrier.arrive.shared::cta.b64 _, [%7];\n"
                 "@q mov.u32 %4, 0;\n}"
                 : "+r"(c0), "+r"(c1), "+r"(d0), "+r"(d1), "+r"(todo) : "r"(mc), "r"(dc), "r"(sb + SM_BAR + MB_MEM + hf * 8), "r"(n < SPIN_LIMIT ? 0x10000u : ~0u) : "memory");
  } while (__any_sync(~0u, todo));
  return n - 1;
}

__global__ void __cluster_dims__(2, 1, 1) __launch_bounds__(384, 1)
rec_kernel(const __grid_constant__ CUtensorMap tmx, const __grid_constant__ CUtensorMap tmw, const __grid_constant__ WMaps W, RecParams P, const __grid_constant__ SideParams SP) {
  extern __shared__ __align__(1024) unsigned char smem[];
  asm volatile("griddepcontrol.launch_dependents;");
  const uint32_t sb = smem_u32(smem);
  const int tid = threadIdx.x, lane = tid & 31, t128 = tid & 127;
  const int wg = __shfl_sync(~0u, tid >> 7, 0), wq = __shfl_sync(~0u, (tid >> 5) & 3, 0);
  const int r = blockIdx.x & 1, pp = blockIdx.x >> 1;
  const int mi = lane >> 3, r8 = lane & 7;
  const uint32_t xb16 = __shfl_sync(~0u, (((sb + SM_X + (tid >> 7) * 32768 + r * 16384) & 0x3FFFF) >> 4) | (1u << 16), 0);
  const uint32_t va16 = __shfl_sync(~0u, (((sb + SM_WVS + (tid >> 7) * 16384) & 0x3FFFF) >> 4) | (64u << 16), 0);
#if defined(PER) || defined(PRO)
  const uint32_t tstart = gt32();
#endif

  if (tid == 0) {
    mbar_init(sb + SM_BAR + MB_F, 1); mbar_init(sb + SM_BAR + MB_F + 8, 1); mbar_init(sb + SM_BAR + MB_XE0, 2); mbar_init(sb + SM_BAR + MB_XE1, 2); mbar_init(sb + SM_BAR + MB_INIT, 2);
    mbar_init(sb + SM_BAR + MB_MEM, 32); mbar_init(sb + SM_BAR + MB_MEM + 8, 32); for (int i = 0; i < 8; i++) mbar_init(sb + SM_BAR + MB_W + i * 8, 1);
    mbar_init(sb + SM_BAR + MB_XF, 8); mbar_init(sb + SM_BAR + MB_X0, 1); mbar_init(sb + SM_BAR + MB_WO, 1); mbar_init(sb + SM_BAR + MB_VR, 5);
    sts32(sb + SM_Z + 40, ~0u);
    asm volatile("fence.mbarrier_init.release.cluster;" ::: "memory");
  }
  if (tid >= 64 && tid < 96) {
    const uint32_t l16 = lane * 16, qa = ((l16 & 0x30u) << 3) | ((l16 & 0x10u) << 2) | ((l16 >> 3) & 0x30u) | ((l16 >> 4) & 4u);
    sts128(sb + SM_QA + l16, qa + (sb + SM_QKP), (qa ^ 64u) + (sb + SM_QKP), 0u, 0u);
  }
  if (tid == 32) {
    asm volatile("prefetch.tensormap [%0];" :: "l"(&W.q) : "memory"); asm volatile("prefetch.tensormap [%0];" :: "l"(&W.k) : "memory");
    asm volatile("prefetch.tensormap [%0];" :: "l"(&W.v) : "memory"); asm volatile("prefetch.tensormap [%0];" :: "l"(&tmx) : "memory");
  }
  if (tid >= 256 && tid < 320) {
    unsigned char* pl = P.win + r * W_2 + (W_UP | (1u << 19) | ((pp >> 5) << 14)) + (pp & 31) * 128 + wq * 4096;
    stg_r1(pl + lane * 4, 0u);
    uint32_t best = 1u << 30;
    if (lane == 0) {
#pragma unroll 1
      for (int rep = 0; rep < NPROBE; rep++) {
        uint32_t dt;
        asm volatile("{\n.reg .u32 a, b, v;\nmov.u32 a, %%clock;\natom.relaxed.gpu.global.exch.b32 v, [%1], 0;\n"
                     "st.volatile.shared.u32 [%2], v;\nmov.u32 b, %%clock;\nsub.u32 %0, b, a;\n}" : "=r"(dt) : "l"(pl), "r"(sb + SM_SIDE + wq * 4) : "memory");
        best = min(best, dt);
      }
    }
    if (lane == 0) sts32(sb + SM_SIDE + wq * 4, best);
    bar_sync(B_P, 64);
    if (wq == 0) {
      const uint2 bt = lds64(sb + SM_SIDE);
      if (lane < 8 && (r == 0 || pp == 0)) stg_r1(&g_side[(r ? 66 : pp) * 32 + lane], 2u | (bt.x < bt.y ? 1u : 0u));
      spin(DLY_TB);
      uint32_t a, b, c; int n = 0;
#pragma unroll 1
      do {
        a = ldg_r1(&g_side[lane * 32]); b = ldg_r1(&g_side[(32 + lane) * 32]); c = ldg_r1(&g_side[(64 + min(lane, 2)) * 32]);
      } while (!__all_sync(~0u, a & b & c & 2u) && ++n < SPIN_LIMIT);
      a = __ballot_sync(~0u, a & 1u); b = __ballot_sync(~0u, b & 1u); c = __ballot_sync(~0u, c & 1u);
      const uint32_t pol2 = (a ^ (c >> 2)) & 1u;
      c &= 3u;
      const unsigned long long ab = ((unsigned long long)b << 32) | a;
      const int sd = pp < 64 ? (int)(ab >> pp) & 1 : (int)(c >> (pp - 64)) & 1;
      const int n1 = __popcll(ab) + __popc(c), n0 = 66 - n1;
      const int below1 = pp < 64 ? __popcll(ab & ((1ull << pp) - 1)) : __popcll(ab) + (pp == 65 ? (int)(c & 1u) : 0);
      const int rk = sd ? below1 : pp - below1;
      const int k0 = (n0 & 1) ? n0 - 1 : n0 >= n1 ? n0 - 2 : n0, k1 = 64 - k0;
      const int role = rk >= (sd ? k1 : k0) ? 64 + ((n0 & 1) ? sd : rk - (sd ? k1 : k0)) : sd ? k0 + rk : rk;
      __syncwarp();
      if (lane == 0) sts128(sb + SM_SIDE, 2 * k0, 0u, pol2, role * 2 + r);
#ifdef PER
      if (lane == 0) { atomicMax(&g_end[6], gt32()); atomicMin(&g_end[7], max(bt.x, bt.y) - min(bt.x, bt.y)); }
#endif
    }
  }
  __syncthreads();
  const int cta = __shfl_sync(~0u, (int)lds32(sb + SM_SIDE + 12), 0), h = cta >> 2, j = cta & 3, p = j >> 1;
  const int sw = (cta >= __shfl_sync(~0u, (int)lds32(sb + SM_SIDE), 0) ? 1 : 0) ^ r;
  if (cta >= NCTA) {
    spin(DLY_SIDE);
#ifndef NOSIDE
    side_work(SP, smem, cta - NCTA);
#endif
#ifdef PER
    if (threadIdx.x == 0) atomicMax(&g_end[1], gt32());
#endif
    return;
  }
#ifdef PER
  if (threadIdx.x == 0) g_per[cta][63] = tstart;
#endif
#ifdef PRO
  if (tid == 0) { g_pro[cta][0] = tstart; g_pro[cta][1] = gt32(); }
#endif
  asm volatile("barrier.cluster.arrive.relaxed.aligned;" ::: "memory");
#define WLOAD(i0, i1) _Pragma("unroll 1") for (int u = i0; u < i1; u++) {        \
    const int g2 = u >> 2, i = u & 3, k = g2 * 512 + ((i * 128 + r * 256) & 511); \
    const uint32_t mb = sb + SM_BAR + MB_W + u * 8; \
    mbar_expect_tx(mb, i < 2 ? 32768 : 16384); \
    tma_load_2d(sb + g2 * 65536 + i * 8192, &W.q, h * DH + j * 32, k, mb); \
    tma_load_2d(sb + g2 * 65536 + 32768 + i * 8192, &W.k, h * DH + j * 32, k, mb); \
    if (i < 2) tma_load_2d(sb + (i ? SM_WVS : SM_VST) + g2 * 16384, &W.v, h * DH + p * 64, k, mb); }
  if (tid == 288) {
    mbar_expect_tx(sb + SM_BAR + MB_X0, 32768);
#pragma unroll 1
    for (int i = 0; i < 2; i++)
      asm volatile("cp.async.bulk.tensor.3d.shared::cluster.global.mbarrier::complete_tx::bytes [%0], [%1, {%3, %3, %4}], [%2];"
                   :: "r"(sb + SM_MEM + i * 16384), "l"(&tmx), "r"(sb + SM_BAR + MB_X0), "r"(0), "r"(i * 4) : "memory");
    WLOAD(0, 4 + WSPL);
  }
  __syncwarp();
  asm volatile("barrier.cluster.wait.acquire.aligned;" ::: "memory");
#define SIDES() const uint4 sm2 = lds128(sb + SM_SIDE); const int nlo = sm2.x; const uint32_t me = cta >= nlo

#define XLOAD(t, sg) tma_load_mc(sb + SM_X + ((t) * 8 + r * 4) * 4096, &tmx, (sg) * SEG, (t) * 8 + r * 4, sb + SM_BAR + MB_F + (t) * 8)
#define F0LOAD() do { mbar_wait(sb + SM_BAR + MB_XE0, s & 1); \
    if (l16 == 0) XLOAD(0, s + 2); \
    __syncwarp(); } while (0)
  if (wg < 2) {
    asm volatile("setmaxnreg.inc.sync.aligned.u32 " STR(RF_FAT) ";");
    uint32_t w[32][4], wv[8][4];
    uint32_t lm = ((mi >> 1) * 8 + r8) * 128 + (((wq * 2 + (mi & 1)) ^ r8) << 4), l16 = lane * 16;
    lm = __shfl_sync(~0u, lm, lane); l16 = __shfl_sync(~0u, l16, lane);
    {
      const uint32_t lq0 = sb + wg * 65536 + (wq >> 1) * 32768 + ((mi >> 1) * 8 + r8) * 64 + ((((wq & 1) * 2 + (mi & 1)) ^ (r8 >> 1)) << 4);
      const uint32_t f = wq < 2 ? 0x3D003D00u : 0x3F803F80u;
#pragma unroll
      for (int i = 0; i < 4; i++) {
        mbar_wait(sb + SM_BAR + MB_W + (wg * 4 + i) * 8, 0);
        if (i == 3) PT(2 + wg, t128 == 0);
#pragma unroll
        for (int kk = 8 * i; kk < 8 * i + 8; kk++) ldmatrix_x4_trans(w[kk], lq0 + kk * 1024);
        if (i == 0) {
#pragma unroll
          for (int kk = 0; kk < 8; kk++) ldmatrix_x4_trans(wv[kk], sb + SM_VST + wg * 16384 + kk * 2048 + lm);
        }
#pragma unroll
        for (int kk = 32 * i; kk < 32 * i + 32; kk++) w[kk >> 2][kk & 3] = mulb2v(w[kk >> 2][kk & 3], f);
      }
    }
    if (wg == 0) bar_sync(B_V, 160);
    else bar_arrive(B_P, 160);
    const int w8 = wg * 4 + wq;
    const int cw = sw ^ wg;
    const uint32_t xh16 = xb16 ^ 1024u;
    const uint32_t rsb = mapa(sb, r ^ 1);
#define MT (l16 + (sb + SM_MEM + wg * 8192))
#define WA (lm + (sb + SM_WVS + wg * 16384))
#define WOF(f) (lm + (sb + SM_WOS + wg * 32768 + ((f) & 1) * 16384 + ((f) >> 1) * 2048))
#define TH(base) (l16 + (sb + (base) + w8 * 512))
#define TQ(base) (l16 + (sb + (base) + wq * 512))
#define DUMP(base) _Pragma("unroll") for (int n = 0; n < 4; n++) sts128f(TQ((base) + n * 2048), d[4 * n], d[4 * n + 1], d[4 * n + 2], d[4 * n + 3])
#define INIT(base) _Pragma("unroll") for (int n = 0; n < 4; n++) { const float4 t = lds128f(TQ((base) + n * 2048)); d[4 * n] = t.x; d[4 * n + 1] = t.y; d[4 * n + 2] = t.z; d[4 * n + 3] = t.w; }
#define XQK(first, b0, b1) do { wg_fence(); XR<0, 16, 0, 32, first>::run(d, w, b0); XR<0, 16, 16, 32, 0>::run(d, w, b1); wg_commit(); wg_wait0(); } while (0)
#define XVS(first, b0) do { wg_fence(); XS<8, 8, 16, first>::run(d, va16, b0); XR<0, 8, 0, 8, 0>::run(d, wv, b0); wg_commit(); wg_wait0(); } while (0)
#define XREL(mb) do { if (wq == 0 && l16 == 0) { mbar_arrive_cluster_rlx(rsb + SM_BAR + (mb)); mbar_arrive(sb + SM_BAR + (mb)); } } while (0)
#define XFOUT() do { \
          _Pragma("unroll") for (int hf = 0; hf < 2; hf++) \
            stsm4t(l16 + (sb + SM_XF + (wq * 2 + hf) * 512), pack_bf16(d[8 * hf], d[8 * hf + 1]), pack_bf16(d[8 * hf + 2], d[8 * hf + 3]), \
                   pack_bf16(d[8 * hf + 4], d[8 * hf + 5]), pack_bf16(d[8 * hf + 6], d[8 * hf + 7])); \
          __syncwarp(); \
          if (l16 < 32) mbar_arrive(sb + SM_BAR + MB_XF); } while (0)
#define VDUMP(base) _Pragma("unroll") for (int n = 0; n < 2; n++) sts128(TQ((base) + n * 2048), pack_bf16(d[8 * n], d[8 * n + 1]), pack_bf16(d[8 * n + 2], d[8 * n + 3]), pack_bf16(d[8 * n + 4], d[8 * n + 5]), pack_bf16(d[8 * n + 6], d[8 * n + 7]))

    if (wg == 0) {
      float d[16];
      const uint32_t x0 = (((sb + SM_MEM + r * 16384) & 0x3FFFF) >> 4) | (1u << 16), x1 = (((sb + SM_MEM + (r ^ 1) * 16384) & 0x3FFFF) >> 4) | (1u << 16);
      mbar_wait(sb + SM_BAR + MB_X0, 0);
      XQK(1, x0, x1);
      DUMP(SM_CQ);
      XVS(1, x0);
      bar_arrive(B_X2, 256);
      VDUMP(SM_CV);
      bar_sync(B_CQ, 256);
    } else {
      float d[16];
      bar_sync(B_CQ, 256);
      INIT(SM_CQ);
      mbar_wait(sb + SM_BAR + MB_F + 8, 0);
      PT(4, t128 == 0);
      XQK(0, xb16, xh16);
      XFOUT();
      PT(5, t128 == 0);
    }
    if (wg == 0) mbar_wait(sb + SM_BAR + MB_F, 0);
    for (int s = -1;; s++) {
      if (s >= 0) {
        OPAQUE_R(lm); OPAQUE_R(l16);
        {
          uint32_t sa[4][4];
#pragma unroll
          for (int i = 0; i < 2; i++) ldmatrix_x4_trans(sa[i], WA + i * 2048);
          float a[2][4], v[2][4]; uint4 c[4]; uint2 qa;
          FENCE();
          mbar_wait(sb + SM_BAR + MB_MEM + wg * 8, s & 1);
#define QP(i) ((i) >= 12 ? (i) - 8 : (i) % 3 == 1 ? (i) / 3 : 8 + (i) - ((i) + 2) / 3)
#pragma unroll
          for (int i = 0; i < 3; i++) c[i] = ldsm4t(MT + QP(i) * 512);
#pragma unroll
          for (int i = 0; i < 16; i++) {
            if (i + 3 < 16) c[(i + 3) & 3] = ldsm4t(MT + QP(i + 3) * 512);
            if (i == 13) qa = lds64(l16 + (sb + SM_QA));
            if (i == 0) {
              mma4z(a[0], w[2 * QP(i)][0], w[2 * QP(i)][1], w[2 * QP(i)][2], w[2 * QP(i)][3], c[i & 3].x, c[i & 3].y);
              mma4z(a[1], w[2 * QP(i) + 1][0], w[2 * QP(i) + 1][1], w[2 * QP(i) + 1][2], w[2 * QP(i) + 1][3], c[i & 3].z, c[i & 3].w);
            } else {
              mma_16816(a[0], w[2 * QP(i)], c[i & 3].x, c[i & 3].y);
              mma_16816(a[1], w[2 * QP(i) + 1], c[i & 3].z, c[i & 3].w);
            }
            if (QP(i) == 0) {
              mma4z(v[0], wv[0][0], wv[0][1], wv[0][2], wv[0][3], c[i & 3].x, c[i & 3].y);
              mma4z(v[1], wv[1][0], wv[1][1], wv[1][2], wv[1][3], c[i & 3].z, c[i & 3].w);
            } else if (QP(i) < 4) {
              mma_16816(v[0], wv[2 * (QP(i) & 3)], c[i & 3].x, c[i & 3].y);
              mma_16816(v[1], wv[2 * (QP(i) & 3) + 1], c[i & 3].z, c[i & 3].w);
            }
            if (i == 12) {
              mma_16816(v[0], sa[0], c[0].x, c[0].y); mma_16816(v[1], sa[1], c[0].z, c[0].w);
            }
            if (i == 13) { ldmatrix_x4_trans(sa[0], WA + 2 * 2048); ldmatrix_x4_trans(sa[1], WA + 3 * 2048); ldmatrix_x4_trans(sa[2], WA + 4 * 2048); }
            FENCE();
          }
#pragma unroll
          for (int i = 0; i < 4; i++) sts32(((i & 1) ? qa.y : qa.x) + (w8 * 512 + (i >> 1) * 8), f2u(a[0][i] + a[1][i]));
          bar_arrive(B_QK, 288);
          bar_arrive(B_QK1, 288);
          FENCE();
          uint32_t sc2[4];
          ldmatrix_x4_trans(sa[3], WA + 5 * 2048); ldmatrix_x4_trans(sc2, WA + 6 * 2048);
          mma_16816(v[0], sa[0], c[1].x, c[1].y); mma_16816(v[1], sa[1], c[1].z, c[1].w);
          FENCE();
          ldmatrix_x4_trans(sa[0], WA + 7 * 2048);
          FENCE();
          mma_16816(v[0], sa[2], c[2].x, c[2].y); mma_16816(v[1], sa[3], c[2].z, c[2].w);
          mma_16816(v[0], sc2, c[3].x, c[3].y); mma_16816(v[1], sa[0], c[3].z, c[3].w);
          FENCE();
          sts128f(TH(SM_VP), v[0][0] + v[1][0], v[0][1] + v[1][1], v[0][2] + v[1][2], v[0][3] + v[1][3]);
          bar_arrive(B_V, 320);
        }
        if (s == NSEG - 1) break;
        OPAQUE_R(lm); OPAQUE_R(l16);
        uint32_t wo[WPF][4];
        {
          float d[16];
#define XOUT(g) _Pragma("unroll") for (int n = 0; n < 2; n++) sts128f(TQ(SM_CQ + ((g) * 2 + n) * 2048), d[8 - 8 * (g) + 4 * n], d[9 - 8 * (g) + 4 * n], d[10 - 8 * (g) + 4 * n], d[11 - 8 * (g) + 4 * n])
#define XIN(g) do { \
            const float4 t0 = lds128f(TQ(SM_CQ + (2 - 2 * (g)) * 2048)), t1 = lds128f(TQ(SM_CQ + (3 - 2 * (g)) * 2048)); \
            stsm4t(l16 + (sb + SM_XF + (wq * 2 + (g)) * 512), pack_bf16(d[8 * (g)] + t0.x, d[8 * (g) + 1] + t0.y), pack_bf16(d[8 * (g) + 2] + t0.z, d[8 * (g) + 3] + t0.w), \
                   pack_bf16(d[8 * (g) + 4] + t1.x, d[8 * (g) + 5] + t1.y), pack_bf16(d[8 * (g) + 6] + t1.z, d[8 * (g) + 7] + t1.w)); } while (0)
          if (wg == 0) {
            INIT(SM_CW);
            bar_sync(B_PUB, 320);
            wg_fence();
            XR<KB, 16, 0, 32, 0>::run(d, w, xb16); XR<0, 16, 16, 32, 0>::run(d, w, xh16);
            wg_commit(); wg_wait0();
            TSF(13, 1);
            OPAQUE_R(l16);
            XOUT(0);
            bar_arrive(B_G1, 256);
            XREL(MB_XE0);
            bar_sync(B_CQ, 256);
            XIN(0);
#pragma unroll
            for (int f = 0; f < WPA; f++) ldmatrix_x4_trans(wo[f], WOF(f));
          } else {
            const uint32_t ok = mbar_test(sb + SM_BAR + MB_F + 8, (s + 1) & 1);
            bar_sync(B_PUB, 320);
            if (!ok) mbar_wait(sb + SM_BAR + MB_F + 8, (s + 1) & 1);
            wg_fence();
#if WKP
            XR<0, 16, 0, 32, 1>::run(d, w, xb16); XR<0, WKP - 16, 16, 32, 0>::run(d, w, xh16);
            wg_commit(); wg_fence();
            XR<WKP - 16, WKP - 15, 16, 32, 0>::run(d, w, xh16);
#pragma unroll
            for (int f = 0; f < WPA; f++) ldmatrix_x4_trans(wo[f], WOF(f));
            wg_commit(); wg_fence();
            XR<WKP - 15, 16, 16, 32, 0>::run(d, w, xh16);
            wg_commit();
#else
            XR<0, 16, 0, 32, 1>::run(d, w, xb16); XR<0, 16, 16, 32, 0>::run(d, w, xh16);
            wg_commit();
#pragma unroll
            for (int f = 0; f < WPA; f++) ldmatrix_x4_trans(wo[f], WOF(f));
#endif
            wg_wait0();
            TSF(31, 5);
            OPAQUE_R(l16);
            XOUT(1);
            bar_arrive(B_CQ, 256);
            bar_sync(B_G1, 256);
            XIN(1);
          }
          __syncwarp();
          if (l16 == 0) mbar_arrive(sb + SM_BAR + MB_XF);
          TSF(3, 5);
        }
        if (Z1 && s == 0) {
          mbar_wait(sb + SM_BAR + MB_WO, 0);
#pragma unroll
          for (int f = 0; f < WPA; f++) ldmatrix_x4_trans(wo[f], WOF(f));
        }
#pragma unroll
        for (int f = WPA; f < WPF; f++) ldmatrix_x4_trans(wo[f], WOF(f));
        unsigned char* pa = P.win + (w_ar(s) + (j * 32 + cw * 16 + wq * 2) * 256 + (l16 >> 2));
        uint32_t ce = (l16 >> 4) - 4 * (cw * 4 + wq);
        OPAQUE_L(pa); OPAQUE_R(ce);
        FENCE();
        bar_sync(wg ? B_O : B_O2, wg || !XG ? 192 : 224);
        uint4 ob[2];
        ob[0] = ldsm4(l16 + (sb + SM_OF)); ob[1] = ldsm4(l16 + (sb + SM_OF + 512));
        float acc[2][4]; uint32_t f0ok;
#pragma unroll
        for (int f = 0; f < 16; f++) {
          const int ks = f >> 1;
          const uint32_t b0 = (ks & 1) ? ob[(ks >> 1) & 1].z : ob[(ks >> 1) & 1].x, b1 = (ks & 1) ? ob[(ks >> 1) & 1].w : ob[(ks >> 1) & 1].y;
          if (f < 2) mma4z(acc[f], wo[f][0], wo[f][1], wo[f][2], wo[f][3], b0, b1);
          else mma_16816(acc[f % 2], wo[f < WPF ? f : 2 + (f - WPF) % (WPF - 2)], b0, b1);
          if (f - 1 >= 2 && f - 1 + (WPF - 2) < 16) {
            const int nf = f - 1 + (WPF - 2);
            ldmatrix_x4_trans(wo[2 + (nf - WPF) % (WPF - 2)], WOF(nf));
          }
          if (f == 4 || f == 8) ob[((f >> 2) - 1) & 1] = ldsm4(l16 + (sb + SM_OF + (1 + (f >> 2)) * 512));
          if (f == 12) f0ok = mbar_test(sb + SM_BAR + MB_F, (s + 1) & 1);
          if (f < 15) FENCE();
        }
        if (!wg) bar_arrive(B_CV, 256);
        red_bf2(pa, pack_bf16(acc[0][0], ce == 0 ? 1.f : acc[0][1])); red_bf2(pa + 256, pack_bf16(acc[0][2], ce == 1 ? 1.f : acc[0][3]));
        red_bf2(pa + 2048, pack_bf16(acc[1][0], ce == 2 ? 1.f : acc[1][1])); red_bf2(pa + 2304, pack_bf16(acc[1][2], ce == 3 ? 1.f : acc[1][3]));
        red_bf2p4(pa + (W_DS + (wq & 1) * 256), pack_bf16(ce == 0 ? acc[0][1] : ce == 1 ? acc[0][3] : ce == 2 ? acc[1][1] : acc[1][3], 1.f), ce);
        TSF(4, 1); TSF(2, 6);
        if (wg) bar_sync(B_CV, 256);
        else if (!f0ok) mbar_wait(sb + SM_BAR + MB_F, (s + 1) & 1);
      }
      OPAQUE_R(lm); OPAQUE_R(l16);
      {
        float d[16];
        const uint32_t cv = TQ(SM_CV + ((s ^ wg) & 1) * 4096);
        TSF(9, 1);
        wg_fence();
        XR<0, 1, 0, 8, 1>::run(d, wv, xb16); XS<8, 8, 9, 0>::run(d, va16, xb16); XR<1, 2, 0, 8, 0>::run(d, wv, xb16); XS<9, 8, 10, 0>::run(d, va16, xb16);
        XR<2, 3, 0, 8, 0>::run(d, wv, xb16); XS<10, 8, 11, 0>::run(d, va16, xb16); XR<3, 4, 0, 8, 0>::run(d, wv, xb16); XS<11, 8, 12, 0>::run(d, va16, xb16);
        XR<4, 5, 0, 8, 0>::run(d, wv, xb16); XS<12, 8, 13, 0>::run(d, va16, xb16); XR<5, 6, 0, 8, 0>::run(d, wv, xb16); XS<13, 8, 14, 0>::run(d, va16, xb16);
        XR<6, 7, 0, 8, 0>::run(d, wv, xb16); XS<14, 8, 15, 0>::run(d, va16, xb16); XR<7, 8, 0, 8, 0>::run(d, wv, xb16); XS<15, 8, 16, 0>::run(d, va16, xb16);
        wg_commit(); wg_wait0();
        uint32_t q[8];
#pragma unroll
        for (int i = 0; i < 8; i++) q[i] = pack_bf16(d[2 * i], d[2 * i + 1]);
        if (wg == 0) {
          sts128(cv, q[0], q[1], q[2], q[3]); sts128(cv + 2048, q[4], q[5], q[6], q[7]);
          wg_fence(); XR<0, KB, 0, 32, 1>::run(d, w, xb16); wg_commit(); wg_wait0();
          OPAQUE_R(l16);
          DUMP(SM_CW);
          TSF(5, 1);
        } else {
          const uint4 o = lds128(cv + (r ^ 1) * 2048), k = lds128(cv + r * 2048);
          XREL(MB_XE1);
          st_async4(l16 + (rsb + SM_VR + wq * 512), u2f(addb2(r ? q[0] : q[4], o.x)), u2f(addb2(r ? q[1] : q[5], o.y)), u2f(addb2(r ? q[2] : q[6], o.z)), u2f(addb2(r ? q[3] : q[7], o.w)),
                    rsb + SM_BAR + MB_VR);
          sts128(TQ(SM_VL), addb2(r ? q[4] : q[0], k.x), addb2(r ? q[5] : q[1], k.y), addb2(r ? q[6] : q[2], k.z), addb2(r ? q[7] : q[3], k.w));
          __syncwarp();
          if (l16 == 0) mbar_arrive(sb + SM_BAR + MB_VR);
          TSF(28, 5);
        }
      }
    }
  } else {
    asm volatile("setmaxnreg.dec.sync.aligned.u32 " STR(RF_CTL) ";");
    const int g = lane >> 2, tq = lane & 3;
    if (wq == 0) {
      if (lane < 12) asm volatile("prefetch.global.L2 [%0];" :: "l"(SP.x + (size_t)(cta * 12 + lane) * 64));
      __syncwarp();
      {
        SIDES();
        const uint32_t o[6] = {w_blk(w_h1(cta), me), w_blk(w_h1(cta) ^ H1_V, me), w_blk(w_mvx(cta, 0), me ^ sm2.z), w_blk(w_mvx(cta, 1), me ^ sm2.z),
                               w_blk(w_mxa(cta, 0), me ^ sm2.z), w_blk(w_mxa(cta, 1), me ^ sm2.z)};
#pragma unroll
        for (int i = 0; i < 24; i++) stg_r4(P.win + (o[i >> 2] + (i & 3) * 512 + lane * 16), 0u, 0u, 0u, 0u);
#pragma unroll
        for (int i = 0; i < 6; i++) stg_r1(P.win + (w_ar(i >> 1) + cta * 256 + (i & 1) * W_DS + lane * 4), 0u);
        __threadfence();
        __syncwarp();
      }
      {
        const uint32_t wv = movm(*reinterpret_cast<const uint32_t*>(P.mem0 + g * DM + cta * 8 + tq * 2));
        const bool sp = lane == cnt_word(cta & 31);
        stg_r1(P.win + (w_ar(-1) + cta * 256 + lane * 4), sp ? (wv & 0xffffu) | 0x42000000u : wv);
        if (sp) stg_r1(P.win + (w_ar(-1) + ((cta & ~9) + ((cta >> 1) & 1)) * 256 + W_DS + lane * 4), (wv >> 16) | 0x42000000u);
      }
      bar_sync(B_V, 160);
      if (lane == 0) {
        fence_async_smem(); mbar_arrive_cluster_rlx(mapa(sb + SM_BAR + MB_INIT, 0)); mbar_arrive_cluster_rlx(mapa(sb + SM_BAR + MB_INIT, 1));
        mbar_wait(sb + SM_BAR + MB_INIT, 0);
        mbar_expect_tx(sb + SM_BAR + MB_F, 32768);
        mbar_expect_tx(sb + SM_BAR + MB_F + 8, 32768);
        XLOAD(1, 0); XLOAD(0, 1);
        WLOAD(4 + WSPL, 8);
      }
      __syncwarp();
#ifdef PER
      if (lane == 0) atomicMax(&g_end[5], gt32());
#endif
    }
    bar_sync(B_X2, 256);
    SIDES();
    uint32_t l16 = __shfl_sync(~0u, lane * 16, lane);
    const uint32_t me2 = me ^ sm2.z;
    const float sc = 32.f * 0.08838834764831845f * 1.4426950408889634f;
    uint32_t ls = l16 + sb;
#define PVM(o, zs, p0, p2, M1, M2, M3) do { \
        FENCE(); \
        mma4z(zs, 0x3F803F80u, 0x3F803F80u, 0x3F803F80u, 0x3F803F80u, p0.x, p0.y); \
        FENCE(); M1; \
        _Pragma("unroll") for (int t = 0; t < 4; t++) mma4z(o[t], va[2 * t].x, va[2 * t].y, va[2 * t].z, va[2 * t].w, p0.x, p0.y); \
        FENCE(); M2; \
        mma4(zs, 0x3F803F80u, 0x3F803F80u, 0x3F803F80u, 0x3F803F80u, p0.z, p0.w); \
        _Pragma("unroll") for (int t = 0; t < 2; t++) mma4(o[t], va[2 * t + 1].x, va[2 * t + 1].y, va[2 * t + 1].z, va[2 * t + 1].w, p0.z, p0.w); \
        FENCE(); M3; \
        mma_1688(zs, 0x3F803F80u, 0x3F803F80u, p2); \
        _Pragma("unroll") for (int t = 2; t < 4; t++) mma4(o[t], va[2 * t + 1].x, va[2 * t + 1].y, va[2 * t + 1].z, va[2 * t + 1].w, p0.z, p0.w); \
        mma_1688(o[0], vm[0].x, vm[0].y, p2); mma_1688(o[1], vm[0].z, vm[0].w, p2); mma_1688(o[2], vm[1].x, vm[1].y, p2); mma_1688(o[3], vm[1].z, vm[1].w, p2); } while (0)
#define PVE(o, z, dst) do { \
        const float i0 = rcpf(z[0]), i1 = rcpf(z[1]); \
        _Pragma("unroll") for (int u = 0; u < 2; u++) \
          stsm4t(ls + (dst) + u * 1024, pack_bf16(o[2 * u][0] * i0, o[2 * u][1] * i1), pack_bf16(o[2 * u][2] * i0, o[2 * u][3] * i1), \
                 pack_bf16(o[2 * u + 1][0] * i0, o[2 * u + 1][1] * i1), pack_bf16(o[2 * u + 1][2] * i0, o[2 * u + 1][3] * i1)); } while (0)
    const uint32_t lq = (l16 ^ ((l16 >> 1) & 64u)) + sb, l12 = (l16 >> 2) * 3;
#define M3PTR(sl) \
            const uint32_t tf = me ^ 1 ^ r, m3i = w_ar(sl) + (wq & 1) * 16384 + (l16 & 0x70u) + ((l16 & 0x180u) << 1); \
            const unsigned char* p0f = P.win + (m3i + r * 8192 + tf * 4096); const unsigned char* p0n = P.win + (m3i + r * 8192 + (tf ^ 1) * 4096); \
            const unsigned char* p1f = P.win + (m3i + (r ^ 1) * 8192 + (tf ^ 1) * 4096); const unsigned char* p1n = P.win + (m3i + (r ^ 1) * 8192 + tf * 4096); \
            const unsigned char* pd = P.win + (w_ar(sl) + (wq & 1) * 16384 + (((l16 >> 7) ^ r) & 1u) * 8192 + ((l16 & 64u) * 4 + (l16 & 48u) * 2 + (l16 & 16u)) * 16 + W_DS + (l16 & 0x70u)); \
            uint32_t mf = ls + SM_MEM + (wq & 1) * 8192 + tf * 2048, mn = ls + SM_MEM + (wq & 1) * 8192 + (tf ^ 1) * 2048, nr = l16 < 256u ? 1u + (((l16 >> 6) ^ (l16 >> 7) ^ tf) & 1u) : 0u; \
            OPAQUE_L(p0f); OPAQUE_L(p0n); OPAQUE_L(p1f); OPAQUE_L(p1n); OPAQUE_L(pd); OPAQUE_R(mf); OPAQUE_R(mn); OPAQUE_R(nr); FENCE()
#define M3REQ() \
            _Pragma("unroll") for (int i = 0; i < 4; i++) { cp16(mn + 4096 + i * 512, p1f + i * 1024); cp16(mf + i * 512, p0f + i * 1024); } \
            cp16p(ls + SM_RD + (wq & 1) * 256, pd, nr & 1u); \
            _Pragma("unroll") for (int i = 0; i < 4; i++) { cp16(mf + 4096 + i * 512, p1n + i * 1024); cp16(mn + i * 512, p0n + i * 1024); } \
            cp16p(ls + SM_RD + (wq & 1) * 256, pd, nr & 2u)
    if (wq >= 2) { M3PTR(-1); M3REQ(); }
    if (wq == 0) {
      bar_sync(B_P, 160);
      if (l16 == 0) {
        fence_async_smem();
        mbar_expect_tx(sb + SM_BAR + MB_WO, 65536);
        for (int i = 0; i < 8; i++) tma_load_2d(sb + SM_WOS + i * 8192, &tmw, j * 256 + ((i >> 1) ^ (2 * sw)) * 64, h * DH + (i & 1) * 64, sb + SM_BAR + MB_WO);
      }
      __syncwarp();
    }
#define ETA(k, first) ETAT(gt32() + (k), first)
#define ETAT(tm, first) do { unsigned char* pt = P.win + (w_ar(s) + (W_DS + 256) + (cta >> 5) * 8192 + ((cta >> 4) & 1) * 2048 + (l16 & 16u) * 256); \
          asm volatile("{\n.reg .pred q;\nsetp.lt.u32 q, %2, 32;\n@q red.relaxed.gpu.global.max.u32 [%0+4], %1;\n}" :: "l"(pt), "r"(tm), "r"(l16) : "memory"); \
          if (first) asm volatile("{\n.reg .pred q;\nsetp.lt.u32 q, %1, 32;\n@q red.relaxed.gpu.global.add.u32 [%0], 1;\n}" :: "l"(pt), "r"(l16) : "memory"); } while (0)
    if (wq == 1) {
      const uint32_t xin = w_blk(w_mxa(cta, 0), me2) + l16;
      const uint32_t lsq = sb + ((l16 & 0x70u) | ((l16 & 0x80u) << 1) | ((l16 & 0x100u) >> 1));
      mbar_wait(sb + SM_BAR + MB_MEM, 0); mbar_wait(sb + SM_BAR + MB_MEM + 8, 0);
      for (int s = 0; s < NSEG; s++) {
        const uint32_t t2 = ((s >> 1) & 1) ^ 1;
        mbar_wait(sb + SM_BAR + MB_XF, s & 1);
        {
        uint4 kx[4], qx[4];
#pragma unroll
        for (int i = 0; i < 4; i++) { kx[i] = ldsm4(ls + (SM_XF + (4 + i) * 512)); qx[i] = ldsm4(lsq + (SM_XF + i * 512)); }
        const uint32_t db = w_blk(w_mxa(h * 4, s), me2) + l16 - 512;
        {
          float S[2][4][4];
          if (XG == 2 && s > 0) bar_arrive(B_O2, 224);
          FENCE();
#pragma unroll
          for (int mt = 0; mt < 2; mt++) {
            const uint4 q0 = qx[mt];
            mma4z(S[mt][0], q0.x, q0.y, q0.z, q0.w, kx[0].x, kx[0].y); mma4z(S[mt][1], q0.x, q0.y, q0.z, q0.w, kx[0].z, kx[0].w);
            mma4z(S[mt][2], q0.x, q0.y, q0.z, q0.w, kx[1].x, kx[1].y); mma4z(S[mt][3], q0.x, q0.y, q0.z, q0.w, kx[1].z, kx[1].w);
          }
#pragma unroll
          for (int mt = 0; mt < 2; mt++) {
            const uint4 q1 = qx[2 + mt];
            mma4(S[mt][0], q1.x, q1.y, q1.z, q1.w, kx[2].x, kx[2].y); mma4(S[mt][1], q1.x, q1.y, q1.z, q1.w, kx[2].z, kx[2].w);
            mma4(S[mt][2], q1.x, q1.y, q1.z, q1.w, kx[3].x, kx[3].y); mma4(S[mt][3], q1.x, q1.y, q1.z, q1.w, kx[3].z, kx[3].w);
          }
          FENCE();
          if (XG == 1 && s > 0) bar_arrive(B_O2, 224);
          FENCE();
#pragma unroll
          for (int u = 0; u < 4; u++) {
            const int mt = u >> 1, c = 2 * (u & 1);
            const uint32_t m0 = tagw(pack_f16(S[mt][0][c], S[mt][0][c + 1]), t2), m1 = pack_f16(S[mt][1][c], S[mt][1][c + 1]),
                           m2 = pack_f16(S[mt][2][c], S[mt][2][c + 1]), m3 = pack_f16(S[mt][3][c], S[mt][3][c + 1]);
            const int e = u ^ j;
            if (e) stg_r4(P.win + (db + mt * 16384 + (u & 1) * 2048 + e * 512), m0, m1, m2, m3);
            else sts128(ls + SM_XS, m0, m1, m2, m3);
          }
        }
        TS(15);
        float sx[10];
        const unsigned char* pa = P.win + (xin + ((s & 1) << 20));
        uint4 xv[3];
        if (s > 0) spin(DLY_XD);
#pragma unroll
        for (int i = 0; i < 3; i++) xv[i] = ldg_r4(pa + i * 512);
        FENCE();
        int n = 0; float mx;
        auto xsum = [&]() {
#pragma unroll 1
        while (__any_sync(~0u, (x3(xv[0].x, xv[1].x, t2) | (xv[2].x ^ t2)) & 1u) && ++n < SPIN_LIMIT) {
#pragma unroll
          for (int i = 0; i < 3; i++) xv[i] = ldg_r4(pa + i * 512);
        }
        {
          const uint4 v3 = lds128(ls + SM_XS);
          sum_h4(sx[2], sx[3], xv[0].x, xv[1].x, xv[2].x, v3.x); sum_h4(sx[4], sx[5], xv[0].y, xv[1].y, xv[2].y, v3.y);
          sum_h4(sx[6], sx[7], xv[0].z, xv[1].z, xv[2].z, v3.z); sum_h4(sx[8], sx[9], xv[0].w, xv[1].w, xv[2].w, v3.w);
          const int row = 8 * j + g - 2 * tq;
#pragma unroll
          for (int i = 0; i < 8; i++) if ((i >> 1) * 8 + (i & 1) > row) sx[2 + i] = -INFINITY;
        }
        mx = fmaxf(fmaxf(fmaxf(sx[2], sx[3]), fmaxf(sx[4], sx[5])), fmaxf(fmaxf(sx[6], sx[7]), fmaxf(sx[8], sx[9])));
        };
        if (!Z0 || s > 0) xsum();
        else {
#pragma unroll
          for (int i = 2; i < 10; i++) sx[i] = 0.f;
          mx = 0.f;
        }
        sts32(ls - l12 + SM_XS + 512, f2u(mx));
        {
          if (l16 == 0) mbar_expect_tx(sb + SM_BAR + MB_VR, 2048);
          unsigned char* d = P.win + (w_blk(w_mvx(cta, s), me2) + l16);
          OPAQUE_L(d); FENCE();
          mbar_wait(sb + SM_BAR + MB_VR, s & 1);
#pragma unroll
          for (int t = 0; t < 4; t++) {
            const uint4 a0 = lds128(ls + (SM_VL + t * 512)), a1 = lds128(ls + (SM_VR + t * 512));
            stg_r4(d + t * 512, tagw(addb2(a0.x, a1.x), t2), addb2(a0.y, a1.y), addb2(a0.z, a1.z), addb2(a0.w, a1.w));
          }
          TS(23);
        }
        unsigned char* pm = P.win + (db + 2048 + j * 128 - l12);
        const unsigned char* py = pa + 1536 - l12;
        OPAQUE_L(pm); OPAQUE_L(py);
        if (s > 0) bar_sync(B_PXF, 96);
        FENCE();
        bar_sync(B_QK1, 288);
        uint32_t kb[2][2];
#pragma unroll
        for (int t = 0; t < 2; t++) {
          const float4 u = lds128f(lq + (SM_QKP + (2 + t) * 512)), v4 = lds128f(lq + (SM_QKP + 2048 + (2 + t) * 512));
          kb[t][0] = pack_bf16(u.x + v4.x, u.y + v4.y); kb[t][1] = pack_bf16(u.z + v4.z, u.w + v4.w);
        }
        float S[2][4];
#pragma unroll
        for (int mt = 0; mt < 2; mt++) mma4z(S[mt], qx[mt].x, qx[mt].y, qx[mt].z, qx[mt].w, kb[0][0], kb[0][1]);
#pragma unroll
        for (int mt = 0; mt < 2; mt++) mma4(S[mt], qx[2 + mt].x, qx[2 + mt].y, qx[2 + mt].z, qx[2 + mt].w, kb[1][0], kb[1][1]);
        PT(14, s == 0 && l16 == 0);
        if (!Z1 && s == 0) mbar_wait(sb + SM_BAR + MB_WO, 0);
        PT(15, s == 0 && l16 == 0);
        if (s < NSEG - 1) bar_arrive(B_PUB, 320);
        FENCE();
#pragma unroll
        for (int u = 0; u < 4; u++) stg_r1(pm + (u >> 1) * 16384 + (u & 1) * 2048, tagw(pack_f16(S[u >> 1][2 * (u & 1)], S[u >> 1][2 * (u & 1) + 1]), t2));
        TS(30);
        FENCE();
        if (Z0 && s == 0) xsum();
        spin(DLY_XL);
        uint32_t xy[4];
#pragma unroll
        for (int i = 0; i < 4; i++) xy[i] = ldg_r1(py + i * 128);
        FENCE();

        n = 0;
#pragma unroll 1
        while (__any_sync(~0u, (x3(xy[0], xy[1], t2) | x3(xy[2], xy[3], t2)) & 1u) && ++n < SPIN_LIMIT) {
#pragma unroll
          for (int i = 0; i < 4; i++) xy[i] = ldg_r1(py + i * 128);
        }
        sum_h4(sx[0], sx[1], xy[0], xy[1], xy[2], xy[3]);
        mx = fmaxf(mx, fmaxf(sx[0], sx[1]));
        mx = fmaxf(fmaxf(mx, __shfl_xor_sync(~0u, mx, 1)), fmaxf(__shfl_xor_sync(~0u, mx, 2), __shfl_xor_sync(~0u, mx, 3)));
#pragma unroll
        for (int i = 0; i < 10; i++) sx[i] = ex2(fmaf(sx[i], sc, -sc * mx));
        sts128(ls + SM_PX, pack_bf16(sx[2], sx[3]), pack_bf16(sx[4], sx[5]), pack_bf16(sx[6], sx[7]), pack_bf16(sx[8], sx[9]));
        sts32(ls - l12 + SM_PX + 512, pack_bf16(sx[0], sx[1]));
        bar_arrive(B_PX, 96);
        TS(1);
        }
      }
    } else {
      const uint32_t ho = (wq & 1) * 512 + l16, hv = wq == 0 ? 0u : H1_V;
      uint32_t ow = w_blk(w_h1(cta) ^ hv, me) + ho, or0 = w_blk(w_h1(cta ^ 1) ^ hv, me) + ho, or1 = w_blk(w_h1((cta ^ 2) & ~1) ^ hv, me) + ho;
#define PTRS() OPAQUE_R(ow); OPAQUE_R(or0); OPAQUE_R(or1); \
      unsigned char* pw0 = P.win + ow; const unsigned char* pr0 = P.win + or0; const unsigned char* pr1 = P.win + or1; \
      OPAQUE_L(pw0); OPAQUE_L(pr0); OPAQUE_L(pr1); FENCE()
      if (wq == 0) {
        const uint32_t xcnt = me ? NCTA - nlo : nlo, xrank = (me ? cta - nlo : cta) + lane * xcnt;
        int kd = DLY_K;
        mbar_wait(sb + SM_BAR + MB_XE1, 0);
        if (l16 == 0) { mbar_expect_tx(sb + SM_BAR + MB_F + 8, 32768); XLOAD(1, 1); }
        __syncwarp();
        for (int s = 0; s < NSEG - 1; s++) {
          const uint32_t tg = (s & 1) ^ 1;
          mbar_wait(sb + SM_BAR + MB_XF, s & 1);
          uint4 xf[4];
#pragma unroll
          for (int i = 0; i < 4; i++) xf[i] = ldsm4(ls + (SM_XF + (4 + i) * 512));
          PTRS();
          unsigned char* pw1 = pw0 + 512 - l12; OPAQUE_L(pw1);
          bar_sync(B_QK, 288);
          float4 u[4], v4[4];
#pragma unroll
          for (int t = 0; t < 4; t++) { u[t] = lds128f(lq + (SM_QKP + t * 512)); v4[t] = lds128f(lq + (SM_QKP + 2048 + t * 512)); }
          FENCE();
          uint32_t f[4][2], m[5];
#pragma unroll
          for (int t = 0; t < 2; t++) { f[t][0] = pack_bf16(u[t].x + v4[t].x, u[t].y + v4[t].y); f[t][1] = pack_bf16(u[t].z + v4[t].z, u[t].w + v4[t].w); }
          float S[5][4], T[5][4];
          mma4z(S[1], f[0][0], f[1][0], f[0][1], f[1][1], xf[0].x, xf[0].y); mma4z(T[1], f[0][0], f[1][0], f[0][1], f[1][1], xf[2].x, xf[2].y);
          mma4z(S[2], f[0][0], f[1][0], f[0][1], f[1][1], xf[0].z, xf[0].w); mma4z(T[2], f[0][0], f[1][0], f[0][1], f[1][1], xf[2].z, xf[2].w);
          FENCE();
#pragma unroll
          for (int t = 2; t < 4; t++) { f[t][0] = packv(u[t].x, v4[t].x, u[t].y, v4[t].y); f[t][1] = packv(u[t].z, v4[t].z, u[t].w, v4[t].w); }
          mma4z(S[3], f[0][0], f[1][0], f[0][1], f[1][1], xf[1].x, xf[1].y); mma4z(T[3], f[0][0], f[1][0], f[0][1], f[1][1], xf[3].x, xf[3].y);
          mma4z(S[4], f[0][0], f[1][0], f[0][1], f[1][1], xf[1].z, xf[1].w); mma4z(T[4], f[0][0], f[1][0], f[0][1], f[1][1], xf[3].z, xf[3].w);
          FENCE();
          mma4z(S[0], f[0][0], f[1][0], f[0][1], f[1][1], f[2][0], f[2][1]); mma4z(T[0], f[0][0], f[1][0], f[0][1], f[1][1], f[3][0], f[3][1]);
          bar_arrive(B_PUB, 320);
          FENCE();
#if SO
#pragma unroll
          for (int i = 1; i < 5; i++) m[i] = packh(S[i][0], T[i][2], S[i][1], T[i][3]);
          m[1] = tagw(m[1], tg);
          stg_r4(pw0, m[1], m[2], m[3], m[4]);
          FENCE();
          m[0] = tagw(packh(S[0][0], T[0][2], S[0][1], T[0][3]), tg);
          stg_r1(pw1, m[0]);
#else
#pragma unroll
          for (int i = 1; i < 5; i++) m[i] = pack_f16(S[i][0] + T[i][2], S[i][1] + T[i][3]);
          stg_r4(pw0, tagw(m[1], tg), m[2], m[3], m[4]);
          m[0] = pack_f16(S[0][0] + T[0][2], S[0][1] + T[0][3]);
          stg_r1(pw1, tagw(m[0], tg));
#endif
          TS(6); PT(11, s == 0 && l16 == 0);
          FENCE();
          const uint32_t ts = clk32();
          uint32_t te = gt32() + kd;
          const unsigned char* py0 = pr0 + 512 - l12; const unsigned char* py1 = pr1 + 512 - l12;
          OPAQUE_L(py0); OPAQUE_L(py1);
          unsigned char* pt = P.win + (w_ar(s) + (W_DS + 256) + (cta >> 5) * 8192 + ((cta >> 4) & 1) * 2048 + (l16 & 16u) * 256);
          OPAQUE_L(pt);
          if (l16 == 0) mbar_expect_tx(sb + SM_BAR + MB_F, s < NSEG - 2 ? 32768 : 0);
          FENCE();
          while (clk32() - ts < (uint32_t)DLY_S) {}
          {
            float sx[10]; uint32_t x, x1, x2, x3_; int n = 0; bool bad;
#pragma unroll 1
            do {
              uint4 v[3]; uint32_t y[3], t[5];
              v[0] = ldg_r4(pr0); v[1] = ldg_r4(pr1); v[2] = ldg_r4(pr1 + 2048);
              y[0] = ldg_r1(py0); y[1] = ldg_r1(py1); y[2] = ldg_r1(py1 + 2048);
              if (n) te = gt32() + DLY_KS;
              eta2(pt, te, n == 0, l16);
              n++;
              FENCE();
#define Q3(o, a, b, c) hadd2(hadd2(o, a), hadd2(b, c))
              t[1] = Q3(m[1], v[0].x, v[1].x, v[2].x); t[2] = Q3(m[2], v[0].y, v[1].y, v[2].y); t[3] = Q3(m[3], v[0].z, v[1].z, v[2].z); t[4] = Q3(m[4], v[0].w, v[1].w, v[2].w);
              t[0] = Q3(m[0], y[0], y[1], y[2]);
              bad = __any_sync(~0u, or3(x3(v[0].x, v[1].x, tg), x3(v[2].x, y[0], tg), x3(y[1], y[2], tg)) & (n < SPIN_LIMIT ? 1u : 0u));
              x = hmax2(hmax2(hmax2(t[1], t[2]), hmax2(t[3], t[4])), t[0]);
              const float2 xm = __half22float2(*reinterpret_cast<__half2*>(&x));
              x = f2u(fmaxf(xm.x, xm.y) * -sc);
              x1 = shfl_x(x, 1); x2 = shfl_x(x, 2); x3_ = shfl_x(x, 3);
              FENCE();
#if OS
#pragma unroll
              for (int i = 1; i < 6; i++) {
                h2f(sx[2 * (i % 5)], sx[2 * (i % 5) + 1], t[i % 5]);
                sx[2 * (i % 5)] = ex2v(sx[2 * (i % 5)], sc, u2f(x)); sx[2 * (i % 5) + 1] = ex2v(sx[2 * (i % 5) + 1], sc, u2f(x));
              }
              FENCE();
            } while (bad);
            const float cr = ex2(fminf(fminf(u2f(x), u2f(x1)), fminf(u2f(x2), u2f(x3_))) - u2f(x));
#pragma unroll
            for (int i = 1; i < 6; i++) m[i % 5] = pack_bf16(sx[2 * (i % 5)] * cr, sx[2 * (i % 5) + 1] * cr);
#else
#pragma unroll
              for (int i = 1; i < 6; i++) h2f(sx[2 * (i % 5)], sx[2 * (i % 5) + 1], t[i % 5]);
              FENCE();
            } while (bad);
            const float mx = fminf(fminf(u2f(x), u2f(x1)), fminf(u2f(x2), u2f(x3_)));
#pragma unroll
            for (int i = 2; i < 12; i++) sx[i % 10] = ex2v(sx[i % 10], sc, mx);
#pragma unroll
            for (int i = 1; i < 6; i++) m[i % 5] = pack_bf16(sx[2 * (i % 5)], sx[2 * (i % 5) + 1]);
#endif
            sts128(ls + SM_PF, m[1], m[2], m[3], m[4]);
            sts32(ls - l12 + SM_PF + 512, m[0]);
            TV(19, n - 1);
          }
          TS(12);
          bar_sync(B_P, 96);
          PT(12, s == 0 && l16 == 0);
          OPAQUE_R(l16);
          {
            const unsigned char* pe = P.win + w_blk(w_ar(s) + (W_DS + 256) + (l16 & 0x60u) * 256 + (l16 & 16u) * 128, me);
            const uint32_t tp = gt32() + DLY_M3;
            if (s < NSEG - 2) F0LOAD();
            ETAT(tp, 0);
            uint32_t tg0; int n = 0;
#pragma unroll 1
            for (;;) {
              const uint2 e = ldg_r2(pe);
              tg0 = __reduce_max_sync(~0u, e.y);
              if (tg0 - tp >= 4096u) tg0 = tp;
              if ((!__any_sync(~0u, e.x != 16u) && (int)(tg0 - gt32()) < DLY_RR) || ++n >= SPIN_LIMIT) break;
            }
            sts32(sb + SM_Z + 32, tg0);
            TV(16, tg0); TV(7, kd - DLY_K);
            bar_arrive(B_GO, 96);
          }
          if (s < NSEG - 2) {
            mbar_wait(sb + SM_BAR + MB_XE1, (s + 1) & 1);
            if (l16 == 0) mbar_expect_tx(sb + SM_BAR + MB_F + 8, 32768);
            mbar_wait(sb + SM_BAR + MB_MEM, (s + 1) & 1); mbar_wait(sb + SM_BAR + MB_MEM + 8, (s + 1) & 1);
            if (l16 == 0) XLOAD(1, s + 2);
            __syncwarp();
          }
          if (XPF && s + XPF < NSEG) {
            for (uint32_t i = xrank; i < 512; i += 32 * xcnt)
              asm volatile("prefetch.global.L2 [%0];" :: "l"(SP.x + (size_t)(s + XPF) * (SEG * DM) + i * 64));
            __syncwarp();
          }
          stg_2(P.win + (w_ar(s + 2) + cta * 256 + (l16 >> 8) * W_DS + ((l16 >> 1) & 127u)), 0u, 0u);
          kd = lds32(sb + SM_Z + 40) == (uint32_t)(s + 1) ? min(kd + KU, DLY_K + 256) : max(kd - KD, DLY_K);
          kd = __shfl_sync(~0u, kd, l16 >> 4);
#ifdef PER
          if (l16 == 0) { g_per[cta][s] = gt32(); g_pclk[cta][s] = clk32(); g_pk[cta][s] = kd - DLY_K; }
#endif
        }
        bar_sync(B_QK, 288);
      } else {
        const int mt = wq - 2;
        const uint32_t lt = ls + mt * 1024;
        const uint32_t vi0 = w_blk(w_mvx(h * 4, 0), me2) + mt * 1024;
        const int m3d = r ? -8192 : 8192;
#ifdef PROF
        const uint32_t epoch = gt32(); TST(-1, 30 + mt, l16, epoch);
#endif
        float ox[4][4], zx[4];
#pragma unroll
        for (int i = 0; i < 16; i++) ox[i >> 2][i & 3] = zx[i & 3] = 1.f;
        for (int s = 0;; s++) {
          const uint32_t tg = (s & 1) ^ 1, t2 = ((s >> 1) & 1) ^ 1;
          {
            OPAQUE_R(l16);
            const uint32_t m3i = (mt * 2 + r) * 8192 + (l16 & 0x70u) + ((l16 & 0x180u) << 1);
            const uint32_t m3j = (mt * 2 + (r ^ (l16 >> 7 & 1))) * 8192 + ((l16 & 64u) * 4 + (l16 & 48u) * 2 + (l16 & 16u)) * 16 + W_DS + (l16 & 0x70u);
            uint32_t m3c = sb + SM_MEM + mt * 8192 + cnt_line(l16 >> 4) * 128 + (l16 >> 2);
            const unsigned char* p3 = P.win + (m3i + w_ar(s - 1)); const unsigned char* pd = P.win + (m3j + w_ar(s - 1));
            OPAQUE_L(pd); OPAQUE_R(m3c);
#define XEPI() do {        \
              PVE(ox, zx, SM_OX + mt * 512); \
              __syncwarp(); \
              const uint32_t oa = sb + SM_OX + mt * 512 + ((l16 & 48u) << 3) + ((l16 >> 2) & 0x70u); \
              const uint4 a = lds128(oa), b = lds128(oa + 1024); \
              unsigned char* o = reinterpret_cast<unsigned char*>(g_ox + (size_t)((s - 1) * SEG + 8 * j) * (NH * DH) + h * DH + mt * 32) + ((l16 >> 6) * (NH * DH * 2) + (l16 & 48u)); \
              stg_4(o, a); stg_4(o + 128, b); \
              TST(s - 1, 18, l16 | mt, TCLK()); } while (0)
            if (s > 0) XEPI();
            if (s == NSEG) break;
            if (s > 0) {
              M3PTR(s - 1);
              bar_sync(B_GO, 96);
              const uint32_t tg0 = lds32(sb + SM_Z + 32);
              while (tg0 - gt32() - 1u < 8192u) {}
              M3REQ();
            }
            FENCE();
            const int n = m3_check(sb, p3, pd, m3d, l16, m3c, mt, s);
            FENCE();
            TST(s, mt ? 21 : 0, l16, TCLK());
            TST(s, mt ? 22 : 17, l16, n);
            PT(6 + s, s < 5 && (l16 | mt) == 0);
          }
          uint4 va[8], vm[2], p0, q0; uint32_t p2, q2;
          const unsigned char* a0 = P.win + (vi0 + ((s & 1) << 20) + l16);
#define VALD() _Pragma("unroll") for (int i = 0; i < 4; i++) { va[i] = ldg_r4(a0 + (i >> 1) * 512 + (i & 1) * 2048); va[4 + i] = ldg_r4(a0 + 16384 + (i >> 1) * 512 + (i & 1) * 2048); }
          spin(DLY_WO);
          VALD();
          {
          PTRS();
          bar_sync(B_V, 320);
            const float4 u0 = lds128f(lt + SM_VP), w0 = lds128f(lt + SM_VP + 2048), u1 = lds128f(lt + SM_VP + 512), w1 = lds128f(lt + SM_VP + 2560);
            const uint32_t m0 = tagw(pack_bf16(u0.x + w0.x, u0.y + w0.y), tg), m1 = pack_bf16(u0.z + w0.z, u0.w + w0.w),
                           m2 = pack_bf16(u1.x + w1.x, u1.y + w1.y), m3 = pack_bf16(u1.z + w1.z, u1.w + w1.w);
            stg_r4(pw0, m0, m1, m2, m3);
            if (wq == 2) TS(10);
            FENCE();
            const uint32_t tv = clk32();
            while (clk32() - tv < (uint32_t)DLY_V) {}
            uint4 v[3]; int n = 0; uint32_t bada = 0;
#pragma unroll 1
            do {
              v[0] = ldg_r4(pr0); v[1] = ldg_r4(pr1); v[2] = ldg_r4(pr1 + 2048);
              if (n) {
                TST(s, __any_sync(~0u, bada & 1u) ? 26 : 24, l16, epoch);
                if (__any_sync(~0u, bada & 1u)) { VALD(); }
                if (s < NSEG - 1) ETA(DLY_KS - 192, 0);
              }
              n++;
              FENCE();
              bada = or3(x3(va[0].x, va[1].x, t2), x3(va[2].x, va[3].x, t2), x3(va[4].x, va[5].x, t2)) | x3(va[6].x, va[7].x, t2);
            } while (__any_sync(~0u, or3(bada, x3(v[0].x, v[1].x, tg), v[2].x ^ tg) & 1u) && n < SPIN_LIMIT);
            const uint4 A = make_uint4(addb2(m0, v[0].x), addb2(m1, v[0].y), addb2(m2, v[0].z), addb2(m3, v[0].w));
            const uint4 B = make_uint4(addb2(v[1].x, v[2].x), addb2(v[1].y, v[2].y), addb2(v[1].z, v[2].z), addb2(v[1].w, v[2].w));
            vm[0] = p ? B : A; vm[1] = p ? A : B;
            TST(s, 11, l16 | mt, TCLK()); TST(s, 29, l16 | (mt ^ 1), TCLK());
          }
          FENCE();
          if (s < NSEG - 1) {
          bar_sync(B_P, 96);
          p0 = lds128(ls + SM_PF); p2 = lds32(ls - l12 + SM_PF + 512);
          float o[4][4], z[4];
          PVM(o, z, p0, p2, , , );
          PVE(o, z, SM_OF + mt * 512);
          bar_arrive(B_O, 192);
          }
          FENCE();
          TST(s, 8, l16 | mt, TCLK());
          bar_sync(B_PX, 96);
          q0 = lds128(ls + SM_PX); q2 = lds32(ls - l12 + SM_PX + 512);
#define O2A(k) if (O2P == k) { if (s < NSEG - 1) bar_arrive(B_O2, XG ? 224 : 192); FENCE(); }
          O2A(0);
          PVM(ox, zx, q0, q2, O2A(1), O2A(2), O2A(3));
          O2A(4);
          FENCE();
          if (s < NSEG - 1) bar_arrive(B_PXF, 96);
        }
      }
    }
  }
  asm volatile("barrier.cluster.arrive.relaxed.aligned;\nbarrier.cluster.wait.aligned;" ::: "memory");
#ifdef PER
  if (threadIdx.x == 0) atomicMax(&g_end[0], gt32());
#endif
}
#ifndef PW
#define PW 2
#endif
#ifndef G2_PD
#define G2_PD 300
#endif
#ifndef G2_HD
#define G2_HD 8000
#endif
#ifndef G2_ST
#define G2_ST 6
#endif
#define G2_TB (G2_ST * 32768 + 1024)
#define G2_SMEM (G2_TB + 32768)
template <int AOFF, int BOFF>
static __device__ __forceinline__ void wgmma_n128_ta(float (&d)[64], uint32_t a16, uint32_t b16) {
  asm volatile(
      "{\n.reg .b32 t, u;\n.reg .b64 da, db;\nadd.u32 t, %64, %66;\nmov.b64 da, {t, %68};\nadd.u32 u, %65, %67;\nmov.b64 db, {u, %68};\n"
      "wgmma.mma_async.sync.aligned.m64n128k16.f32.bf16.bf16 "
      "{%0,%1,%2,%3,%4,%5,%6,%7,%8,%9,%10,%11,%12,%13,%14,%15,%16,%17,%18,%19,%20,%21,%22,%23,%24,%25,%26,%27,%28,%29,%30,%31,"
      "%32,%33,%34,%35,%36,%37,%38,%39,%40,%41,%42,%43,%44,%45,%46,%47,%48,%49,%50,%51,%52,%53,%54,%55,%56,%57,%58,%59,%60,%61,%62,%63}, "
      "da, db, 1, 1, 1, 1, 0;\n}"
      : "+f"(d[0]), "+f"(d[1]), "+f"(d[2]), "+f"(d[3]), "+f"(d[4]), "+f"(d[5]), "+f"(d[6]), "+f"(d[7]), "+f"(d[8]), "+f"(d[9]), "+f"(d[10]), "+f"(d[11]),
        "+f"(d[12]), "+f"(d[13]), "+f"(d[14]), "+f"(d[15]), "+f"(d[16]), "+f"(d[17]), "+f"(d[18]), "+f"(d[19]), "+f"(d[20]), "+f"(d[21]), "+f"(d[22]), "+f"(d[23]),
        "+f"(d[24]), "+f"(d[25]), "+f"(d[26]), "+f"(d[27]), "+f"(d[28]), "+f"(d[29]), "+f"(d[30]), "+f"(d[31]), "+f"(d[32]), "+f"(d[33]), "+f"(d[34]), "+f"(d[35]),
        "+f"(d[36]), "+f"(d[37]), "+f"(d[38]), "+f"(d[39]), "+f"(d[40]), "+f"(d[41]), "+f"(d[42]), "+f"(d[43]), "+f"(d[44]), "+f"(d[45]), "+f"(d[46]), "+f"(d[47]),
        "+f"(d[48]), "+f"(d[49]), "+f"(d[50]), "+f"(d[51]), "+f"(d[52]), "+f"(d[53]), "+f"(d[54]), "+f"(d[55]), "+f"(d[56]), "+f"(d[57]), "+f"(d[58]), "+f"(d[59]),
        "+f"(d[60]), "+f"(d[61]), "+f"(d[62]), "+f"(d[63])
      : "r"(a16), "r"(b16), "n"(AOFF >> 4), "n"(BOFF >> 4), "n"(DESC_HI(1024)));
}
__global__ void __cluster_dims__(2, 1, 1) __launch_bounds__(384, 1)
gemm2_kernel(const __grid_constant__ CUtensorMap tmo, const __grid_constant__ CUtensorMap tmw, const bf16* __restrict__ x, bf16* __restrict__ out, unsigned char* win) {
  extern __shared__ __align__(1024) unsigned char smem[];
  const uint32_t sb = smem_u32(smem), bars = sb + G2_ST * 32768;
  const int tid = threadIdx.x, lane = tid & 31, warp = __shfl_sync(~0u, tid >> 5, 0);
  const int r = blockIdx.x & 1, n0 = (blockIdx.x & 7) * 128, m0 = (blockIdx.x >> 3) * 128;
  if (tid == 0) {
    for (int i = 0; i < G2_ST; i++) { mbar_init(bars + i * 8, 1); mbar_init(bars + 64 + i * 8, 4); }
    asm volatile("fence.mbarrier_init.release.cluster;" ::: "memory");
  }
  if (tid == 32) { asm volatile("prefetch.tensormap [%0];" :: "l"(&tmw) : "memory"); asm volatile("prefetch.tensormap [%0];" :: "l"(&tmo) : "memory"); }
  __syncthreads();
  asm volatile("barrier.cluster.arrive.relaxed.aligned;" ::: "memory");
#define LW(kt, st) asm volatile("cp.async.bulk.tensor.3d.shared::cluster.global.mbarrier::complete_tx::bytes [%0], [%1, {%3, %4, %5}], [%2];" \
                     :: "r"(sb + (st) * 32768), "l"(&tmw), "r"(bars + (st) * 8), "r"(0), "r"((kt) * 64), "r"(n0 >> 6) : "memory")
#define LO(kt, st) asm volatile("cp.async.bulk.tensor.2d.shared::cluster.global.mbarrier::complete_tx::bytes.multicast::cluster [%0], [%1, {%3, %4}], [%2], %5;" \
                     :: "r"(sb + (st) * 32768 + 16384 + r * 8192), "l"(&tmo), "r"(bars + (st) * 8), "r"((kt) * 64), "r"(m0 + r * 64), "h"((uint16_t)3) : "memory")
  if (tid == 256) for (int kt = 0; kt < G2_ST; kt++) { mbar_expect_tx(bars + kt * 8, 32768); if (kt < PW) LW(kt, kt); }
  __syncwarp();
  asm volatile("barrier.cluster.wait.acquire.aligned;" ::: "memory");
  if (warp == 8) {
    if (lane == 0) {
      asm volatile("griddepcontrol.wait;" ::: "memory");
      for (int kt = 0; kt < G2_ST; kt++) { LO(kt, kt); if (kt >= PW) LW(kt, kt); spin(G2_PD); }
#pragma unroll 1
      for (int kt = G2_ST, st = 0, ph = 0; kt < 64; kt++) {
        mbar_wait(bars + 64 + st * 8, ph);
        mbar_expect_tx(bars + st * 8, 32768);
        LO(kt, st); LW(kt, st);
        if (++st == G2_ST) { st = 0; ph ^= 1; }
      }
    }
  } else if (warp > 8) {
    const int t = tid - 288, ch = t & 15;
    asm volatile("griddepcontrol.wait;" ::: "memory");
#ifdef PER
    if (t == 0) atomicMax(&g_end[3], gt32());
#endif
    spin(G2_HD);
    int idx[8];
#pragma unroll
    for (int c = 0; c < 8; c++) idx[c] = g_idx[c];
    const int gi = blockIdx.x * 96 + t;
    if (gi < 67) g_side[gi * 32] = 0u;
    if (gi == 0) g_sbar = 0u;
#pragma unroll 4
    for (int row = t >> 4; row < 128; row += 6) {
      const int tok = m0 + row;
      const uint4 xv = *reinterpret_cast<const uint4*>(x + (size_t)tok * DM + n0 + ch * 8);
      const float g = g_gate[tok], omg = rbf(1.f - g);
      int sel = -1;
#pragma unroll
      for (int c = 0; c < 8; c++) if (idx[c] == tok) sel = c;
      uint4 uv = make_uint4(0u, 0u, 0u, 0u);
      if (sel >= 0) uv = *reinterpret_cast<const uint4*>(g_upd + sel * DM + n0 + ch * 8);
      const uint32_t x4[4] = {xv.x, xv.y, xv.z, xv.w}, u4[4] = {uv.x, uv.y, uv.z, uv.w};
      uint32_t o4[4];
#pragma unroll
      for (int e = 0; e < 4; e++) {
        const float b0 = rbf(u2f(x4[e] << 16) + u2f(u4[e] << 16)), b1 = rbf(u2f(x4[e] & 0xffff0000u) + u2f(u4[e] & 0xffff0000u));
        o4[e] = pack_bf16(omg * b0, omg * b1);
      }
      sts128(sb + G2_TB + row * 256 + ch * 16, o4[0], o4[1], o4[2], o4[3]);
      if (ch == 0) sts32(bars + 512 + row * 4, pack_bf16(g, g));
    }
    bar_arrive(2, 352);
  } else {
    const int wg = warp >> 2;
    float d[64];
#pragma unroll
    for (int i = 0; i < 64; i++) d[i] = 0.f;
    const uint32_t e0 = mapa(bars + 64, 0), e1 = mapa(bars + 64, 1);
#ifdef PER
    if (threadIdx.x == 0) { mbar_wait(bars, 0); atomicMax(&g_end[4], gt32()); }
    __syncwarp();
#endif
    const uint32_t a16 = (((sb + wg * 8192) & 0x3FFFF) >> 4) | (64u << 16), b16 = (((sb + 16384) & 0x3FFFF) >> 4) | (1u << 16);
#pragma unroll 1
    for (int kt = 0, st = 0, ph = 0, ps = -1; kt < 64; kt++) {
      mbar_wait(bars + st * 8, ph);
      wg_fence();
      wgmma_n128_ta<0, 0>(d, a16 + st * 2048, b16 + st * 2048); wgmma_n128_ta<2048, 32>(d, a16 + st * 2048, b16 + st * 2048);
      wgmma_n128_ta<4096, 64>(d, a16 + st * 2048, b16 + st * 2048); wgmma_n128_ta<6144, 96>(d, a16 + st * 2048, b16 + st * 2048);
      wg_commit();
      asm volatile("wgmma.wait_group.sync.aligned 1;" ::: "memory");
      if (ps >= 0 && (tid & 127) == 0) {
        mbar_arrive_cluster_rlx(e0 + ps * 8); mbar_arrive_cluster_rlx(e1 + ps * 8);
      }
      ps = st;
      if (++st == G2_ST) { st = 0; ph ^= 1; }
    }
    wg_wait0();
#ifdef PER
    if (threadIdx.x == 0) atomicMax(&g_end[5], gt32());
#endif
    bar_sync(1, 256);
#pragma unroll
    for (int jj = 0; jj < 8; jj++) {
      const uint32_t q0 = pack_bf16(d[8 * jj], d[8 * jj + 1]), q1 = pack_bf16(d[8 * jj + 2], d[8 * jj + 3]);
      const uint32_t q2 = pack_bf16(d[8 * jj + 4], d[8 * jj + 5]), q3 = pack_bf16(d[8 * jj + 6], d[8 * jj + 7]);
      stsm4t(sb + (jj * 16 + (lane >> 4) * 8 + (lane & 7)) * 272 + (warp * 16 + ((lane >> 3) & 1) * 8) * 2, q0, q1, q2, q3);
    }
    bar_sync(2, 352);
#pragma unroll
    for (int it = 0; it < 8; it++) {
      const int row = it * 16 + (tid >> 4), ch = tid & 15, tok = m0 + row;
      const uint4 av = lds128(sb + row * 272 + ch * 16), tv = lds128(sb + G2_TB + row * 256 + ch * 16);
      const uint32_t g = lds32(bars + 512 + row * 4);
      *reinterpret_cast<uint4*>(out + (size_t)tok * DM + n0 + ch * 8) =
          make_uint4(addb2(mulb2(g, av.x), tv.x), addb2(mulb2(g, av.y), tv.y), addb2(mulb2(g, av.z), tv.z), addb2(mulb2(g, av.w), tv.w));
    }
  }
  asm volatile("barrier.cluster.arrive.relaxed.aligned;\nbarrier.cluster.wait.aligned;" ::: "memory");
#ifdef PER
  if (threadIdx.x == 0) atomicMax(&g_end[2], gt32());
#endif
}
#ifndef WPROM
#define WPROM CU_TENSOR_MAP_L2_PROMOTION_L2_128B
#endif
#ifndef PDL
#define PDL 1
#endif
typedef CUresult (*PFN_encodeTiled)(CUtensorMap*, CUtensorMapDataType, cuuint32_t, void*, const cuuint64_t*, const cuuint64_t*,
                                    const cuuint32_t*, const cuuint32_t*, CUtensorMapInterleave, CUtensorMapSwizzle,
                                    CUtensorMapL2promotion, CUtensorMapFloatOOBfill);

extern "C" void kernel_launch(void* const* d_in, const int* in_sizes, int n_in, void* d_out, int out_size) {
  const bf16* x = (const bf16*)d_in[0];
  const bf16* mem0 = (const bf16*)d_in[1];
  const bf16* Wq = (const bf16*)d_in[2];
  const bf16* Wk = (const bf16*)d_in[3];
  const bf16* Wv = (const bf16*)d_in[4];
  const bf16* Wo = (const bf16*)d_in[5];
  const bf16* w_r = (const bf16*)d_in[8];
  const bf16* w_gate = (const bf16*)d_in[9];
  const bf16* w_up = (const bf16*)d_in[10];
  const bf16* w_down = (const bf16*)d_in[11];
  const bf16* gate_w = (const bf16*)d_in[12];
  bf16* out = (bf16*)d_out;

  static PFN_encodeTiled encode = nullptr;
  if (!encode) {
    void* fn = nullptr; cudaDriverEntryPointQueryResult st;
    cudaGetDriverEntryPoint("cuTensorMapEncodeTiled", &fn, cudaEnableDefault, &st);
    encode = (PFN_encodeTiled)fn;
    cudaFuncSetAttribute(rec_kernel, cudaFuncAttributeMaxDynamicSharedMemorySize, SM_TOTAL);
    cudaFuncSetAttribute(gemm2_kernel, cudaFuncAttributeMaxDynamicSharedMemorySize, G2_SMEM);
  }
  CUtensorMap tmx;
  {
    cuuint64_t gd[3] = {64, S_TOK, DM / 64};
    cuuint64_t gs[2] = {DM * 2, 128};
    cuuint32_t bx[3] = {64, SEG, 4};
    cuuint32_t es[3] = {1, 1, 1};
    encode(&tmx, CU_TENSOR_MAP_DATA_TYPE_BFLOAT16, 3, (void*)x, gd, gs, bx, es, CU_TENSOR_MAP_INTERLEAVE_NONE,
           CU_TENSOR_MAP_SWIZZLE_128B, CU_TENSOR_MAP_L2_PROMOTION_L2_128B, CU_TENSOR_MAP_FLOAT_OOB_FILL_NONE);
  }
  bf16* ox;
  cudaGetSymbolAddress((void**)&ox, g_ox);
  CUtensorMap tmo, tmw, tmw3;
  {
    cuuint64_t gd[2] = {NH * DH, S_TOK}; cuuint64_t gs[1] = {NH * DH * 2}; cuuint32_t bx[2] = {64, 64}; cuuint32_t es[3] = {1, 1, 1};
    encode(&tmo, CU_TENSOR_MAP_DATA_TYPE_BFLOAT16, 2, (void*)ox, gd, gs, bx, es, CU_TENSOR_MAP_INTERLEAVE_NONE,
           CU_TENSOR_MAP_SWIZZLE_128B, CU_TENSOR_MAP_L2_PROMOTION_L2_128B, CU_TENSOR_MAP_FLOAT_OOB_FILL_NONE);
    cuuint64_t gd2[2] = {DM, NH * DH}; cuuint64_t gs2[1] = {DM * 2}; cuuint32_t bx2[2] = {64, 64};
    encode(&tmw, CU_TENSOR_MAP_DATA_TYPE_BFLOAT16, 2, (void*)Wo, gd2, gs2, bx2, es, CU_TENSOR_MAP_INTERLEAVE_NONE,
           CU_TENSOR_MAP_SWIZZLE_128B, CU_TENSOR_MAP_L2_PROMOTION_L2_128B, CU_TENSOR_MAP_FLOAT_OOB_FILL_NONE);
  }
  {
    cuuint64_t gd[3] = {64, NH * DH, DM / 64}; cuuint64_t gs[2] = {DM * 2, 128}; cuuint32_t bx[3] = {64, 64, 2}; cuuint32_t es[3] = {1, 1, 1};
    encode(&tmw3, CU_TENSOR_MAP_DATA_TYPE_BFLOAT16, 3, (void*)Wo, gd, gs, bx, es, CU_TENSOR_MAP_INTERLEAVE_NONE,
           CU_TENSOR_MAP_SWIZZLE_128B, CU_TENSOR_MAP_L2_PROMOTION_L2_128B, CU_TENSOR_MAP_FLOAT_OOB_FILL_NONE);
  }
  unsigned char* win;
  cudaGetSymbolAddress((void**)&win, g_win);
  win = (unsigned char*)(((uintptr_t)win + (2u << 20) - 1) & ~(uintptr_t)((2u << 20) - 1));
  WMaps W;
  {
    cuuint64_t gd[2] = {NH * DH, DM}; cuuint64_t gs[1] = {NH * DH * 2}; cuuint32_t b32[2] = {32, 128}, b64[2] = {64, 128}; cuuint32_t es[2] = {1, 1};
    encode(&W.q, CU_TENSOR_MAP_DATA_TYPE_BFLOAT16, 2, (void*)Wq, gd, gs, b32, es, CU_TENSOR_MAP_INTERLEAVE_NONE,
           CU_TENSOR_MAP_SWIZZLE_64B, WPROM, CU_TENSOR_MAP_FLOAT_OOB_FILL_NONE);
    encode(&W.k, CU_TENSOR_MAP_DATA_TYPE_BFLOAT16, 2, (void*)Wk, gd, gs, b32, es, CU_TENSOR_MAP_INTERLEAVE_NONE,
           CU_TENSOR_MAP_SWIZZLE_64B, WPROM, CU_TENSOR_MAP_FLOAT_OOB_FILL_NONE);
    encode(&W.v, CU_TENSOR_MAP_DATA_TYPE_BFLOAT16, 2, (void*)Wv, gd, gs, b64, es, CU_TENSOR_MAP_INTERLEAVE_NONE,
           CU_TENSOR_MAP_SWIZZLE_128B, WPROM, CU_TENSOR_MAP_FLOAT_OOB_FILL_NONE);
  }
  RecParams P{mem0, win};
  SideParams SP{x, w_r, w_gate, w_up, w_down, gate_w, Wo};
  rec_kernel<<<NCTA + 4, 384, SM_TOTAL, cudaStreamPerThread>>>(tmx, tmw, W, P, SP);
  {
    cudaLaunchConfig_t cfg = {};
    cfg.gridDim = dim3(NCTA); cfg.blockDim = dim3(384); cfg.dynamicSmemBytes = G2_SMEM; cfg.stream = cudaStreamPerThread;
    cudaLaunchAttribute at[1];
    at[0].id = cudaLaunchAttributeProgrammaticStreamSerialization; at[0].val.programmaticStreamSerializationAllowed = 1;
    cfg.attrs = at; cfg.numAttrs = PDL;
    cudaLaunchKernelEx(&cfg, gemm2_kernel, tmo, tmw3, x, out, win);
  }
}
```

```cpp
#include <cuda_runtime.h>
#include <cuda_bf16.h>
#include <cuda_fp16.h>
#include <cuda.h>
#include <stdint.h>

typedef __nv_bfloat16 bf16;

#define S_TOK 2048
#define DM 1024
#define NH 32
#define DH 128
#define SEG 32
#define NSEG 64
#define FF 3584
#define NCTA 128

static __device__ bf16 g_ox[(size_t)S_TOK * NH * DH];
static __device__ float g_gate[S_TOK];
static __device__ float g_r[S_TOK];
static __device__ int g_idx[8];
static __device__ bf16 g_upd[8 * DM];

static __device__ __forceinline__ float rbf(float v) { return __bfloat162float(__float2bfloat16(v)); }
static __device__ __forceinline__ uint32_t smem_u32(const void* p) { return (uint32_t)__cvta_generic_to_shared(p); }
static __device__ __forceinline__ uint32_t pack_bf16(float lo, float hi) {
  __nv_bfloat162 v = __floats2bfloat162_rn(lo, hi);
  return *reinterpret_cast<uint32_t*>(&v);
}

static __device__ __forceinline__ void wg_fence() { asm volatile("wgmma.fence.sync.aligned;" ::: "memory"); }
static __device__ __forceinline__ void wg_commit() { asm volatile("wgmma.commit_group.sync.aligned;" ::: "memory"); }
static __device__ __forceinline__ void wg_wait0() { asm volatile("wgmma.wait_group.sync.aligned 0;" ::: "memory"); }
static __device__ __forceinline__ void fence_async_smem() { asm volatile("fence.proxy.async.shared::cta;" ::: "memory"); }

static __device__ __forceinline__ uint64_t make_desc(uint32_t addr, uint32_t lbo, uint32_t sbo) {
  uint64_t d = 0;
  d |= (uint64_t)((addr & 0x3FFFF) >> 4);
  d |= (uint64_t)((lbo >> 4) & 0x3FFF) << 16;
  d |= (uint64_t)((sbo >> 4) & 0x3FFF) << 32;
  d |= (uint64_t)1 << 62;
  return d;
}

#define DESC_HI(sbo) (((sbo) >> 4) | (1u << 30))
template <int OFF, int SCALE>
static __device__ __forceinline__ void wgmma_n32_ra(float (&d)[16], const uint32_t (&a)[4], uint32_t base16) {
  asm volatile(
      "{\n.reg .b32 t;\n.reg .b64 dd;\nadd.u32 t, %20, %21;\nmov.b64 dd, {t, %22};\n"
      "wgmma.mma_async.sync.aligned.m64n32k16.f32.bf16.bf16 "
      "{%0,%1,%2,%3,%4,%5,%6,%7,%8,%9,%10,%11,%12,%13,%14,%15}, {%16,%17,%18,%19}, dd, %23, 1, 1, 0;\n}"
      : "+f"(d[0]), "+f"(d[1]), "+f"(d[2]), "+f"(d[3]), "+f"(d[4]), "+f"(d[5]), "+f"(d[6]), "+f"(d[7]),
        "+f"(d[8]), "+f"(d[9]), "+f"(d[10]), "+f"(d[11]), "+f"(d[12]), "+f"(d[13]), "+f"(d[14]), "+f"(d[15])
      : "r"(a[0]), "r"(a[1]), "r"(a[2]), "r"(a[3]), "r"(base16), "n"(OFF >> 4), "n"(DESC_HI(1024)), "n"(SCALE));
}
template <int AOFF, int BOFF, int SCALE>
static __device__ __forceinline__ void wgmma_n32_ss_ta(float (&d)[16], uint32_t abase16, uint32_t bbase16) {
  asm volatile(
      "{\n.reg .b32 t, u;\n.reg .b64 da, db;\nadd.u32 t, %16, %18;\nmov.b64 da, {t, %20};\nadd.u32 u, %17, %19;\nmov.b64 db, {u, %20};\n"
      "wgmma.mma_async.sync.aligned.m64n32k16.f32.bf16.bf16 "
      "{%0,%1,%2,%3,%4,%5,%6,%7,%8,%9,%10,%11,%12,%13,%14,%15}, da, db, %21, 1, 1, 1, 0;\n}"
      : "+f"(d[0]), "+f"(d[1]), "+f"(d[2]), "+f"(d[3]), "+f"(d[4]), "+f"(d[5]), "+f"(d[6]), "+f"(d[7]),
        "+f"(d[8]), "+f"(d[9]), "+f"(d[10]), "+f"(d[11]), "+f"(d[12]), "+f"(d[13]), "+f"(d[14]), "+f"(d[15])
      : "r"(abase16), "r"(bbase16), "n"(AOFF >> 4), "n"(BOFF >> 4), "n"(DESC_HI(1024)), "n"(SCALE));
}
static __device__ __forceinline__ void ldmatrix_x4_trans(uint32_t (&r)[4], uint32_t addr) {
  asm volatile("ldmatrix.sync.aligned.m8n8.x4.trans.shared.b16 {%0,%1,%2,%3}, [%4];"
               : "=r"(r[0]), "=r"(r[1]), "=r"(r[2]), "=r"(r[3]) : "r"(addr) : "memory");
}
static __device__ __forceinline__ void mma_16816(float (&d)[4], const uint32_t (&a)[4], uint32_t b0, uint32_t b1) {
  asm volatile("mma.sync.aligned.m16n8k16.row.col.f32.bf16.bf16.f32 {%0,%1,%2,%3}, {%4,%5,%6,%7}, {%8,%9}, {%0,%1,%2,%3};"
               : "+f"(d[0]), "+f"(d[1]), "+f"(d[2]), "+f"(d[3])
               : "r"(a[0]), "r"(a[1]), "r"(a[2]), "r"(a[3]), "r"(b0), "r"(b1));
}

static __device__ __forceinline__ uint32_t mapa(uint32_t addr, uint32_t rank) {
  uint32_t r; asm volatile("mapa.shared::cluster.u32 %0, %1, %2;" : "=r"(r) : "r"(addr), "r"(rank)); return r;
}

static __device__ __forceinline__ void mbar_init(uint32_t bar, int cnt) {
  asm volatile("mbarrier.init.shared::cta.b64 [%0], %1;" :: "r"(bar), "r"(cnt) : "memory");
}
static __device__ __forceinline__ void mbar_expect_tx(uint32_t bar, uint32_t bytes) {
  asm volatile("mbarrier.arrive.expect_tx.shared::cta.b64 _, [%0], %1;" :: "r"(bar), "r"(bytes) : "memory");
}
static __device__ __forceinline__ void tma_load_2d(uint32_t dst, const CUtensorMap* tm, int c0, int c1, uint32_t bar) {
  asm volatile("cp.async.bulk.tensor.2d.shared::cluster.global.mbarrier::complete_tx::bytes [%0], [%1, {%3, %4}], [%2];"
               :: "r"(dst), "l"(tm), "r"(bar), "r"(c0), "r"(c1) : "memory");
}

static __device__ unsigned char g_win[6 << 20];
static __device__ unsigned int g_side[67 * 32];
static __device__ unsigned int g_err;
#define W_UP (1u << 20)
#define W_2 (2u << 20)
static __device__ __forceinline__ uint32_t w_blk(uint32_t off, uint32_t side) { return off | (((__popc((off >> 12) & 0xb3u) ^ side) & 1u) << 12); }
static __device__ __forceinline__ uint32_t w_h1(int c) { return W_UP | (1u << 13) | ((c >> 1) << 14) | ((c & 1) << 11); }
#define W_DS 0x30000u
static __device__ __forceinline__ uint32_t w_ar(int s) { return ((s & 1) << 15) | ((s & 2) << 17); }
static __device__ __forceinline__ uint32_t w_mvx(int c, int s) { return W_2 | ((s & 1) << 20) | ((c >> 1) << 14) | ((c & 1) << 11); }
static __device__ __forceinline__ uint32_t w_mxa(int c, int s) { return W_2 | ((s & 1) << 20) | (1u << 13) | ((c >> 1) << 14) | ((c & 1) << 11); }
#define H1_V (1u << 13)

#define SPIN_LIMIT (1 << 18)

#define SM_X 0
#define SM_WOS 65536
#define SM_WVS 131072
#define SM_MEM 163840
#define SM_QKP 180224
#define SM_VP 184320
#define SM_CW 188416
#define SM_VST 196608
#define SM_VR 196608
#define SM_CQ 200704
#define SM_CV 208896
#define SM_XF 217088
#define SM_VL 221184
#define SM_OF 225280
#define SM_OX 227328
#define SM_PF 229376
#define SM_PX 230016
#define SM_RD 198656
#define SM_QA 230656
#define SM_XS 231168
#define SM_BAR 231808
#define SM_Z 231936
#define SM_TOTAL 232128
#define MB_F 0
#define MB_XE0 16
#define MB_XE1 112
#define MB_INIT 24
#define MB_MEM 32
#define MB_W 256
#define MB_XF 64
#define MB_VR 72
#define MB_X0 80
#define MB_WO 88
#define SM_SIDE (SM_BAR + 96)
#define B_QK 1
#define B_V 2
#define B_P 3
#define B_O 4
#define B_O2 5
#define B_PUB 6
#define B_CQ 7
#define B_QK1 8
#define B_PXF 10
#define B_CV 15
#define B_X2 11
#define B_PX 12
#define B_GO 14
#define B_G1 13

#ifdef PROF
__device__ unsigned int g_ts[NCTA][80][32];
#ifdef GT
#define TCLK() gt32()
#else
#define TCLK() clk32()
#endif
#ifndef TMASK
#define TMASK 0xffffffffu
#endif
#define TST(st, i, c, v) do { if ((TMASK >> (i)) & 1u) asm volatile("{\n.reg .pred q;\nsetp.eq.u32 q, %2, 0;\n@q st.global.u32 [%0], %1;\n}" :: "l"(&g_ts[cta][(st) + 1][i]), "r"((uint32_t)(v)), "r"((uint32_t)(c)) : "memory"); } while (0)
#define TS(i) TST(s, i, l16, TCLK())
#define TV(i, v) TST(s, i, l16, v)
#define TSF(i, w) TST(s, i, l16 | (w8 ^ (w)), TCLK())
#define TSP(i, w) TST(s - 1, i, l16 | (w8 ^ (w)), TCLK())
#define TVF(i, v) TV(i, v)
#else
#define TST(a, b, c, d)
#define TSF(i, w)
#define TSP(i, w)
#define TVF(i, v)
#define TS(i)
#define TV(i, v)
#endif

static __device__ __forceinline__ void bar_sync(int id, int n) { asm volatile("bar.sync %0, %1;" :: "r"(id), "r"(n) : "memory"); }
static __device__ __forceinline__ void bar_arrive(int id, int n) { asm volatile("bar.arrive %0, %1;" :: "r"(id), "r"(n) : "memory"); }
static __device__ __forceinline__ uint4 ldg_r4(const void* p) { uint4 v;
  asm volatile("ld.relaxed.gpu.global.v4.u32 {%0,%1,%2,%3}, [%4];" : "=r"(v.x), "=r"(v.y), "=r"(v.z), "=r"(v.w) : "l"(p) : "memory"); return v; }
static __device__ __forceinline__ uint32_t ldg_r1(const void* p) { uint32_t v;
  asm volatile("ld.relaxed.gpu.global.u32 %0, [%1];" : "=r"(v) : "l"(p) : "memory"); return v; }
static __device__ __forceinline__ void stg_r4(void* p, uint32_t a, uint32_t b, uint32_t c, uint32_t d) {
  asm volatile("st.relaxed.gpu.global.v4.u32 [%0], {%1,%2,%3,%4};" :: "l"(p), "r"(a), "r"(b), "r"(c), "r"(d) : "memory"); }
static __device__ __forceinline__ uint2 ldg_r2(const void* p) { uint2 v;
  asm volatile("ld.relaxed.gpu.global.v2.u32 {%0,%1}, [%2];" : "=r"(v.x), "=r"(v.y) : "l"(p) : "memory"); return v; }
static __device__ __forceinline__ void stg_4(void* p, const uint4& v) {
  asm volatile("st.global.v4.u32 [%0], {%1,%2,%3,%4};" :: "l"(p), "r"(v.x), "r"(v.y), "r"(v.z), "r"(v.w) : "memory"); }
static __device__ __forceinline__ uint32_t f2u(float v) { return __float_as_uint(v); }
static __device__ __forceinline__ void stg_2(void* p, uint32_t a, uint32_t b) {
  asm volatile("st.global.v2.u32 [%0], {%1,%2};" :: "l"(p), "r"(a), "r"(b) : "memory"); }
static __device__ __forceinline__ void stg_r1(void* p, uint32_t a) {
  asm volatile("st.relaxed.gpu.global.u32 [%0], %1;" :: "l"(p), "r"(a) : "memory"); }
static __device__ __forceinline__ void sts128(uint32_t a, uint32_t x, uint32_t y, uint32_t z, uint32_t w) {
  asm volatile("st.shared.v4.u32 [%0], {%1,%2,%3,%4};" :: "r"(a), "r"(x), "r"(y), "r"(z), "r"(w) : "memory"); }
static __device__ __forceinline__ void sts128f(uint32_t a, float x, float y, float z, float w) {
  asm volatile("st.shared.v4.f32 [%0], {%1,%2,%3,%4};" :: "r"(a), "f"(x), "f"(y), "f"(z), "f"(w) : "memory"); }
static __device__ __forceinline__ uint4 lds128(uint32_t a) { uint4 v;
  asm volatile("ld.shared.v4.u32 {%0,%1,%2,%3}, [%4];" : "=r"(v.x), "=r"(v.y), "=r"(v.z), "=r"(v.w) : "r"(a) : "memory"); return v; }
static __device__ __forceinline__ float4 lds128f(uint32_t a) { float4 v;
  asm volatile("ld.shared.v4.f32 {%0,%1,%2,%3}, [%4];" : "=f"(v.x), "=f"(v.y), "=f"(v.z), "=f"(v.w) : "r"(a) : "memory"); return v; }
static __device__ __forceinline__ void sts32(uint32_t a, uint32_t x) { asm volatile("st.shared.u32 [%0], %1;" :: "r"(a), "r"(x) : "memory"); }
static __device__ __forceinline__ uint2 lds64(uint32_t a) { uint2 v;
  asm volatile("ld.shared.v2.u32 {%0,%1}, [%2];" : "=r"(v.x), "=r"(v.y) : "r"(a) : "memory"); return v; }
static __device__ __forceinline__ void st_async4(uint32_t ra, float x, float y, float z, float w, uint32_t rbar) {
  asm volatile("st.async.weak.shared::cluster.mbarrier::complete_tx::bytes.v4.f32 [%0], {%1,%2,%3,%4}, [%5];"
               :: "r"(ra), "f"(x), "f"(y), "f"(z), "f"(w), "r"(rbar) : "memory"); }
static __device__ __forceinline__ void stsm4t(uint32_t a, uint32_t x, uint32_t y, uint32_t z, uint32_t w) {
  asm volatile("stmatrix.sync.aligned.m8n8.x4.trans.shared.b16 [%0], {%1,%2,%3,%4};" :: "r"(a), "r"(x), "r"(y), "r"(z), "r"(w) : "memory"); }
static __device__ __forceinline__ uint32_t hmax2(uint32_t a, uint32_t b) { uint32_t d;
  asm("max.f16x2 %0, %1, %2;" : "=r"(d) : "r"(a), "r"(b)); return d; }
static __device__ __forceinline__ uint32_t hadd2(uint32_t a, uint32_t b) { uint32_t d;
  asm("add.rn.f16x2 %0, %1, %2;" : "=r"(d) : "r"(a), "r"(b)); return d; }
static __device__ __forceinline__ uint32_t packv(float a, float b, float c, float d) { uint32_t r;
  asm volatile("{\n.reg .f32 x, y;\nadd.f32 x, %1, %2;\nadd.f32 y, %3, %4;\ncvt.rn.bf16x2.f32 %0, y, x;\n}" : "=r"(r) : "f"(a), "f"(b), "f"(c), "f"(d)); return r; }
static __device__ __forceinline__ uint32_t packh(float a, float b, float c, float d) { uint32_t r;
  asm volatile("{\n.reg .f32 x, y;\nadd.f32 x, %1, %2;\nadd.f32 y, %3, %4;\ncvt.rn.satfinite.f16x2.f32 %0, y, x;\n}" : "=r"(r) : "f"(a), "f"(b), "f"(c), "f"(d)); return r; }
static __device__ __forceinline__ float ex2v(float a, float b, float c) { float y;
  asm volatile("{\n.reg .f32 x;\nfma.rn.f32 x, %1, %2, %3;\nex2.approx.ftz.f32 %0, x;\n}" : "=f"(y) : "f"(a), "f"(b), "f"(c)); return y; }
static __device__ __forceinline__ uint32_t shfl_x(uint32_t a, int m) { uint32_t d;
  asm volatile("shfl.sync.bfly.b32 %0, %1, %2, 0x1f, 0xffffffff;" : "=r"(d) : "r"(a), "r"(m)); return d; }
static __device__ __forceinline__ void h2f(float& lo, float& hi, uint32_t a) {
  asm volatile("{\n.reg .b16 l, h;\nmov.b32 {l, h}, %2;\ncvt.f32.f16 %0, l;\ncvt.f32.f16 %1, h;\n}" : "=f"(lo), "=f"(hi) : "r"(a)); }
static __device__ __forceinline__ uint4 ldsm4(uint32_t a) { uint4 v;
  asm volatile("ldmatrix.sync.aligned.m8n8.x4.shared.b16 {%0,%1,%2,%3}, [%4];" : "=r"(v.x), "=r"(v.y), "=r"(v.z), "=r"(v.w) : "r"(a) : "memory"); return v; }
static __device__ __forceinline__ uint4 ldsm4t(uint32_t a) { uint4 v;
  asm volatile("ldmatrix.sync.aligned.m8n8.x4.trans.shared.b16 {%0,%1,%2,%3}, [%4];" : "=r"(v.x), "=r"(v.y), "=r"(v.z), "=r"(v.w) : "r"(a) : "memory"); return v; }
static __device__ __forceinline__ uint32_t movm(uint32_t a) { uint32_t d;
  asm volatile("movmatrix.sync.aligned.m8n8.trans.b16 %0, %1;" : "=r"(d) : "r"(a)); return d; }
static __device__ __forceinline__ float u2f(uint32_t v) { return __uint_as_float(v); }
static __device__ __forceinline__ uint32_t tagw(uint32_t w, uint32_t t) { uint32_t d;
  asm("lop3.b32 %0, %1, %2, 1, 0xd8;" : "=r"(d) : "r"(w), "r"(t)); return d; }
static __device__ __forceinline__ uint32_t pack_f16(float lo, float hi) { uint32_t d;
  asm("cvt.rn.satfinite.f16x2.f32 %0, %1, %2;" : "=r"(d) : "f"(hi), "f"(lo)); return d; }
static __device__ __forceinline__ void sum_h4(float& lo, float& hi, uint32_t a, uint32_t b, uint32_t c, uint32_t d) {
  const float2 x = __half22float2(*reinterpret_cast<__half2*>(&a)), y = __half22float2(*reinterpret_cast<__half2*>(&b));
  const float2 z = __half22float2(*reinterpret_cast<__half2*>(&c)), w = __half22float2(*reinterpret_cast<__half2*>(&d));
  lo = (x.x + y.x) + (z.x + w.x); hi = (x.y + y.y) + (z.y + w.y);
}
static __device__ __forceinline__ uint32_t lds32(uint32_t a) { uint32_t v; asm volatile("ld.shared.u32 %0, [%1];" : "=r"(v) : "r"(a) : "memory"); return v; }
static __device__ __forceinline__ uint32_t addb2(uint32_t a, uint32_t b) { uint32_t d;
  asm("add.rn.bf16x2 %0, %1, %2;" : "=r"(d) : "r"(a), "r"(b)); return d; }
static __device__ __forceinline__ uint32_t mulb2(uint32_t a, uint32_t b) { uint32_t d;
  asm("mul.rn.bf16x2 %0, %1, %2;" : "=r"(d) : "r"(a), "r"(b)); return d; }
static __device__ __forceinline__ uint32_t mulb2v(uint32_t a, uint32_t b) { uint32_t d;
  asm volatile("mul.rn.bf16x2 %0, %1, %2;" : "=r"(d) : "r"(a), "r"(b)); return d; }
static __device__ __forceinline__ uint32_t x3(uint32_t a, uint32_t b, uint32_t t) { uint32_t d;
  asm("lop3.b32 %0, %1, %2, %3, 0x7e;" : "=r"(d) : "r"(a), "r"(b), "r"(t)); return d; }
static __device__ __forceinline__ uint32_t or3(uint32_t a, uint32_t b, uint32_t c) { uint32_t d;
  asm("lop3.b32 %0, %1, %2, %3, 0xfe;" : "=r"(d) : "r"(a), "r"(b), "r"(c)); return d; }
static __device__ __forceinline__ float ex2(float x) { float y; asm("ex2.approx.ftz.f32 %0, %1;" : "=f"(y) : "f"(x)); return y; }
static __device__ __forceinline__ float rcpf(float x) { float y; asm("rcp.approx.ftz.f32 %0, %1;" : "=f"(y) : "f"(x)); return y; }
static __device__ __forceinline__ void mbar_wait(uint32_t bar, int parity) {
  asm volatile("{\n.reg .pred p, q;\n.reg .u32 n;\nmbarrier.try_wait.parity.shared::cta.b64 p, [%0], %1;\n@p bra W_DONE;\nmov.u32 n, 0;\n"
               "W_LOOP:\nmbarrier.try_wait.parity.shared::cta.b64 p, [%0], %1;\nadd.u32 n, n, 1;\nsetp.lt.and.u32 q, n, %2, !p;\n@q bra W_LOOP;\nW_DONE:\n}"
               :: "r"(bar), "r"(parity), "n"(SPIN_LIMIT) : "memory");
}
static __device__ __forceinline__ uint32_t mbar_test(uint32_t bar, int parity) { uint32_t ok;
  asm volatile("{\n.reg .pred p;\nmbarrier.test_wait.parity.shared::cta.b64 p, [%1], %2;\nselp.u32 %0, 1, 0, p;\n}" : "=r"(ok) : "r"(bar), "r"(parity) : "memory"); return ok; }
static __device__ __forceinline__ void mbar_arrive(uint32_t bar) {
  asm volatile("mbarrier.arrive.shared::cta.b64 _, [%0];" :: "r"(bar) : "memory"); }
static __device__ __forceinline__ void mbar_arrive_cluster_rlx(uint32_t raddr) {
  asm volatile("mbarrier.arrive.relaxed.cluster.shared::cluster.b64 _, [%0];" :: "r"(raddr) : "memory"); }
static __device__ __forceinline__ void tma_load_mc(uint32_t dst, const CUtensorMap* tm, int c1, int c2, uint32_t bar) {
#ifdef NOTMA
  if ((NOTMA >> (c2 >> 3)) & 1) asm volatile("mbarrier.complete_tx.relaxed.cta.shared::cta.b64 [%0], 32768;" :: "r"(bar) : "memory"); else
#endif
  asm volatile("cp.async.bulk.tensor.3d.shared::cluster.global.mbarrier::complete_tx::bytes.multicast::cluster [%0], [%1, {%3, %4, %5}], [%2], %6;"
               :: "r"(dst), "l"(tm), "r"(bar), "r"(0), "r"(c1), "r"(c2), "h"((uint16_t)3) : "memory"); }
static __device__ __forceinline__ void cp16(uint32_t dst, const void* src) {
  asm volatile("cp.async.cg.shared.global [%0], [%1], 16;" :: "r"(dst), "l"(src) : "memory"); }
static __device__ __forceinline__ void mma_1688(float (&d)[4], uint32_t a0, uint32_t a1, uint32_t b0) {
  asm volatile("mma.sync.aligned.m16n8k8.row.col.f32.bf16.bf16.f32 {%0,%1,%2,%3}, {%4,%5}, {%6}, {%0,%1,%2,%3};"
               : "+f"(d[0]), "+f"(d[1]), "+f"(d[2]), "+f"(d[3]) : "r"(a0), "r"(a1), "r"(b0)); }
static __device__ __forceinline__ void mma4(float (&d)[4], uint32_t a0, uint32_t a1, uint32_t a2, uint32_t a3, uint32_t b0, uint32_t b1) {
  asm volatile("mma.sync.aligned.m16n8k16.row.col.f32.bf16.bf16.f32 {%0,%1,%2,%3}, {%4,%5,%6,%7}, {%8,%9}, {%0,%1,%2,%3};"
               : "+f"(d[0]), "+f"(d[1]), "+f"(d[2]), "+f"(d[3]) : "r"(a0), "r"(a1), "r"(a2), "r"(a3), "r"(b0), "r"(b1)); }
static __device__ __forceinline__ void mma4z(float (&d)[4], uint32_t a0, uint32_t a1, uint32_t a2, uint32_t a3, uint32_t b0, uint32_t b1) {
  asm volatile("mma.sync.aligned.m16n8k16.row.col.f32.bf16.bf16.f32 {%0,%1,%2,%3}, {%4,%5,%6,%7}, {%8,%9}, {%10,%10,%10,%10};"
               : "=f"(d[0]), "=f"(d[1]), "=f"(d[2]), "=f"(d[3]) : "r"(a0), "r"(a1), "r"(a2), "r"(a3), "r"(b0), "r"(b1), "f"(0.f)); }
static __device__ __forceinline__ uint32_t clk32() { uint32_t t; asm volatile("mov.u32 %0, %%clock;" : "=r"(t)); return t; }
static __device__ __forceinline__ uint32_t gt32() { uint32_t t; asm volatile("mov.u32 %0, %%globaltimer_lo;" : "=r"(t)); return t; }
static __device__ __forceinline__ void spin(int clk) { if (clk > 0) { uint32_t t = clk32(); while (clk32() - t < (uint32_t)clk) {} } }
static __device__ __forceinline__ void spinv(int clk, uint32_t z) { const uint32_t t = clk32() + (z >> 31); while (clk32() - t < (uint32_t)clk) {} }
#define FENCE() asm volatile("griddepcontrol.launch_dependents;" ::: "memory")
#define OPAQUE_L(p) asm volatile("" : "+l"(p))
#define OPAQUE_R(p) asm volatile("" : "+r"(p))

template <int KK, int K1, int W0, int NW, int FIRST> struct XR {
  static __device__ __forceinline__ void run(float (&d)[16], const uint32_t (&w)[NW][4], uint32_t b16) {
#ifdef NOWG
    if (KK % NOWG == 0)
#endif
    wgmma_n32_ra<(KK >> 2) * 4096 + (KK & 3) * 32, !FIRST>(d, w[W0 + KK], b16);
    XR<KK + 1, K1, W0, NW, 0>::run(d, w, b16);
  }
};
template <int K1, int W0, int NW, int FIRST> struct XR<K1, K1, W0, NW, FIRST> { static __device__ __forceinline__ void run(float (&)[16], const uint32_t (&)[NW][4], uint32_t) {} };
template <int KK, int K0, int K1, int FIRST> struct XS {
  static __device__ __forceinline__ void run(float (&d)[16], uint32_t a16, uint32_t b16) {
#ifdef NOWG
    if (KK % NOWG == 0)
#endif
    wgmma_n32_ss_ta<(KK - K0) * 2048, (KK >> 2) * 4096 + (KK & 3) * 32, !FIRST>(d, a16, b16);
    XS<KK + 1, K0, K1, 0>::run(d, a16, b16);
  }
};
template <int K0, int K1, int FIRST> struct XS<K1, K0, K1, FIRST> { static __device__ __forceinline__ void run(float (&)[16], uint32_t, uint32_t) {} };

static __device__ bf16 g_h[8 * FF];
static __device__ unsigned int g_sbar;
struct SideParams { const bf16* x; const bf16* w_r; const bf16* w_gate; const bf16* w_up; const bf16* w_down; const bf16* gate_w; const bf16* Wo; };

static __device__ __forceinline__ void side_barrier(unsigned int target) {
  __syncthreads();
  if (threadIdx.x == 0) {
    __threadfence();
    atomicAdd(&g_sbar, 1u);
    int n = 0;
    while (*(volatile unsigned int*)&g_sbar < target) { if (++n > (1 << 22)) { g_err = 50; break; } }
    __threadfence();
  }
  __syncthreads();
}
static __device__ __forceinline__ uint4 ldg_nc(const void* p) { uint4 v;
  asm volatile("ld.global.nc.L1::no_allocate.v4.u32 {%0,%1,%2,%3}, [%4];" : "=r"(v.x), "=r"(v.y), "=r"(v.z), "=r"(v.w) : "l"(p)); return v; }
#ifndef SPD
#define SPD 3
#endif
static __device__ __forceinline__ void l2pf(const void* p) { asm volatile("prefetch.global.L2 [%0];" :: "l"(p)); }
static __device__ __forceinline__ void mm8(float (&acc)[8][4], const bf16* W, const bf16* Wn, int ldw, int nk16, uint32_t abase, uint32_t ring, int lane) {
  const int rw = lane >> 3, ch = lane & 7;
  const bf16* wp = W + (size_t)rw * ldw + ch * 8;
  const uint32_t wd = ring + rw * 128, rd = ring + ((rw & 1) * 8 + ch) * 128;
#define MM_LD(k) do { if ((k) < nk16) { const bf16* q = wp + (size_t)(k) * 16 * ldw; \
    _Pragma("unroll") for (int i = 0; i < 4; i++) cp16(wd + ((k) & 3) * 2048 + i * 512 + ((ch ^ (rw + (i & 1) * 4)) << 4), q + (size_t)(4 * i) * ldw); } \
    asm volatile("cp.async.commit_group;" ::: "memory"); } while (0)
  __syncwarp();
  MM_LD(0); MM_LD(1); MM_LD(2);
#pragma unroll 1
  for (int k = 0; k < nk16; k++) {
    if ((k & 1) == 0) {
      const int kp = k + 4 * SPD;
      const bf16* pf = kp < nk16 ? W + (size_t)(kp * 16) * ldw : Wn ? Wn + (size_t)((kp - nk16) * 16) * ldw : nullptr;
      if (pf) l2pf(pf + (size_t)lane * ldw);
    }
    asm volatile("cp.async.wait_group 2;" ::: "memory");
    __syncwarp();
    MM_LD(k + 3);
    const uint32_t a0 = lds32(abase + k * 32), a2 = lds32(abase + k * 32 + 16);
#pragma unroll
    for (int i = 0; i < 4; i++) {
      const uint4 b = ldsm4t(rd + (k & 3) * 2048 + (((2 * i + (rw >> 1)) ^ ch) << 4));
      mma4(acc[2 * i], a0, 0u, a2, 0u, b.x, b.y); mma4(acc[2 * i + 1], a0, 0u, a2, 0u, b.z, b.w);
    }
  }
}
static __device__ __noinline__ void side_work(const SideParams& P, unsigned char* smem, int q) {
  const int tid = threadIdx.x, lane = tid & 31, warp = tid >> 5, g = lane >> 2, t = lane & 3;
  const uint32_t sb = smem_u32(smem);
  unsigned int* cand = reinterpret_cast<unsigned int*>(smem);
  bf16* xs = reinterpret_cast<bf16*>(smem + 1024);
  float* part = reinterpret_cast<float*>(smem + 65536);
  {
    for (int i = tid; i < 256; i += 384) *reinterpret_cast<uint4*>(smem + 1024 + i * 16) = ldg_nc((i < 128 ? P.gate_w : P.w_r - DM) + i * 8);
    __syncthreads();
#pragma unroll 1
    for (int it = warp; it < 64; it += 12) {
      const bf16* xp = P.x + (size_t)(q * 512 + (it >> 1) * 16 + g) * DM + (it & 1) * 512 + t * 8;
      for (int a = it == warp ? 0 : 1; a < 2 && it + 12 * a < 64; a++)
#pragma unroll
        for (int i = 0; i < 4; i++) l2pf(P.x + (size_t)(q * 512 + (it >> 1) * 16 + a * 96 + i * 4 + (lane >> 3)) * DM + (it & 1) * 512 + (lane & 7) * 64);
      const uint32_t xb = sb + 16384 + warp * 16384 + lane * 16;
#pragma unroll
      for (int i = 0; i < 16; i++) { cp16(xb + i * 1024, xp + i * 32); cp16(xb + i * 1024 + 512, xp + 8 * DM + i * 32); }
      asm volatile("cp.async.commit_group;\ncp.async.wait_group 0;" ::: "memory");
      float sg[4] = {0.f, 0.f, 0.f, 0.f}, sr[4] = {0.f, 0.f, 0.f, 0.f};
#pragma unroll
      for (int i = 0; i < 16; i++) {
        const uint4 gw = lds128(sb + 1024 + (it & 1) * 1024 + i * 64 + t * 16), wr = lds128(sb + 3072 + (it & 1) * 1024 + i * 64 + t * 16);
        const uint4 lo = lds128(xb + i * 1024), hi = lds128(xb + i * 1024 + 512);
        mma4(sr, lo.x, hi.x, lo.y, hi.y, wr.x, wr.y); mma4(sr, lo.z, hi.z, lo.w, hi.w, wr.z, wr.w);
        mma4(sg, mulb2(lo.x, gw.x), mulb2(hi.x, gw.x), mulb2(lo.y, gw.y), mulb2(hi.y, gw.y), 0x3F803F80u, 0x3F803F80u);
        mma4(sg, mulb2(lo.z, gw.z), mulb2(hi.z, gw.z), mulb2(lo.w, gw.w), mulb2(hi.w, gw.w), 0x3F803F80u, 0x3F803F80u);
      }
      if (t == 0) {
        float* pp = reinterpret_cast<float*>(smem + 8192) + (it & 1) * 1024 + (it >> 1) * 16 + g;
        pp[0] = sg[0]; pp[8] = sg[2]; pp[512] = sr[0]; pp[520] = sr[2];
      }
    }
    __syncthreads();
    for (int i = tid; i < 512; i += 384) {
      const float* pp = reinterpret_cast<const float*>(smem + 8192);
      g_gate[q * 512 + i] = rbf(1.f / (1.f + expf(-rbf(pp[i] + pp[1024 + i]))));
      g_r[q * 512 + i] = rbf(pp[512 + i] + pp[1536 + i]);
    }
    for (int i = tid; i < 16 * 896; i += 384) part[i] = 0.f;
  }
#define GU(u) (((u) % 28) / 14 ? P.w_up : P.w_gate) + (size_t)((u) / 28) * 512 * FF + q * 896 + ((u) % 14) * 64
  for (int i = lane; i < 64 * SPD; i += 32) l2pf(GU(warp) + (size_t)i * FF);
  side_barrier(4);
  {
    unsigned int key[8];
#pragma unroll
    for (int i = 0; i < 8; i++) {
      const int tok = (warp & 7) * 256 + i * 32 + lane;
      const uint32_t b = __float_as_uint(__ldcg(&g_r[tok]) + 0.f) >> 16;
      key[i] = (((b & 0x8000u) ? (~b & 0xffffu) : (b | 0x8000u)) << 16) | (uint32_t)(2047 - tok);
    }
    for (int pass = 0; pass < 2; pass++) {
      if (pass == 0 ? warp < 8 : warp == 0) {
        for (int c = 0; c < 8; c++) {
          const unsigned int m = __reduce_max_sync(~0u, max(max(max(key[0], key[1]), max(key[2], key[3])), max(max(key[4], key[5]), max(key[6], key[7]))));
#pragma unroll
          for (int i = 0; i < 8; i++) if (key[i] == m) key[i] = 0u;
          if (lane == 0) cand[pass ? 128 + c : warp * 8 + c] = m;
        }
      }
      __syncthreads();
      if (pass == 0 && warp == 0) {
#pragma unroll
        for (int i = 0; i < 8; i++) key[i] = i < 2 ? cand[i * 32 + lane] : 0u;
      }
    }
    if (q == 0 && tid < 8) g_idx[tid] = 2047 - (int)(cand[128 + tid] & 0xffffu);
    for (int i = tid; i < 1024; i += 384) {
      const int c = i >> 7, tok = 2047 - (int)(cand[128 + c] & 0xffffu);
      *reinterpret_cast<uint4*>(xs + c * (FF + 8) + (i & 127) * 8) = ldg_nc(P.x + (size_t)tok * DM + (i & 127) * 8);
    }
    __syncthreads();
  }
  const uint32_t abase = sb + 1024 + g * (FF + 8) * 2 + t * 4, ring = sb + 131072 + warp * 8192;
  for (int u = warp; u < 56; u += 12) {
    const int kh = u / 28, mat = (u % 28) / 14, cb = u % 14;
    float acc[8][4];
#pragma unroll
    for (int i = 0; i < 8; i++) acc[i][0] = acc[i][1] = acc[i][2] = acc[i][3] = 0.f;
    mm8(acc, GU(u), u + 12 < 56 ? GU(u + 12) : nullptr, FF, DM / 32, abase + kh * 1024, ring, lane);
    float* pp = part + (mat * 8 + g) * 896 + cb * 64 + 2 * t;
#pragma unroll
    for (int i = 0; i < 8; i++) { atomicAdd(pp + 8 * i, acc[i][0]); atomicAdd(pp + 8 * i + 1, acc[i][1]); }
  }
  for (int i = lane; i < 64 * SPD; i += 32) l2pf(P.w_down + (size_t)((warp >> 2) * 1216 + i) * DM + q * 256 + (warp & 3) * 64);
  __syncthreads();
  for (int i = tid; i < 8 * 896; i += 384) {
    const float ag = rbf(part[i]), au = rbf(part[8 * 896 + i]);
    g_h[(i / 896) * FF + q * 896 + i % 896] = __float2bfloat16(rbf(ag / (1.f + expf(-ag))) * au);
  }
  side_barrier(8);
  for (int i = tid; i < 8 * FF / 8; i += 384) {
    const int c = i / (FF / 8), o = i % (FF / 8);
    *reinterpret_cast<uint4*>(xs + c * (FF + 8) + o * 8) = __ldcg(reinterpret_cast<const uint4*>(g_h + c * FF + o * 8));
  }
  __syncthreads();
  {
    const int cb = warp & 3, kq = warp >> 2;
    float acc[8][4];
#pragma unroll
    for (int i = 0; i < 8; i++) acc[i][0] = acc[i][1] = acc[i][2] = acc[i][3] = 0.f;
    mm8(acc, P.w_down + (size_t)kq * 1216 * DM + q * 256 + cb * 64, nullptr, DM, kq == 2 ? 72 : 76, abase + kq * 1216 * 2, ring, lane);
#pragma unroll
    for (int i = 0; i < 8; i++) { part[(kq * 8 + g) * 256 + cb * 64 + 2 * t + 8 * i] = acc[i][0]; part[(kq * 8 + g) * 256 + cb * 64 + 2 * t + 8 * i + 1] = acc[i][1]; }
    __syncthreads();
    for (int i = tid; i < 2048; i += 384) {
      const int c = i >> 8, tok = 2047 - (int)(cand[128 + c] & 0xffffu);
      const float y = (part[i] + part[2048 + i]) + part[4096 + i];
      const float rs = rbf(1.f / (1.f + expf(-__ldcg(&g_r[tok]))));
      g_upd[c * DM + q * 256 + (i & 255)] = __float2bfloat16(rbf(y) * rs);
    }
  }
}
struct RecParams { const bf16* mem0; unsigned char* win; };
struct WMaps { CUtensorMap q, k, v; };
#ifndef KB
#define KB 8
#endif
#ifndef WPF
#define WPF 7
#endif
#ifndef WPA
#define WPA 3
#endif
#ifndef XPF
#define XPF 4
#endif
#ifndef O2P
#define O2P 4
#endif
#ifndef XG
#define XG 1
#endif
#ifndef Z0
#define Z0 1
#endif
#ifndef Z1
#define Z1 1
#endif
#ifndef WKP
#define WKP 0
#endif
#ifndef OS
#define OS 1
#endif
#ifndef SO
#define SO 1
#endif
#define RF_FAT 208
#define RF_CTL 88
#define WSPL 1
#define NPROBE 3
#define DLY_TB 700
#define DLY_SIDE 16000
#define KU 32
#define KD 4
#ifndef DLYS
#define DLYS 560, 200, 225, 150, 770, 250, 1240, 850, 460
#endif
#define NTUNE 9
#define TUNE_NAMES {"OM3", "XL", "S", "XD", "WO", "V", "OK", "OKS", "ORR"}
__constant__ int g_tune[NTUNE] = {DLYS};
#define DLY_M3 g_tune[0]
#define DLY_XL g_tune[1]
#define DLY_S g_tune[2]
#define DLY_XD g_tune[3]
#define DLY_WO g_tune[4]
#define DLY_V g_tune[5]
#define DLY_K g_tune[6]
#define DLY_KS g_tune[7]
#define DLY_RR g_tune[8]
#ifdef PRO
__device__ unsigned g_pro[NCTA][16];
#define PT(i, c) do { if (c) g_pro[cta][i] = gt32(); } while (0)
#else
#define PT(i, c)
#endif
#ifdef PER
__device__ unsigned g_pk[NCTA][64], g_pclk[NCTA][64], g_per[NCTA][64], g_end[8] = {0, 0, 0, 0, 0, 0, 0, 100000};
#endif
#define STR2(x) #x
#define STR(x) STR2(x)

static __device__ __forceinline__ void cp16p(uint32_t dst, const void* src, uint32_t v) {
  asm volatile("{\n.reg .pred q;\nsetp.ne.u32 q, %2, 0;\n@q cp.async.cg.shared.global [%0], [%1], 16;\n}" :: "r"(dst), "l"(src), "r"(v) : "memory"); }
static __device__ __forceinline__ void red_bf2(void* p, uint32_t v) {
  asm volatile("red.relaxed.gpu.global.add.noftz.bf16x2 [%0], %1;" :: "l"(p), "r"(v) : "memory"); }
static __device__ __forceinline__ void red_bf2p4(void* p, uint32_t v, uint32_t e) {
  asm volatile("{\n.reg .pred q;\nsetp.lt.u32 q, %2, 4;\n@q red.relaxed.gpu.global.add.noftz.bf16x2 [%0], %1;\n}" :: "l"(p), "r"(v), "r"(e) : "memory"); }
static __device__ __forceinline__ void eta2(void* p, uint32_t t, uint32_t first, uint32_t l16) {
  asm volatile("{\n.reg .pred q;\nsetp.lt.u32 q, %3, 32;\n@q red.relaxed.gpu.global.max.u32 [%0+4], %1;\n@q red.relaxed.gpu.global.add.u32 [%0], %2;\n}" :: "l"(p), "r"(t), "r"(first), "r"(l16) : "memory"); }
static __device__ __forceinline__ void sts16(uint32_t a, uint32_t x) { asm volatile("{\n.reg .b16 h;\ncvt.u16.u32 h, %1;\nst.shared.u16 [%0], h;\n}" :: "r"(a), "r"(x) : "memory"); }
static __device__ __forceinline__ uint32_t cnt_word(uint32_t L) { return (L & 17u) | ((L & 6u) << 1) | ((L & 8u) >> 2); }
static __device__ __forceinline__ uint32_t cnt_line(uint32_t l) { return (l & 17u) | ((l & 12u) >> 1) | ((l & 2u) << 2); }
static __device__ __forceinline__ int m3_check(uint32_t sb, const unsigned char* p3, const unsigned char* pd, int dq, uint32_t l16, uint32_t mc, int hf, int s) {
  const uint32_t md = l16 + (sb + SM_MEM + hf * 8192), dd = l16 + (sb + SM_RD + hf * 256), dc = (l16 >> 2) + (sb + SM_RD + hf * 256);
  int n = 0;
  uint32_t c0 = 0, c1 = 0, d0 = 0, d1 = 0, todo = 1;
#pragma unroll 1
  do {
    if (n) {
      const int src = cnt_word(l16 >> 4);
      const uint32_t m0 = __ballot_sync(~0u, (__shfl_sync(~0u, c0, src) >> 16) != 0x4200u) >> (l16 >> 7), m1 = __ballot_sync(~0u, (__shfl_sync(~0u, c1, src) >> 16) != 0x4200u) >> (l16 >> 7);
      const uint32_t m2 = __ballot_sync(~0u, (d0 >> 16) != 0x4200u), m3 = __ballot_sync(~0u, (d1 >> 16) != 0x4200u);
#pragma unroll
      for (int i = 0; i < 8; i++) { cp16p(md + i * 512, p3 + i * 1024, m0 & (1u << (4 * i))); cp16p(md + 4096 + i * 512, p3 + dq + i * 1024, m1 & (1u << (4 * i))); }
      cp16p(dd, pd, l16 < 256u ? (((l16 & 128u) ? m3 : m2) >> ((l16 >> 2) & 28u)) & 15u : 0u);
      sts32(sb + SM_Z + 40, s);
    }
    n++;
    asm volatile("cp.async.commit_group;\ncp.async.wait_group 0;" ::: "memory");
    __syncwarp();
    asm volatile("{\n.reg .pred p, q;\n.reg .b32 a, b;\n.reg .b16 h, g;\nsetp.ne.u32 p, %4, 0;\n"
                 "@p ld.shared.u32 %2, [%6];\n@p ld.shared.u32 %3, [%6+128];\n@p ld.shared.u32 %0, [%5];\n@p ld.shared.u32 %1, [%5+4096];\n"
                 "lop3.b32 a, %2, %3, 0x42000000, 0x7e;\nlop3.b32 b, %0, %1, 0x42000000, 0x7e;\nor.b32 a, a, b;\nsetp.lt.and.u32 q, a, %8, p;\n"
                 "cvt.u16.u32 h, %2;\ncvt.u16.u32 g, %3;\n@q st.shared.u16 [%5+2], h;\n@q st.shared.u16 [%5+4098], g;\n@q mbarrier.arrive.shared::cta.b64 _, [%7];\n"
                 "@q mov.u32 %4, 0;\n}"
                 : "+r"(c0), "+r"(c1), "+r"(d0), "+r"(d1), "+r"(todo) : "r"(mc), "r"(dc), "r"(sb + SM_BAR + MB_MEM + hf * 8), "r"(n < SPIN_LIMIT ? 0x10000u : ~0u) : "memory");
  } while (__any_sync(~0u, todo));
  return n - 1;
}

__global__ void __cluster_dims__(2, 1, 1) __launch_bounds__(384, 1)
rec_kernel(const __grid_constant__ CUtensorMap tmx, const __grid_constant__ CUtensorMap tmw, const __grid_constant__ WMaps W, RecParams P, const __grid_constant__ SideParams SP) {
  extern __shared__ __align__(1024) unsigned char smem[];
  asm volatile("griddepcontrol.launch_dependents;");
  const uint32_t sb = smem_u32(smem);
  const int tid = threadIdx.x, lane = tid & 31, t128 = tid & 127;
  const int wg = __shfl_sync(~0u, tid >> 7, 0), wq = __shfl_sync(~0u, (tid >> 5) & 3, 0);
  const int r = blockIdx.x & 1, pp = blockIdx.x >> 1;
  const int mi = lane >> 3, r8 = lane & 7;
  const uint32_t xb16 = __shfl_sync(~0u, (((sb + SM_X + (tid >> 7) * 32768 + r * 16384) & 0x3FFFF) >> 4) | (1u << 16), 0);
  const uint32_t va16 = __shfl_sync(~0u, (((sb + SM_WVS + (tid >> 7) * 16384) & 0x3FFFF) >> 4) | (64u << 16), 0);
#if defined(PER) || defined(PRO)
  const uint32_t tstart = gt32();
#endif

  if (tid == 0) {
    mbar_init(sb + SM_BAR + MB_F, 1); mbar_init(sb + SM_BAR + MB_F + 8, 1); mbar_init(sb + SM_BAR + MB_XE0, 2); mbar_init(sb + SM_BAR + MB_XE1, 2); mbar_init(sb + SM_BAR + MB_INIT, 2);
    mbar_init(sb + SM_BAR + MB_MEM, 32); mbar_init(sb + SM_BAR + MB_MEM + 8, 32); for (int i = 0; i < 8; i++) mbar_init(sb + SM_BAR + MB_W + i * 8, 1);
    mbar_init(sb + SM_BAR + MB_XF, 8); mbar_init(sb + SM_BAR + MB_X0, 1); mbar_init(sb + SM_BAR + MB_WO, 1); mbar_init(sb + SM_BAR + MB_VR, 5);
    sts32(sb + SM_Z + 40, ~0u);
    asm volatile("fence.mbarrier_init.release.cluster;" ::: "memory");
  }
  if (tid >= 64 && tid < 96) {
    const uint32_t l16 = lane * 16, qa = ((l16 & 0x30u) << 3) | ((l16 & 0x10u) << 2) | ((l16 >> 3) & 0x30u) | ((l16 >> 4) & 4u);
    sts128(sb + SM_QA + l16, qa + (sb + SM_QKP), (qa ^ 64u) + (sb + SM_QKP), 0u, 0u);
  }
  if (tid == 32) {
    asm volatile("prefetch.tensormap [%0];" :: "l"(&W.q) : "memory"); asm volatile("prefetch.tensormap [%0];" :: "l"(&W.k) : "memory");
    asm volatile("prefetch.tensormap [%0];" :: "l"(&W.v) : "memory"); asm volatile("prefetch.tensormap [%0];" :: "l"(&tmx) : "memory");
  }
  if (tid >= 256 && tid < 320) {
    unsigned char* pl = P.win + r * W_2 + (W_UP | (1u << 19) | ((pp >> 5) << 14)) + (pp & 31) * 128 + wq * 4096;
    stg_r1(pl + lane * 4, 0u);
    uint32_t best = 1u << 30;
    if (lane == 0) {
#pragma unroll 1
      for (int rep = 0; rep < NPROBE; rep++) {
        uint32_t dt;
        asm volatile("{\n.reg .u32 a, b, v;\nmov.u32 a, %%clock;\natom.relaxed.gpu.global.exch.b32 v, [%1], 0;\n"
                     "st.volatile.shared.u32 [%2], v;\nmov.u32 b, %%clock;\nsub.u32 %0, b, a;\n}" : "=r"(dt) : "l"(pl), "r"(sb + SM_SIDE + wq * 4) : "memory");
        best = min(best, dt);
      }
    }
    if (lane == 0) sts32(sb + SM_SIDE + wq * 4, best);
    bar_sync(B_P, 64);
    if (wq == 0) {
      const uint2 bt = lds64(sb + SM_SIDE);
      if (lane < 8 && (r == 0 || pp == 0)) stg_r1(&g_side[(r ? 66 : pp) * 32 + lane], 2u | (bt.x < bt.y ? 1u : 0u));
      spin(DLY_TB);
      uint32_t a, b, c; int n = 0;
#pragma unroll 1
      do {
        a = ldg_r1(&g_side[lane * 32]); b = ldg_r1(&g_side[(32 + lane) * 32]); c = ldg_r1(&g_side[(64 + min(lane, 2)) * 32]);
      } while (!__all_sync(~0u, a & b & c & 2u) && ++n < SPIN_LIMIT);
      a = __ballot_sync(~0u, a & 1u); b = __ballot_sync(~0u, b & 1u); c = __ballot_sync(~0u, c & 1u);
      const uint32_t pol2 = (a ^ (c >> 2)) & 1u;
      c &= 3u;
      const unsigned long long ab = ((unsigned long long)b << 32) | a;
      const int sd = pp < 64 ? (int)(ab >> pp) & 1 : (int)(c >> (pp - 64)) & 1;
      const int n1 = __popcll(ab) + __popc(c), n0 = 66 - n1;
      const int below1 = pp < 64 ? __popcll(ab & ((1ull << pp) - 1)) : __popcll(ab) + (pp == 65 ? (int)(c & 1u) : 0);
      const int rk = sd ? below1 : pp - below1;
      const int k0 = (n0 & 1) ? n0 - 1 : n0 >= n1 ? n0 - 2 : n0, k1 = 64 - k0;
      const int role = rk >= (sd ? k1 : k0) ? 64 + ((n0 & 1) ? sd : rk - (sd ? k1 : k0)) : sd ? k0 + rk : rk;
      __syncwarp();
      if (lane == 0) sts128(sb + SM_SIDE, 2 * k0, 0u, pol2, role * 2 + r);
#ifdef PER
      if (lane == 0) { atomicMax(&g_end[6], gt32()); atomicMin(&g_end[7], max(bt.x, bt.y) - min(bt.x, bt.y)); }
#endif
    }
  }
  __syncthreads();
  const int cta = __shfl_sync(~0u, (int)lds32(sb + SM_SIDE + 12), 0), h = cta >> 2, j = cta & 3, p = j >> 1;
  const int sw = (cta >= __shfl_sync(~0u, (int)lds32(sb + SM_SIDE), 0) ? 1 : 0) ^ r;
  if (cta >= NCTA) {
    spin(DLY_SIDE);
#ifndef NOSIDE
    side_work(SP, smem, cta - NCTA);
#endif
#ifdef PER
    if (threadIdx.x == 0) atomicMax(&g_end[1], gt32());
#endif
    return;
  }
#ifdef PER
  if (threadIdx.x == 0) g_per[cta][63] = tstart;
#endif
#ifdef PRO
  if (tid == 0) { g_pro[cta][0] = tstart; g_pro[cta][1] = gt32(); }
#endif
  asm volatile("barrier.cluster.arrive.relaxed.aligned;" ::: "memory");
#define WLOAD(i0, i1) _Pragma("unroll 1") for (int u = i0; u < i1; u++) {        \
    const int g2 = u >> 2, i = u & 3, k = g2 * 512 + ((i * 128 + r * 256) & 511); \
    const uint32_t mb = sb + SM_BAR + MB_W + u * 8; \
    mbar_expect_tx(mb, i < 2 ? 32768 : 16384); \
    tma_load_2d(sb + g2 * 65536 + i * 8192, &W.q, h * DH + j * 32, k, mb); \
    tma_load_2d(sb + g2 * 65536 + 32768 + i * 8192, &W.k, h * DH + j * 32, k, mb); \
    if (i < 2) tma_load_2d(sb + (i ? SM_WVS : SM_VST) + g2 * 16384, &W.v, h * DH + p * 64, k, mb); }
  if (tid == 288) {
    mbar_expect_tx(sb + SM_BAR + MB_X0, 32768);
#pragma unroll 1
    for (int i = 0; i < 2; i++)
      asm volatile("cp.async.bulk.tensor.3d.shared::cluster.global.mbarrier::complete_tx::bytes [%0], [%1, {%3, %3, %4}], [%2];"
                   :: "r"(sb + SM_MEM + i * 16384), "l"(&tmx), "r"(sb + SM_BAR + MB_X0), "r"(0), "r"(i * 4) : "memory");
    WLOAD(0, 4 + WSPL);
  }
  __syncwarp();
  asm volatile("barrier.cluster.wait.acquire.aligned;" ::: "memory");
#define SIDES() const uint4 sm2 = lds128(sb + SM_SIDE); const int nlo = sm2.x; const uint32_t me = cta >= nlo

#define XLOAD(t, sg) tma_load_mc(sb + SM_X + ((t) * 8 + r * 4) * 4096, &tmx, (sg) * SEG, (t) * 8 + r * 4, sb + SM_BAR + MB_F + (t) * 8)
#define F0LOAD() do { mbar_wait(sb + SM_BAR + MB_XE0, s & 1); \
    if (l16 == 0) XLOAD(0, s + 2); \
    __syncwarp(); } while (0)
  if (wg < 2) {
    asm volatile("setmaxnreg.inc.sync.aligned.u32 " STR(RF_FAT) ";");
    uint32_t w[32][4], wv[8][4];
    uint32_t lm = ((mi >> 1) * 8 + r8) * 128 + (((wq * 2 + (mi & 1)) ^ r8) << 4), l16 = lane * 16;
    lm = __shfl_sync(~0u, lm, lane); l16 = __shfl_sync(~0u, l16, lane);
    {
      const uint32_t lq0 = sb + wg * 65536 + (wq >> 1) * 32768 + ((mi >> 1) * 8 + r8) * 64 + ((((wq & 1) * 2 + (mi & 1)) ^ (r8 >> 1)) << 4);
      const uint32_t f = wq < 2 ? 0x3D003D00u : 0x3F803F80u;
#pragma unroll
      for (int i = 0; i < 4; i++) {
        mbar_wait(sb + SM_BAR + MB_W + (wg * 4 + i) * 8, 0);
        if (i == 3) PT(2 + wg, t128 == 0);
#pragma unroll
        for (int kk = 8 * i; kk < 8 * i + 8; kk++) ldmatrix_x4_trans(w[kk], lq0 + kk * 1024);
        if (i == 0) {
#pragma unroll
          for (int kk = 0; kk < 8; kk++) ldmatrix_x4_trans(wv[kk], sb + SM_VST + wg * 16384 + kk * 2048 + lm);
        }
#pragma unroll
        for (int kk = 32 * i; kk < 32 * i + 32; kk++) w[kk >> 2][kk & 3] = mulb2v(w[kk >> 2][kk & 3], f);
      }
    }
    if (wg == 0) bar_sync(B_V, 160);
    else bar_arrive(B_P, 160);
    const int w8 = wg * 4 + wq;
    const int cw = sw ^ wg;
    const uint32_t xh16 = xb16 ^ 1024u;
    const uint32_t rsb = mapa(sb, r ^ 1);
#define MT (l16 + (sb + SM_MEM + wg * 8192))
#define WA (lm + (sb + SM_WVS + wg * 16384))
#define WOF(f) (lm + (sb + SM_WOS + wg * 32768 + ((f) & 1) * 16384 + ((f) >> 1) * 2048))
#define TH(base) (l16 + (sb + (base) + w8 * 512))
#define TQ(base) (l16 + (sb + (base) + wq * 512))
#define DUMP(base) _Pragma("unroll") for (int n = 0; n < 4; n++) sts128f(TQ((base) + n * 2048), d[4 * n], d[4 * n + 1], d[4 * n + 2], d[4 * n + 3])
#define INIT(base) _Pragma("unroll") for (int n = 0; n < 4; n++) { const float4 t = lds128f(TQ((base) + n * 2048)); d[4 * n] = t.x; d[4 * n + 1] = t.y; d[4 * n + 2] = t.z; d[4 * n + 3] = t.w; }
#define XQK(first, b0, b1) do { wg_fence(); XR<0, 16, 0, 32, first>::run(d, w, b0); XR<0, 16, 16, 32, 0>::run(d, w, b1); wg_commit(); wg_wait0(); } while (0)
#define XVS(first, b0) do { wg_fence(); XS<8, 8, 16, first>::run(d, va16, b0); XR<0, 8, 0, 8, 0>::run(d, wv, b0); wg_commit(); wg_wait0(); } while (0)
#define XREL(mb) do { if (wq == 0 && l16 == 0) { mbar_arrive_cluster_rlx(rsb + SM_BAR + (mb)); mbar_arrive(sb + SM_BAR + (mb)); } } while (0)
#define XFOUT() do { \
          _Pragma("unroll") for (int hf = 0; hf < 2; hf++) \
            stsm4t(l16 + (sb + SM_XF + (wq * 2 + hf) * 512), pack_bf16(d[8 * hf], d[8 * hf + 1]), pack_bf16(d[8 * hf + 2], d[8 * hf + 3]), \
                   pack_bf16(d[8 * hf + 4], d[8 * hf + 5]), pack_bf16(d[8 * hf + 6], d[8 * hf + 7])); \
          __syncwarp(); \
          if (l16 < 32) mbar_arrive(sb + SM_BAR + MB_XF); } while (0)
#define VDUMP(base) _Pragma("unroll") for (int n = 0; n < 2; n++) sts128(TQ((base) + n * 2048), pack_bf16(d[8 * n], d[8 * n + 1]), pack_bf16(d[8 * n + 2], d[8 * n + 3]), pack_bf16(d[8 * n + 4], d[8 * n + 5]), pack_bf16(d[8 * n + 6], d[8 * n + 7]))

    if (wg == 0) {
      float d[16];
      const uint32_t x0 = (((sb + SM_MEM + r * 16384) & 0x3FFFF) >> 4) | (1u << 16), x1 = (((sb + SM_MEM + (r ^ 1) * 16384) & 0x3FFFF) >> 4) | (1u << 16);
      mbar_wait(sb + SM_BAR + MB_X0, 0);
      XQK(1, x0, x1);
      DUMP(SM_CQ);
      XVS(1, x0);
      bar_arrive(B_X2, 256);
      VDUMP(SM_CV);
      bar_sync(B_CQ, 256);
    } else {
      float d[16];
      bar_sync(B_CQ, 256);
      INIT(SM_CQ);
      mbar_wait(sb + SM_BAR + MB_F + 8, 0);
      PT(4, t128 == 0);
      XQK(0, xb16, xh16);
      XFOUT();
      PT(5, t128 == 0);
    }
    if (wg == 0) mbar_wait(sb + SM_BAR + MB_F, 0);
    for (int s = -1;; s++) {
      if (s >= 0) {
        OPAQUE_R(lm); OPAQUE_R(l16);
        {
          uint32_t sa[4][4];
#pragma unroll
          for (int i = 0; i < 2; i++) ldmatrix_x4_trans(sa[i], WA + i * 2048);
          float a[2][4], v[2][4]; uint4 c[4]; uint2 qa;
          FENCE();
          mbar_wait(sb + SM_BAR + MB_MEM + wg * 8, s & 1);
#define QP(i) ((i) >= 12 ? (i) - 8 : (i) % 3 == 1 ? (i) / 3 : 8 + (i) - ((i) + 2) / 3)
#pragma unroll
          for (int i = 0; i < 3; i++) c[i] = ldsm4t(MT + QP(i) * 512);
#pragma unroll
          for (int i = 0; i < 16; i++) {
            if (i + 3 < 16) c[(i + 3) & 3] = ldsm4t(MT + QP(i + 3) * 512);
            if (i == 13) qa = lds64(l16 + (sb + SM_QA));
            if (i == 0) {
              mma4z(a[0], w[2 * QP(i)][0], w[2 * QP(i)][1], w[2 * QP(i)][2], w[2 * QP(i)][3], c[i & 3].x, c[i & 3].y);
              mma4z(a[1], w[2 * QP(i) + 1][0], w[2 * QP(i) + 1][1], w[2 * QP(i) + 1][2], w[2 * QP(i) + 1][3], c[i & 3].z, c[i & 3].w);
            } else {
              mma_16816(a[0], w[2 * QP(i)], c[i & 3].x, c[i & 3].y);
              mma_16816(a[1], w[2 * QP(i) + 1], c[i & 3].z, c[i & 3].w);
            }
            if (QP(i) == 0) {
              mma4z(v[0], wv[0][0], wv[0][1], wv[0][2], wv[0][3], c[i & 3].x, c[i & 3].y);
              mma4z(v[1], wv[1][0], wv[1][1], wv[1][2], wv[1][3], c[i & 3].z, c[i & 3].w);
            } else if (QP(i) < 4) {
              mma_16816(v[0], wv[2 * (QP(i) & 3)], c[i & 3].x, c[i & 3].y);
              mma_16816(v[1], wv[2 * (QP(i) & 3) + 1], c[i & 3].z, c[i & 3].w);
            }
            if (i == 12) {
              mma_16816(v[0], sa[0], c[0].x, c[0].y); mma_16816(v[1], sa[1], c[0].z, c[0].w);
            }
            if (i == 13) { ldmatrix_x4_trans(sa[0], WA + 2 * 2048); ldmatrix_x4_trans(sa[1], WA + 3 * 2048); ldmatrix_x4_trans(sa[2], WA + 4 * 2048); }
            FENCE();
          }
#pragma unroll
          for (int i = 0; i < 4; i++) sts32(((i & 1) ? qa.y : qa.x) + (w8 * 512 + (i >> 1) * 8), f2u(a[0][i] + a[1][i]));
          bar_arrive(B_QK, 288);
          bar_arrive(B_QK1, 288);
          FENCE();
          uint32_t sc2[4];
          ldmatrix_x4_trans(sa[3], WA + 5 * 2048); ldmatrix_x4_trans(sc2, WA + 6 * 2048);
          mma_16816(v[0], sa[0], c[1].x, c[1].y); mma_16816(v[1], sa[1], c[1].z, c[1].w);
          FENCE();
          ldmatrix_x4_trans(sa[0], WA + 7 * 2048);
          FENCE();
          mma_16816(v[0], sa[2], c[2].x, c[2].y); mma_16816(v[1], sa[3], c[2].z, c[2].w);
          mma_16816(v[0], sc2, c[3].x, c[3].y); mma_16816(v[1], sa[0], c[3].z, c[3].w);
          FENCE();
          sts128f(TH(SM_VP), v[0][0] + v[1][0], v[0][1] + v[1][1], v[0][2] + v[1][2], v[0][3] + v[1][3]);
          bar_arrive(B_V, 320);
        }
        if (s == NSEG - 1) break;
        OPAQUE_R(lm); OPAQUE_R(l16);
        uint32_t wo[WPF][4];
        {
          float d[16];
#define XOUT(g) _Pragma("unroll") for (int n = 0; n < 2; n++) sts128f(TQ(SM_CQ + ((g) * 2 + n) * 2048), d[8 - 8 * (g) + 4 * n], d[9 - 8 * (g) + 4 * n], d[10 - 8 * (g) + 4 * n], d[11 - 8 * (g) + 4 * n])
#define XIN(g) do { \
            const float4 t0 = lds128f(TQ(SM_CQ + (2 - 2 * (g)) * 2048)), t1 = lds128f(TQ(SM_CQ + (3 - 2 * (g)) * 2048)); \
            stsm4t(l16 + (sb + SM_XF + (wq * 2 + (g)) * 512), pack_bf16(d[8 * (g)] + t0.x, d[8 * (g) + 1] + t0.y), pack_bf16(d[8 * (g) + 2] + t0.z, d[8 * (g) + 3] + t0.w), \
                   pack_bf16(d[8 * (g) + 4] + t1.x, d[8 * (g) + 5] + t1.y), pack_bf16(d[8 * (g) + 6] + t1.z, d[8 * (g) + 7] + t1.w)); } while (0)
          if (wg == 0) {
            INIT(SM_CW);
            bar_sync(B_PUB, 320);
            wg_fence();
            XR<KB, 16, 0, 32, 0>::run(d, w, xb16); XR<0, 16, 16, 32, 0>::run(d, w, xh16);
            wg_commit(); wg_wait0();
            TSF(13, 1);
            OPAQUE_R(l16);
            XOUT(0);
            bar_arrive(B_G1, 256);
            XREL(MB_XE0);
            bar_sync(B_CQ, 256);
            XIN(0);
#pragma unroll
            for (int f = 0; f < WPA; f++) ldmatrix_x4_trans(wo[f], WOF(f));
          } else {
            const uint32_t ok = mbar_test(sb + SM_BAR + MB_F + 8, (s + 1) & 1);
            bar_sync(B_PUB, 320);
            if (!ok) mbar_wait(sb + SM_BAR + MB_F + 8, (s + 1) & 1);
            wg_fence();
#if WKP
            XR<0, 16, 0, 32, 1>::run(d, w, xb16); XR<0, WKP - 16, 16, 32, 0>::run(d, w, xh16);
            wg_commit(); wg_fence();
            XR<WKP - 16, WKP - 15, 16, 32, 0>::run(d, w, xh16);
#pragma unroll
            for (int f = 0; f < WPA; f++) ldmatrix_x4_trans(wo[f], WOF(f));
            wg_commit(); wg_fence();
            XR<WKP - 15, 16, 16, 32, 0>::run(d, w, xh16);
            wg_commit();
#else
            XR<0, 16, 0, 32, 1>::run(d, w, xb16); XR<0, 16, 16, 32, 0>::run(d, w, xh16);
            wg_commit();
#pragma unroll
            for (int f = 0; f < WPA; f++) ldmatrix_x4_trans(wo[f], WOF(f));
#endif
            wg_wait0();
            TSF(31, 5);
            OPAQUE_R(l16);
            XOUT(1);
            bar_arrive(B_CQ, 256);
            bar_sync(B_G1, 256);
            XIN(1);
          }
          __syncwarp();
          if (l16 == 0) mbar_arrive(sb + SM_BAR + MB_XF);
          TSF(3, 5);
        }
        if (Z1 && s == 0) {
          mbar_wait(sb + SM_BAR + MB_WO, 0);
#pragma unroll
          for (int f = 0; f < WPA; f++) ldmatrix_x4_trans(wo[f], WOF(f));
        }
#pragma unroll
        for (int f = WPA; f < WPF; f++) ldmatrix_x4_trans(wo[f], WOF(f));
        unsigned char* pa = P.win + (w_ar(s) + (j * 32 + cw * 16 + wq * 2) * 256 + (l16 >> 2));
        uint32_t ce = (l16 >> 4) - 4 * (cw * 4 + wq);
        OPAQUE_L(pa); OPAQUE_R(ce);
        FENCE();
        bar_sync(wg ? B_O : B_O2, wg || !XG ? 192 : 224);
        uint4 ob[2];
        ob[0] = ldsm4(l16 + (sb + SM_OF)); ob[1] = ldsm4(l16 + (sb + SM_OF + 512));
        float acc[2][4]; uint32_t f0ok;
#pragma unroll
        for (int f = 0; f < 16; f++) {
          const int ks = f >> 1;
          const uint32_t b0 = (ks & 1) ? ob[(ks >> 1) & 1].z : ob[(ks >> 1) & 1].x, b1 = (ks & 1) ? ob[(ks >> 1) & 1].w : ob[(ks >> 1) & 1].y;
          if (f < 2) mma4z(acc[f], wo[f][0], wo[f][1], wo[f][2], wo[f][3], b0, b1);
          else mma_16816(acc[f % 2], wo[f < WPF ? f : 2 + (f - WPF) % (WPF - 2)], b0, b1);
          if (f - 1 >= 2 && f - 1 + (WPF - 2) < 16) {
            const int nf = f - 1 + (WPF - 2);
            ldmatrix_x4_trans(wo[2 + (nf - WPF) % (WPF - 2)], WOF(nf));
          }
          if (f == 4 || f == 8) ob[((f >> 2) - 1) & 1] = ldsm4(l16 + (sb + SM_OF + (1 + (f >> 2)) * 512));
          if (f == 12) f0ok = mbar_test(sb + SM_BAR + MB_F, (s + 1) & 1);
          if (f < 15) FENCE();
        }
        if (!wg) bar_arrive(B_CV, 256);
        red_bf2(pa, pack_bf16(acc[0][0], ce == 0 ? 1.f : acc[0][1])); red_bf2(pa + 256, pack_bf16(acc[0][2], ce == 1 ? 1.f : acc[0][3]));
        red_bf2(pa + 2048, pack_bf16(acc[1][0], ce == 2 ? 1.f : acc[1][1])); red_bf2(pa + 2304, pack_bf16(acc[1][2], ce == 3 ? 1.f : acc[1][3]));
        red_bf2p4(pa + (W_DS + (wq & 1) * 256), pack_bf16(ce == 0 ? acc[0][1] : ce == 1 ? acc[0][3] : ce == 2 ? acc[1][1] : acc[1][3], 1.f), ce);
        TSF(4, 1); TSF(2, 6);
        if (wg) bar_sync(B_CV, 256);
        else if (!f0ok) mbar_wait(sb + SM_BAR + MB_F, (s + 1) & 1);
      }
      OPAQUE_R(lm); OPAQUE_R(l16);
      {
        float d[16];
        const uint32_t cv = TQ(SM_CV + ((s ^ wg) & 1) * 4096);
        TSF(9, 1);
        wg_fence();
        XR<0, 1, 0, 8, 1>::run(d, wv, xb16); XS<8, 8, 9, 0>::run(d, va16, xb16); XR<1, 2, 0, 8, 0>::run(d, wv, xb16); XS<9, 8, 10, 0>::run(d, va16, xb16);
        XR<2, 3, 0, 8, 0>::run(d, wv, xb16); XS<10, 8, 11, 0>::run(d, va16, xb16); XR<3, 4, 0, 8, 0>::run(d, wv, xb16); XS<11, 8, 12, 0>::run(d, va16, xb16);
        XR<4, 5, 0, 8, 0>::run(d, wv, xb16); XS<12, 8, 13, 0>::run(d, va16, xb16); XR<5, 6, 0, 8, 0>::run(d, wv, xb16); XS<13, 8, 14, 0>::run(d, va16, xb16);
        XR<6, 7, 0, 8, 0>::run(d, wv, xb16); XS<14, 8, 15, 0>::run(d, va16, xb16); XR<7, 8, 0, 8, 0>::run(d, wv, xb16); XS<15, 8, 16, 0>::run(d, va16, xb16);
        wg_commit(); wg_wait0();
        uint32_t q[8];
#pragma unroll
        for (int i = 0; i < 8; i++) q[i] = pack_bf16(d[2 * i], d[2 * i + 1]);
        if (wg == 0) {
          sts128(cv, q[0], q[1], q[2], q[3]); sts128(cv + 2048, q[4], q[5], q[6], q[7]);
          wg_fence(); XR<0, KB, 0, 32, 1>::run(d, w, xb16); wg_commit(); wg_wait0();
          OPAQUE_R(l16);
          DUMP(SM_CW);
          TSF(5, 1);
        } else {
          const uint4 o = lds128(cv + (r ^ 1) * 2048), k = lds128(cv + r * 2048);
          XREL(MB_XE1);
          st_async4(l16 + (rsb + SM_VR + wq * 512), u2f(addb2(r ? q[0] : q[4], o.x)), u2f(addb2(r ? q[1] : q[5], o.y)), u2f(addb2(r ? q[2] : q[6], o.z)), u2f(addb2(r ? q[3] : q[7], o.w)),
                    rsb + SM_BAR + MB_VR);
          sts128(TQ(SM_VL), addb2(r ? q[4] : q[0], k.x), addb2(r ? q[5] : q[1], k.y), addb2(r ? q[6] : q[2], k.z), addb2(r ? q[7] : q[3], k.w));
          __syncwarp();
          if (l16 == 0) mbar_arrive(sb + SM_BAR + MB_VR);
          TSF(28, 5);
        }
      }
    }
  } else {
    asm volatile("setmaxnreg.dec.sync.aligned.u32 " STR(RF_CTL) ";");
    const int g = lane >> 2, tq = lane & 3;
    if (wq == 0) {
      if (lane < 12) asm volatile("prefetch.global.L2 [%0];" :: "l"(SP.x + (size_t)(cta * 12 + lane) * 64));
      __syncwarp();
      {
        SIDES();
        const uint32_t o[6] = {w_blk(w_h1(cta), me), w_blk(w_h1(cta) ^ H1_V, me), w_blk(w_mvx(cta, 0), me ^ sm2.z), w_blk(w_mvx(cta, 1), me ^ sm2.z),
                               w_blk(w_mxa(cta, 0), me ^ sm2.z), w_blk(w_mxa(cta, 1), me ^ sm2.z)};
#pragma unroll
        for (int i = 0; i < 24; i++) stg_r4(P.win + (o[i >> 2] + (i & 3) * 512 + lane * 16), 0u, 0u, 0u, 0u);
#pragma unroll
        for (int i = 0; i < 6; i++) stg_r1(P.win + (w_ar(i >> 1) + cta * 256 + (i & 1) * W_DS + lane * 4), 0u);
        __threadfence();
        __syncwarp();
      }
      {
        const uint32_t wv = movm(*reinterpret_cast<const uint32_t*>(P.mem0 + g * DM + cta * 8 + tq * 2));
        const bool sp = lane == cnt_word(cta & 31);
        stg_r1(P.win + (w_ar(-1) + cta * 256 + lane * 4), sp ? (wv & 0xffffu) | 0x42000000u : wv);
        if (sp) stg_r1(P.win + (w_ar(-1) + ((cta & ~9) + ((cta >> 1) & 1)) * 256 + W_DS + lane * 4), (wv >> 16) | 0x42000000u);
      }
      bar_sync(B_V, 160);
      if (lane == 0) {
        fence_async_smem(); mbar_arrive_cluster_rlx(mapa(sb + SM_BAR + MB_INIT, 0)); mbar_arrive_cluster_rlx(mapa(sb + SM_BAR + MB_INIT, 1));
        mbar_wait(sb + SM_BAR + MB_INIT, 0);
        mbar_expect_tx(sb + SM_BAR + MB_F, 32768);
        mbar_expect_tx(sb + SM_BAR + MB_F + 8, 32768);
        XLOAD(1, 0); XLOAD(0, 1);
        WLOAD(4 + WSPL, 8);
      }
      __syncwarp();
#ifdef PER
      if (lane == 0) atomicMax(&g_end[5], gt32());
#endif
    }
    bar_sync(B_X2, 256);
    SIDES();
    uint32_t l16 = __shfl_sync(~0u, lane * 16, lane);
    const uint32_t me2 = me ^ sm2.z;
    const float sc = 32.f * 0.08838834764831845f * 1.4426950408889634f;
    uint32_t ls = l16 + sb;
#define PVM(o, zs, p0, p2, M1, M2, M3) do { \
        FENCE(); \
        mma4z(zs, 0x3F803F80u, 0x3F803F80u, 0x3F803F80u, 0x3F803F80u, p0.x, p0.y); \
        FENCE(); M1; \
        _Pragma("unroll") for (int t = 0; t < 4; t++) mma4z(o[t], va[2 * t].x, va[2 * t].y, va[2 * t].z, va[2 * t].w, p0.x, p0.y); \
        FENCE(); M2; \
        mma4(zs, 0x3F803F80u, 0x3F803F80u, 0x3F803F80u, 0x3F803F80u, p0.z, p0.w); \
        _Pragma("unroll") for (int t = 0; t < 2; t++) mma4(o[t], va[2 * t + 1].x, va[2 * t + 1].y, va[2 * t + 1].z, va[2 * t + 1].w, p0.z, p0.w); \
        FENCE(); M3; \
        mma_1688(zs, 0x3F803F80u, 0x3F803F80u, p2); \
        _Pragma("unroll") for (int t = 2; t < 4; t++) mma4(o[t], va[2 * t + 1].x, va[2 * t + 1].y, va[2 * t + 1].z, va[2 * t + 1].w, p0.z, p0.w); \
        mma_1688(o[0], vm[0].x, vm[0].y, p2); mma_1688(o[1], vm[0].z, vm[0].w, p2); mma_1688(o[2], vm[1].x, vm[1].y, p2); mma_1688(o[3], vm[1].z, vm[1].w, p2); } while (0)
#define PVE(o, z, dst) do { \
        const float i0 = rcpf(z[0]), i1 = rcpf(z[1]); \
        _Pragma("unroll") for (int u = 0; u < 2; u++) \
          stsm4t(ls + (dst) + u * 1024, pack_bf16(o[2 * u][0] * i0, o[2 * u][1] * i1), pack_bf16(o[2 * u][2] * i0, o[2 * u][3] * i1), \
                 pack_bf16(o[2 * u + 1][0] * i0, o[2 * u + 1][1] * i1), pack_bf16(o[2 * u + 1][2] * i0, o[2 * u + 1][3] * i1)); } while (0)
    const uint32_t lq = (l16 ^ ((l16 >> 1) & 64u)) + sb, l12 = (l16 >> 2) * 3;
#define M3PTR(sl) \
            const uint32_t tf = me ^ 1 ^ r, m3i = w_ar(sl) + (wq & 1) * 16384 + (l16 & 0x70u) + ((l16 & 0x180u) << 1); \
            const unsigned char* p0f = P.win + (m3i + r * 8192 + tf * 4096); const unsigned char* p0n = P.win + (m3i + r * 8192 + (tf ^ 1) * 4096); \
            const unsigned char* p1f = P.win + (m3i + (r ^ 1) * 8192 + (tf ^ 1) * 4096); const unsigned char* p1n = P.win + (m3i + (r ^ 1) * 8192 + tf * 4096); \
            const unsigned char* pd = P.win + (w_ar(sl) + (wq & 1) * 16384 + (((l16 >> 7) ^ r) & 1u) * 8192 + ((l16 & 64u) * 4 + (l16 & 48u) * 2 + (l16 & 16u)) * 16 + W_DS + (l16 & 0x70u)); \
            uint32_t mf = ls + SM_MEM + (wq & 1) * 8192 + tf * 2048, mn = ls + SM_MEM + (wq & 1) * 8192 + (tf ^ 1) * 2048, nr = l16 < 256u ? 1u + (((l16 >> 6) ^ (l16 >> 7) ^ tf) & 1u) : 0u; \
            OPAQUE_L(p0f); OPAQUE_L(p0n); OPAQUE_L(p1f); OPAQUE_L(p1n); OPAQUE_L(pd); OPAQUE_R(mf); OPAQUE_R(mn); OPAQUE_R(nr); FENCE()
#define M3REQ() \
            _Pragma("unroll") for (int i = 0; i < 4; i++) { cp16(mn + 4096 + i * 512, p1f + i * 1024); cp16(mf + i * 512, p0f + i * 1024); } \
            cp16p(ls + SM_RD + (wq & 1) * 256, pd, nr & 1u); \
            _Pragma("unroll") for (int i = 0; i < 4; i++) { cp16(mf + 4096 + i * 512, p1n + i * 1024); cp16(mn + i * 512, p0n + i * 1024); } \
            cp16p(ls + SM_RD + (wq & 1) * 256, pd, nr & 2u)
    if (wq >= 2) { M3PTR(-1); M3REQ(); }
    if (wq == 0) {
      bar_sync(B_P, 160);
      if (l16 == 0) {
        fence_async_smem();
        mbar_expect_tx(sb + SM_BAR + MB_WO, 65536);
        for (int i = 0; i < 8; i++) tma_load_2d(sb + SM_WOS + i * 8192, &tmw, j * 256 + ((i >> 1) ^ (2 * sw)) * 64, h * DH + (i & 1) * 64, sb + SM_BAR + MB_WO);
      }
      __syncwarp();
    }
#define ETA(k, first) ETAT(gt32() + (k), first)
#define ETAT(tm, first) do { unsigned char* pt = P.win + (w_ar(s) + (W_DS + 256) + (cta >> 5) * 8192 + ((cta >> 4) & 1) * 2048 + (l16 & 16u) * 256); \
          asm volatile("{\n.reg .pred q;\nsetp.lt.u32 q, %2, 32;\n@q red.relaxed.gpu.global.max.u32 [%0+4], %1;\n}" :: "l"(pt), "r"(tm), "r"(l16) : "memory"); \
          if (first) asm volatile("{\n.reg .pred q;\nsetp.lt.u32 q, %1, 32;\n@q red.relaxed.gpu.global.add.u32 [%0], 1;\n}" :: "l"(pt), "r"(l16) : "memory"); } while (0)
    if (wq == 1) {
      const uint32_t xin = w_blk(w_mxa(cta, 0), me2) + l16;
      const uint32_t lsq = sb + ((l16 & 0x70u) | ((l16 & 0x80u) << 1) | ((l16 & 0x100u) >> 1));
      mbar_wait(sb + SM_BAR + MB_MEM, 0); mbar_wait(sb + SM_BAR + MB_MEM + 8, 0);
      for (int s = 0; s < NSEG; s++) {
        const uint32_t t2 = ((s >> 1) & 1) ^ 1;
        mbar_wait(sb + SM_BAR + MB_XF, s & 1);
        {
        uint4 kx[4], qx[4];
#pragma unroll
        for (int i = 0; i < 4; i++) { kx[i] = ldsm4(ls + (SM_XF + (4 + i) * 512)); qx[i] = ldsm4(lsq + (SM_XF + i * 512)); }
        const uint32_t db = w_blk(w_mxa(h * 4, s), me2) + l16 - 512;
        {
          float S[2][4][4];
          if (XG == 2 && s > 0) bar_arrive(B_O2, 224);
          FENCE();
#pragma unroll
          for (int mt = 0; mt < 2; mt++) {
            const uint4 q0 = qx[mt];
            mma4z(S[mt][0], q0.x, q0.y, q0.z, q0.w, kx[0].x, kx[0].y); mma4z(S[mt][1], q0.x, q0.y, q0.z, q0.w, kx[0].z, kx[0].w);
            mma4z(S[mt][2], q0.x, q0.y, q0.z, q0.w, kx[1].x, kx[1].y); mma4z(S[mt][3], q0.x, q0.y, q0.z, q0.w, kx[1].z, kx[1].w);
          }
#pragma unroll
          for (int mt = 0; mt < 2; mt++) {
            const uint4 q1 = qx[2 + mt];
            mma4(S[mt][0], q1.x, q1.y, q1.z, q1.w, kx[2].x, kx[2].y); mma4(S[mt][1], q1.x, q1.y, q1.z, q1.w, kx[2].z, kx[2].w);
            mma4(S[mt][2], q1.x, q1.y, q1.z, q1.w, kx[3].x, kx[3].y); mma4(S[mt][3], q1.x, q1.y, q1.z, q1.w, kx[3].z, kx[3].w);
          }
          FENCE();
          if (XG == 1 && s > 0) bar_arrive(B_O2, 224);
          FENCE();
#pragma unroll
          for (int u = 0; u < 4; u++) {
            const int mt = u >> 1, c = 2 * (u & 1);
            const uint32_t m0 = tagw(pack_f16(S[mt][0][c], S[mt][0][c + 1]), t2), m1 = pack_f16(S[mt][1][c], S[mt][1][c + 1]),
                           m2 = pack_f16(S[mt][2][c], S[mt][2][c + 1]), m3 = pack_f16(S[mt][3][c], S[mt][3][c + 1]);
            const int e = u ^ j;
            if (e) stg_r4(P.win + (db + mt * 16384 + (u & 1) * 2048 + e * 512), m0, m1, m2, m3);
            else sts128(ls + SM_XS, m0, m1, m2, m3);
          }
        }
        TS(15);
        float sx[10];
        const unsigned char* pa = P.win + (xin + ((s & 1) << 20));
        uint4 xv[3];
        if (s > 0) spin(DLY_XD);
#pragma unroll
        for (int i = 0; i < 3; i++) xv[i] = ldg_r4(pa + i * 512);
        FENCE();
        int n = 0; float mx;
        auto xsum = [&]() {
#pragma unroll 1
        while (__any_sync(~0u, (x3(xv[0].x, xv[1].x, t2) | (xv[2].x ^ t2)) & 1u) && ++n < SPIN_LIMIT) {
#pragma unroll
          for (int i = 0; i < 3; i++) xv[i] = ldg_r4(pa + i * 512);
        }
        {
          const uint4 v3 = lds128(ls + SM_XS);
          sum_h4(sx[2], sx[3], xv[0].x, xv[1].x, xv[2].x, v3.x); sum_h4(sx[4], sx[5], xv[0].y, xv[1].y, xv[2].y, v3.y);
          sum_h4(sx[6], sx[7], xv[0].z, xv[1].z, xv[2].z, v3.z); sum_h4(sx[8], sx[9], xv[0].w, xv[1].w, xv[2].w, v3.w);
          const int row = 8 * j + g - 2 * tq;
#pragma unroll
          for (int i = 0; i < 8; i++) if ((i >> 1) * 8 + (i & 1) > row) sx[2 + i] = -INFINITY;
        }
        mx = fmaxf(fmaxf(fmaxf(sx[2], sx[3]), fmaxf(sx[4], sx[5])), fmaxf(fmaxf(sx[6], sx[7]), fmaxf(sx[8], sx[9])));
        };
        if (!Z0 || s > 0) xsum();
        else {
#pragma unroll
          for (int i = 2; i < 10; i++) sx[i] = 0.f;
          mx = 0.f;
        }
        sts32(ls - l12 + SM_XS + 512, f2u(mx));
        {
          if (l16 == 0) mbar_expect_tx(sb + SM_BAR + MB_VR, 2048);
          unsigned char* d = P.win + (w_blk(w_mvx(cta, s), me2) + l16);
          OPAQUE_L(d); FENCE();
          mbar_wait(sb + SM_BAR + MB_VR, s & 1);
#pragma unroll
          for (int t = 0; t < 4; t++) {
            const uint4 a0 = lds128(ls + (SM_VL + t * 512)), a1 = lds128(ls + (SM_VR + t * 512));
            stg_r4(d + t * 512, tagw(addb2(a0.x, a1.x), t2), addb2(a0.y, a1.y), addb2(a0.z, a1.z), addb2(a0.w, a1.w));
          }
          TS(23);
        }
        unsigned char* pm = P.win + (db + 2048 + j * 128 - l12);
        const unsigned char* py = pa + 1536 - l12;
        OPAQUE_L(pm); OPAQUE_L(py);
        if (s > 0) bar_sync(B_PXF, 96);
        FENCE();
        bar_sync(B_QK1, 288);
        uint32_t kb[2][2];
#pragma unroll
        for (int t = 0; t < 2; t++) {
          const float4 u = lds128f(lq + (SM_QKP + (2 + t) * 512)), v4 = lds128f(lq + (SM_QKP + 2048 + (2 + t) * 512));
          kb[t][0] = pack_bf16(u.x + v4.x, u.y + v4.y); kb[t][1] = pack_bf16(u.z + v4.z, u.w + v4.w);
        }
        float S[2][4];
#pragma unroll
        for (int mt = 0; mt < 2; mt++) mma4z(S[mt], qx[mt].x, qx[mt].y, qx[mt].z, qx[mt].w, kb[0][0], kb[0][1]);
#pragma unroll
        for (int mt = 0; mt < 2; mt++) mma4(S[mt], qx[2 + mt].x, qx[2 + mt].y, qx[2 + mt].z, qx[2 + mt].w, kb[1][0], kb[1][1]);
        PT(14, s == 0 && l16 == 0);
        if (!Z1 && s == 0) mbar_wait(sb + SM_BAR + MB_WO, 0);
        PT(15, s == 0 && l16 == 0);
        if (s < NSEG - 1) bar_arrive(B_PUB, 320);
        FENCE();
#pragma unroll
        for (int u = 0; u < 4; u++) stg_r1(pm + (u >> 1) * 16384 + (u & 1) * 2048, tagw(pack_f16(S[u >> 1][2 * (u & 1)], S[u >> 1][2 * (u & 1) + 1]), t2));
        TS(30);
        FENCE();
        if (Z0 && s == 0) xsum();
        spin(DLY_XL);
        uint32_t xy[4];
#pragma unroll
        for (int i = 0; i < 4; i++) xy[i] = ldg_r1(py + i * 128);
        FENCE();

        n = 0;
#pragma unroll 1
        while (__any_sync(~0u, (x3(xy[0], xy[1], t2) | x3(xy[2], xy[3], t2)) & 1u) && ++n < SPIN_LIMIT) {
#pragma unroll
          for (int i = 0; i < 4; i++) xy[i] = ldg_r1(py + i * 128);
        }
        sum_h4(sx[0], sx[1], xy[0], xy[1], xy[2], xy[3]);
        mx = fmaxf(mx, fmaxf(sx[0], sx[1]));
        mx = fmaxf(fmaxf(mx, __shfl_xor_sync(~0u, mx, 1)), fmaxf(__shfl_xor_sync(~0u, mx, 2), __shfl_xor_sync(~0u, mx, 3)));
#pragma unroll
        for (int i = 0; i < 10; i++) sx[i] = ex2(fmaf(sx[i], sc, -sc * mx));
        sts128(ls + SM_PX, pack_bf16(sx[2], sx[3]), pack_bf16(sx[4], sx[5]), pack_bf16(sx[6], sx[7]), pack_bf16(sx[8], sx[9]));
        sts32(ls - l12 + SM_PX + 512, pack_bf16(sx[0], sx[1]));
        bar_arrive(B_PX, 96);
        TS(1);
        }
      }
    } else {
      const uint32_t ho = (wq & 1) * 512 + l16, hv = wq == 0 ? 0u : H1_V;
      uint32_t ow = w_blk(w_h1(cta) ^ hv, me) + ho, or0 = w_blk(w_h1(cta ^ 1) ^ hv, me) + ho, or1 = w_blk(w_h1((cta ^ 2) & ~1) ^ hv, me) + ho;
#define PTRS() OPAQUE_R(ow); OPAQUE_R(or0); OPAQUE_R(or1); \
      unsigned char* pw0 = P.win + ow; const unsigned char* pr0 = P.win + or0; const unsigned char* pr1 = P.win + or1; \
      OPAQUE_L(pw0); OPAQUE_L(pr0); OPAQUE_L(pr1); FENCE()
      if (wq == 0) {
        const uint32_t xcnt = me ? NCTA - nlo : nlo, xrank = (me ? cta - nlo : cta) + lane * xcnt;
        int kd = DLY_K;
        mbar_wait(sb + SM_BAR + MB_XE1, 0);
        if (l16 == 0) { mbar_expect_tx(sb + SM_BAR + MB_F + 8, 32768); XLOAD(1, 1); }
        __syncwarp();
        for (int s = 0; s < NSEG - 1; s++) {
          const uint32_t tg = (s & 1) ^ 1;
          mbar_wait(sb + SM_BAR + MB_XF, s & 1);
          uint4 xf[4];
#pragma unroll
          for (int i = 0; i < 4; i++) xf[i] = ldsm4(ls + (SM_XF + (4 + i) * 512));
          PTRS();
          unsigned char* pw1 = pw0 + 512 - l12; OPAQUE_L(pw1);
          bar_sync(B_QK, 288);
          float4 u[4], v4[4];
#pragma unroll
          for (int t = 0; t < 4; t++) { u[t] = lds128f(lq + (SM_QKP + t * 512)); v4[t] = lds128f(lq + (SM_QKP + 2048 + t * 512)); }
          FENCE();
          uint32_t f[4][2], m[5];
#pragma unroll
          for (int t = 0; t < 2; t++) { f[t][0] = pack_bf16(u[t].x + v4[t].x, u[t].y + v4[t].y); f[t][1] = pack_bf16(u[t].z + v4[t].z, u[t].w + v4[t].w); }
          float S[5][4], T[5][4];
          mma4z(S[1], f[0][0], f[1][0], f[0][1], f[1][1], xf[0].x, xf[0].y); mma4z(T[1], f[0][0], f[1][0], f[0][1], f[1][1], xf[2].x, xf[2].y);
          mma4z(S[2], f[0][0], f[1][0], f[0][1], f[1][1], xf[0].z, xf[0].w); mma4z(T[2], f[0][0], f[1][0], f[0][1], f[1][1], xf[2].z, xf[2].w);
          FENCE();
#pragma unroll
          for (int t = 2; t < 4; t++) { f[t][0] = packv(u[t].x, v4[t].x, u[t].y, v4[t].y); f[t][1] = packv(u[t].z, v4[t].z, u[t].w, v4[t].w); }
          mma4z(S[3], f[0][0], f[1][0], f[0][1], f[1][1], xf[1].x, xf[1].y); mma4z(T[3], f[0][0], f[1][0], f[0][1], f[1][1], xf[3].x, xf[3].y);
          mma4z(S[4], f[0][0], f[1][0], f[0][1], f[1][1], xf[1].z, xf[1].w); mma4z(T[4], f[0][0], f[1][0], f[0][1], f[1][1], xf[3].z, xf[3].w);
          FENCE();
          mma4z(S[0], f[0][0], f[1][0], f[0][1], f[1][1], f[2][0], f[2][1]); mma4z(T[0], f[0][0], f[1][0], f[0][1], f[1][1], f[3][0], f[3][1]);
          bar_arrive(B_PUB, 320);
          FENCE();
#if SO
#pragma unroll
          for (int i = 1; i < 5; i++) m[i] = packh(S[i][0], T[i][2], S[i][1], T[i][3]);
          m[1] = tagw(m[1], tg);
          stg_r4(pw0, m[1], m[2], m[3], m[4]);
          FENCE();
          m[0] = tagw(packh(S[0][0], T[0][2], S[0][1], T[0][3]), tg);
          stg_r1(pw1, m[0]);
#else
#pragma unroll
          for (int i = 1; i < 5; i++) m[i] = pack_f16(S[i][0] + T[i][2], S[i][1] + T[i][3]);
          stg_r4(pw0, tagw(m[1], tg), m[2], m[3], m[4]);
          m[0] = pack_f16(S[0][0] + T[0][2], S[0][1] + T[0][3]);
          stg_r1(pw1, tagw(m[0], tg));
#endif
          TS(6); PT(11, s == 0 && l16 == 0);
          FENCE();
          const uint32_t ts = clk32();
          uint32_t te = gt32() + kd;
          const unsigned char* py0 = pr0 + 512 - l12; const unsigned char* py1 = pr1 + 512 - l12;
          OPAQUE_L(py0); OPAQUE_L(py1);
          unsigned char* pt = P.win + (w_ar(s) + (W_DS + 256) + (cta >> 5) * 8192 + ((cta >> 4) & 1) * 2048 + (l16 & 16u) * 256);
          OPAQUE_L(pt);
          if (l16 == 0) mbar_expect_tx(sb + SM_BAR + MB_F, s < NSEG - 2 ? 32768 : 0);
          FENCE();
          while (clk32() - ts < (uint32_t)DLY_S) {}
          {
            float sx[10]; uint32_t x, x1, x2, x3_; int n = 0; bool bad;
#pragma unroll 1
            do {
              uint4 v[3]; uint32_t y[3], t[5];
              v[0] = ldg_r4(pr0); v[1] = ldg_r4(pr1); v[2] = ldg_r4(pr1 + 2048);
              y[0] = ldg_r1(py0); y[1] = ldg_r1(py1); y[2] = ldg_r1(py1 + 2048);
              if (n) te = gt32() + DLY_KS;
              eta2(pt, te, n == 0, l16);
              n++;
              FENCE();
#define Q3(o, a, b, c) hadd2(hadd2(o, a), hadd2(b, c))
              t[1] = Q3(m[1], v[0].x, v[1].x, v[2].x); t[2] = Q3(m[2], v[0].y, v[1].y, v[2].y); t[3] = Q3(m[3], v[0].z, v[1].z, v[2].z); t[4] = Q3(m[4], v[0].w, v[1].w, v[2].w);
              t[0] = Q3(m[0], y[0], y[1], y[2]);
              bad = __any_sync(~0u, or3(x3(v[0].x, v[1].x, tg), x3(v[2].x, y[0], tg), x3(y[1], y[2], tg)) & (n < SPIN_LIMIT ? 1u : 0u));
              x = hmax2(hmax2(hmax2(t[1], t[2]), hmax2(t[3], t[4])), t[0]);
              const float2 xm = __half22float2(*reinterpret_cast<__half2*>(&x));
              x = f2u(fmaxf(xm.x, xm.y) * -sc);
              x1 = shfl_x(x, 1); x2 = shfl_x(x, 2); x3_ = shfl_x(x, 3);
              FENCE();
#if OS
#pragma unroll
              for (int i = 1; i < 6; i++) {
                h2f(sx[2 * (i % 5)], sx[2 * (i % 5) + 1], t[i % 5]);
                sx[2 * (i % 5)] = ex2v(sx[2 * (i % 5)], sc, u2f(x)); sx[2 * (i % 5) + 1] = ex2v(sx[2 * (i % 5) + 1], sc, u2f(x));
              }
              FENCE();
            } while (bad);
            const float cr = ex2(fminf(fminf(u2f(x), u2f(x1)), fminf(u2f(x2), u2f(x3_))) - u2f(x));
#pragma unroll
            for (int i = 1; i < 6; i++) m[i % 5] = pack_bf16(sx[2 * (i % 5)] * cr, sx[2 * (i % 5) + 1] * cr);
#else
#pragma unroll
              for (int i = 1; i < 6; i++) h2f(sx[2 * (i % 5)], sx[2 * (i % 5) + 1], t[i % 5]);
              FENCE();
            } while (bad);
            const float mx = fminf(fminf(u2f(x), u2f(x1)), fminf(u2f(x2), u2f(x3_)));
#pragma unroll
            for (int i = 2; i < 12; i++) sx[i % 10] = ex2v(sx[i % 10], sc, mx);
#pragma unroll
            for (int i = 1; i < 6; i++) m[i % 5] = pack_bf16(sx[2 * (i % 5)], sx[2 * (i % 5) + 1]);
#endif
            sts128(ls + SM_PF, m[1], m[2], m[3], m[4]);
            sts32(ls - l12 + SM_PF + 512, m[0]);
            TV(19, n - 1);
          }
          TS(12);
          bar_sync(B_P, 96);
          PT(12, s == 0 && l16 == 0);
          OPAQUE_R(l16);
          {
            const unsigned char* pe = P.win + w_blk(w_ar(s) + (W_DS + 256) + (l16 & 0x60u) * 256 + (l16 & 16u) * 128, me);
            const uint32_t tp = gt32() + DLY_M3;
            if (s < NSEG - 2) F0LOAD();
            ETAT(tp, 0);
            uint32_t tg0; int n = 0;
#pragma unroll 1
            for (;;) {
              const uint2 e = ldg_r2(pe);
              tg0 = __reduce_max_sync(~0u, e.y);
              if (tg0 - tp >= 4096u) tg0 = tp;
              if ((!__any_sync(~0u, e.x != 16u) && (int)(tg0 - gt32()) < DLY_RR) || ++n >= SPIN_LIMIT) break;
            }
            sts32(sb + SM_Z + 32, tg0);
            TV(16, tg0); TV(7, kd - DLY_K);
            bar_arrive(B_GO, 96);
          }
          if (s < NSEG - 2) {
            mbar_wait(sb + SM_BAR + MB_XE1, (s + 1) & 1);
            if (l16 == 0) mbar_expect_tx(sb + SM_BAR + MB_F + 8, 32768);
            mbar_wait(sb + SM_BAR + MB_MEM, (s + 1) & 1); mbar_wait(sb + SM_BAR + MB_MEM + 8, (s + 1) & 1);
            if (l16 == 0) XLOAD(1, s + 2);
            __syncwarp();
          }
          if (XPF && s + XPF < NSEG) {
            for (uint32_t i = xrank; i < 512; i += 32 * xcnt)
              asm volatile("prefetch.global.L2 [%0];" :: "l"(SP.x + (size_t)(s + XPF) * (SEG * DM) + i * 64));
            __syncwarp();
          }
          stg_2(P.win + (w_ar(s + 2) + cta * 256 + (l16 >> 8) * W_DS + ((l16 >> 1) & 127u)), 0u, 0u);
          kd = lds32(sb + SM_Z + 40) == (uint32_t)(s + 1) ? min(kd + KU, DLY_K + 256) : max(kd - KD, DLY_K);
          kd = __shfl_sync(~0u, kd, l16 >> 4);
#ifdef PER
          if (l16 == 0) { g_per[cta][s] = gt32(); g_pclk[cta][s] = clk32(); g_pk[cta][s] = kd - DLY_K; }
#endif
        }
        bar_sync(B_QK, 288);
      } else {
        const int mt = wq - 2;
        const uint32_t lt = ls + mt * 1024;
        const uint32_t vi0 = w_blk(w_mvx(h * 4, 0), me2) + mt * 1024;
        const int m3d = r ? -8192 : 8192;
#ifdef PROF
        const uint32_t epoch = gt32(); TST(-1, 30 + mt, l16, epoch);
#endif
        float ox[4][4], zx[4];
#pragma unroll
        for (int i = 0; i < 16; i++) ox[i >> 2][i & 3] = zx[i & 3] = 1.f;
        for (int s = 0;; s++) {
          const uint32_t tg = (s & 1) ^ 1, t2 = ((s >> 1) & 1) ^ 1;
          {
            OPAQUE_R(l16);
            const uint32_t m3i = (mt * 2 + r) * 8192 + (l16 & 0x70u) + ((l16 & 0x180u) << 1);
            const uint32_t m3j = (mt * 2 + (r ^ (l16 >> 7 & 1))) * 8192 + ((l16 & 64u) * 4 + (l16 & 48u) * 2 + (l16 & 16u)) * 16 + W_DS + (l16 & 0x70u);
            uint32_t m3c = sb + SM_MEM + mt * 8192 + cnt_line(l16 >> 4) * 128 + (l16 >> 2);
            const unsigned char* p3 = P.win + (m3i + w_ar(s - 1)); const unsigned char* pd = P.win + (m3j + w_ar(s - 1));
            OPAQUE_L(pd); OPAQUE_R(m3c);
#define XEPI() do {        \
              PVE(ox, zx, SM_OX + mt * 512); \
              __syncwarp(); \
              const uint32_t oa = sb + SM_OX + mt * 512 + ((l16 & 48u) << 3) + ((l16 >> 2) & 0x70u); \
              const uint4 a = lds128(oa), b = lds128(oa + 1024); \
              unsigned char* o = reinterpret_cast<unsigned char*>(g_ox + (size_t)((s - 1) * SEG + 8 * j) * (NH * DH) + h * DH + mt * 32) + ((l16 >> 6) * (NH * DH * 2) + (l16 & 48u)); \
              stg_4(o, a); stg_4(o + 128, b); \
              TST(s - 1, 18, l16 | mt, TCLK()); } while (0)
            if (s > 0) XEPI();
            if (s == NSEG) break;
            if (s > 0) {
              M3PTR(s - 1);
              bar_sync(B_GO, 96);
              const uint32_t tg0 = lds32(sb + SM_Z + 32);
              while (tg0 - gt32() - 1u < 8192u) {}
              M3REQ();
            }
            FENCE();
            const int n = m3_check(sb, p3, pd, m3d, l16, m3c, mt, s);
            FENCE();
            TST(s, mt ? 21 : 0, l16, TCLK());
            TST(s, mt ? 22 : 17, l16, n);
            PT(6 + s, s < 5 && (l16 | mt) == 0);
          }
          uint4 va[8], vm[2], p0, q0; uint32_t p2, q2;
          const unsigned char* a0 = P.win + (vi0 + ((s & 1) << 20) + l16);
#define VALD() _Pragma("unroll") for (int i = 0; i < 4; i++) { va[i] = ldg_r4(a0 + (i >> 1) * 512 + (i & 1) * 2048); va[4 + i] = ldg_r4(a0 + 16384 + (i >> 1) * 512 + (i & 1) * 2048); }
          spin(DLY_WO);
          VALD();
          {
          PTRS();
          bar_sync(B_V, 320);
            const float4 u0 = lds128f(lt + SM_VP), w0 = lds128f(lt + SM_VP + 2048), u1 = lds128f(lt + SM_VP + 512), w1 = lds128f(lt + SM_VP + 2560);
            const uint32_t m0 = tagw(pack_bf16(u0.x + w0.x, u0.y + w0.y), tg), m1 = pack_bf16(u0.z + w0.z, u0.w + w0.w),
                           m2 = pack_bf16(u1.x + w1.x, u1.y + w1.y), m3 = pack_bf16(u1.z + w1.z, u1.w + w1.w);
            stg_r4(pw0, m0, m1, m2, m3);
            if (wq == 2) TS(10);
            FENCE();
            const uint32_t tv = clk32();
            while (clk32() - tv < (uint32_t)DLY_V) {}
            uint4 v[3]; int n = 0; uint32_t bada = 0;
#pragma unroll 1
            do {
              v[0] = ldg_r4(pr0); v[1] = ldg_r4(pr1); v[2] = ldg_r4(pr1 + 2048);
              if (n) {
                TST(s, __any_sync(~0u, bada & 1u) ? 26 : 24, l16, epoch);
                if (__any_sync(~0u, bada & 1u)) { VALD(); }
                if (s < NSEG - 1) ETA(DLY_KS - 192, 0);
              }
              n++;
              FENCE();
              bada = or3(x3(va[0].x, va[1].x, t2), x3(va[2].x, va[3].x, t2), x3(va[4].x, va[5].x, t2)) | x3(va[6].x, va[7].x, t2);
            } while (__any_sync(~0u, or3(bada, x3(v[0].x, v[1].x, tg), v[2].x ^ tg) & 1u) && n < SPIN_LIMIT);
            const uint4 A = make_uint4(addb2(m0, v[0].x), addb2(m1, v[0].y), addb2(m2, v[0].z), addb2(m3, v[0].w));
            const uint4 B = make_uint4(addb2(v[1].x, v[2].x), addb2(v[1].y, v[2].y), addb2(v[1].z, v[2].z), addb2(v[1].w, v[2].w));
            vm[0] = p ? B : A; vm[1] = p ? A : B;
            TST(s, 11, l16 | mt, TCLK()); TST(s, 29, l16 | (mt ^ 1), TCLK());
          }
          FENCE();
          if (s < NSEG - 1) {
          bar_sync(B_P, 96);
          p0 = lds128(ls + SM_PF); p2 = lds32(ls - l12 + SM_PF + 512);
          float o[4][4], z[4];
          PVM(o, z, p0, p2, , , );
          PVE(o, z, SM_OF + mt * 512);
          bar_arrive(B_O, 192);
          }
          FENCE();
          TST(s, 8, l16 | mt, TCLK());
          bar_sync(B_PX, 96);
          q0 = lds128(ls + SM_PX); q2 = lds32(ls - l12 + SM_PX + 512);
#define O2A(k) if (O2P == k) { if (s < NSEG - 1) bar_arrive(B_O2, XG ? 224 : 192); FENCE(); }
          O2A(0);
          PVM(ox, zx, q0, q2, O2A(1), O2A(2), O2A(3));
          O2A(4);
          FENCE();
          if (s < NSEG - 1) bar_arrive(B_PXF, 96);
        }
      }
    }
  }
  asm volatile("barrier.cluster.arrive.relaxed.aligned;\nbarrier.cluster.wait.aligned;" ::: "memory");
#ifdef PER
  if (threadIdx.x == 0) atomicMax(&g_end[0], gt32());
#endif
}
#ifndef PW
#define PW 2
#endif
#ifndef G2_PD
#define G2_PD 300
#endif
#ifndef G2_HD
#define G2_HD 8000
#endif
#ifndef G2_B
#define G2_B 4
#endif
#ifndef G2_ST
#define G2_ST 6
#endif
#define G2_TB (G2_ST * 32768 + 1024)
#define G2_SMEM (G2_TB + 32768)
template <int AOFF, int BOFF>
static __device__ __forceinline__ void wgmma_n128_ta(float (&d)[64], uint32_t a16, uint32_t b16) {
  asm volatile(
      "{\n.reg .b32 t, u;\n.reg .b64 da, db;\nadd.u32 t, %64, %66;\nmov.b64 da, {t, %68};\nadd.u32 u, %65, %67;\nmov.b64 db, {u, %68};\n"
      "wgmma.mma_async.sync.aligned.m64n128k16.f32.bf16.bf16 "
      "{%0,%1,%2,%3,%4,%5,%6,%7,%8,%9,%10,%11,%12,%13,%14,%15,%16,%17,%18,%19,%20,%21,%22,%23,%24,%25,%26,%27,%28,%29,%30,%31,"
      "%32,%33,%34,%35,%36,%37,%38,%39,%40,%41,%42,%43,%44,%45,%46,%47,%48,%49,%50,%51,%52,%53,%54,%55,%56,%57,%58,%59,%60,%61,%62,%63}, "
      "da, db, 1, 1, 1, 1, 0;\n}"
      : "+f"(d[0]), "+f"(d[1]), "+f"(d[2]), "+f"(d[3]), "+f"(d[4]), "+f"(d[5]), "+f"(d[6]), "+f"(d[7]), "+f"(d[8]), "+f"(d[9]), "+f"(d[10]), "+f"(d[11]),
        "+f"(d[12]), "+f"(d[13]), "+f"(d[14]), "+f"(d[15]), "+f"(d[16]), "+f"(d[17]), "+f"(d[18]), "+f"(d[19]), "+f"(d[20]), "+f"(d[21]), "+f"(d[22]), "+f"(d[23]),
        "+f"(d[24]), "+f"(d[25]), "+f"(d[26]), "+f"(d[27]), "+f"(d[28]), "+f"(d[29]), "+f"(d[30]), "+f"(d[31]), "+f"(d[32]), "+f"(d[33]), "+f"(d[34]), "+f"(d[35]),
        "+f"(d[36]), "+f"(d[37]), "+f"(d[38]), "+f"(d[39]), "+f"(d[40]), "+f"(d[41]), "+f"(d[42]), "+f"(d[43]), "+f"(d[44]), "+f"(d[45]), "+f"(d[46]), "+f"(d[47]),
        "+f"(d[48]), "+f"(d[49]), "+f"(d[50]), "+f"(d[51]), "+f"(d[52]), "+f"(d[53]), "+f"(d[54]), "+f"(d[55]), "+f"(d[56]), "+f"(d[57]), "+f"(d[58]), "+f"(d[59]),
        "+f"(d[60]), "+f"(d[61]), "+f"(d[62]), "+f"(d[63])
      : "r"(a16), "r"(b16), "n"(AOFF >> 4), "n"(BOFF >> 4), "n"(DESC_HI(1024)));
}
__global__ void __cluster_dims__(2, 1, 1) __launch_bounds__(384, 1)
gemm2_kernel(const __grid_constant__ CUtensorMap tmo, const __grid_constant__ CUtensorMap tmw, const bf16* __restrict__ x, bf16* __restrict__ out, unsigned char* win) {
  extern __shared__ __align__(1024) unsigned char smem[];
  const uint32_t sb = smem_u32(smem), bars = sb + G2_ST * 32768;
  const int tid = threadIdx.x, lane = tid & 31, warp = __shfl_sync(~0u, tid >> 5, 0);
  const int r = blockIdx.x & 1, pp = blockIdx.x >> 1;
  const int n0 = (((pp >> G2_B) & 3) * 2 + r) * 128, m0 = ((pp & ((1 << G2_B) - 1)) | ((pp >> (G2_B + 2)) << G2_B)) * 128;
  if (tid == 0) {
    for (int i = 0; i < G2_ST; i++) { mbar_init(bars + i * 8, 1); mbar_init(bars + 64 + i * 8, 4); }
    asm volatile("fence.mbarrier_init.release.cluster;" ::: "memory");
  }
  if (tid == 32) { asm volatile("prefetch.tensormap [%0];" :: "l"(&tmw) : "memory"); asm volatile("prefetch.tensormap [%0];" :: "l"(&tmo) : "memory"); }
  __syncthreads();
  asm volatile("barrier.cluster.arrive.relaxed.aligned;" ::: "memory");
#define LW(kt, st) asm volatile("cp.async.bulk.tensor.3d.shared::cluster.global.mbarrier::complete_tx::bytes [%0], [%1, {%3, %4, %5}], [%2];" \
                     :: "r"(sb + (st) * 32768), "l"(&tmw), "r"(bars + (st) * 8), "r"(0), "r"((kt) * 64), "r"(n0 >> 6) : "memory")
#define LO(kt, st) asm volatile("cp.async.bulk.tensor.2d.shared::cluster.global.mbarrier::complete_tx::bytes.multicast::cluster [%0], [%1, {%3, %4}], [%2], %5;" \
                     :: "r"(sb + (st) * 32768 + 16384 + r * 8192), "l"(&tmo), "r"(bars + (st) * 8), "r"((kt) * 64), "r"(m0 + r * 64), "h"((uint16_t)3) : "memory")
  if (tid == 256) for (int kt = 0; kt < G2_ST; kt++) { mbar_expect_tx(bars + kt * 8, 32768); if (kt < PW) LW(kt, kt); }
  __syncwarp();
  asm volatile("barrier.cluster.wait.acquire.aligned;" ::: "memory");
  if (warp == 8) {
    if (lane == 0) {
      asm volatile("griddepcontrol.wait;" ::: "memory");
      for (int kt = 0; kt < G2_ST; kt++) { LO(kt, kt); if (kt >= PW) LW(kt, kt); spin(G2_PD); }
#pragma unroll 1
      for (int kt = G2_ST, st = 0, ph = 0; kt < 64; kt++) {
        mbar_wait(bars + 64 + st * 8, ph);
        mbar_expect_tx(bars + st * 8, 32768);
        LO(kt, st); LW(kt, st);
        if (++st == G2_ST) { st = 0; ph ^= 1; }
      }
    }
  } else if (warp > 8) {
    const int t = tid - 288, ch = t & 15;
    asm volatile("griddepcontrol.wait;" ::: "memory");
#ifdef PER
    if (t == 0) atomicMax(&g_end[3], gt32());
#endif
    spin(G2_HD);
    int idx[8];
#pragma unroll
    for (int c = 0; c < 8; c++) idx[c] = g_idx[c];
    const int gi = blockIdx.x * 96 + t;
    if (gi < 67) g_side[gi * 32] = 0u;
    if (gi == 0) g_sbar = 0u;
#pragma unroll 4
    for (int row = t >> 4; row < 128; row += 6) {
      const int tok = m0 + row;
      const uint4 xv = *reinterpret_cast<const uint4*>(x + (size_t)tok * DM + n0 + ch * 8);
      const float g = g_gate[tok], omg = rbf(1.f - g);
      int sel = -1;
#pragma unroll
      for (int c = 0; c < 8; c++) if (idx[c] == tok) sel = c;
      uint4 uv = make_uint4(0u, 0u, 0u, 0u);
      if (sel >= 0) uv = *reinterpret_cast<const uint4*>(g_upd + sel * DM + n0 + ch * 8);
      const uint32_t x4[4] = {xv.x, xv.y, xv.z, xv.w}, u4[4] = {uv.x, uv.y, uv.z, uv.w};
      uint32_t o4[4];
#pragma unroll
      for (int e = 0; e < 4; e++) {
        const float b0 = rbf(u2f(x4[e] << 16) + u2f(u4[e] << 16)), b1 = rbf(u2f(x4[e] & 0xffff0000u) + u2f(u4[e] & 0xffff0000u));
        o4[e] = pack_bf16(omg * b0, omg * b1);
      }
      sts128(sb + G2_TB + row * 256 + ch * 16, o4[0], o4[1], o4[2], o4[3]);
      if (ch == 0) sts32(bars + 512 + row * 4, pack_bf16(g, g));
    }
    bar_arrive(2, 352);
  } else {
    const int wg = warp >> 2;
    float d[64];
#pragma unroll
    for (int i = 0; i < 64; i++) d[i] = 0.f;
    const uint32_t e0 = mapa(bars + 64, 0), e1 = mapa(bars + 64, 1);
#ifdef PER
    if (threadIdx.x == 0) { mbar_wait(bars, 0); atomicMax(&g_end[4], gt32()); }
    __syncwarp();
#endif
    const uint32_t a16 = (((sb + wg * 8192) & 0x3FFFF) >> 4) | (64u << 16), b16 = (((sb + 16384) & 0x3FFFF) >> 4) | (1u << 16);
#pragma unroll 1
    for (int kt = 0, st = 0, ph = 0, ps = -1; kt < 64; kt++) {
      mbar_wait(bars + st * 8, ph);
      wg_fence();
      wgmma_n128_ta<0, 0>(d, a16 + st * 2048, b16 + st * 2048); wgmma_n128_ta<2048, 32>(d, a16 + st * 2048, b16 + st * 2048);
      wgmma_n128_ta<4096, 64>(d, a16 + st * 2048, b16 + st * 2048); wgmma_n128_ta<6144, 96>(d, a16 + st * 2048, b16 + st * 2048);
      wg_commit();
      asm volatile("wgmma.wait_group.sync.aligned 1;" ::: "memory");
      if (ps >= 0 && (tid & 127) == 0) {
        mbar_arrive_cluster_rlx(e0 + ps * 8); mbar_arrive_cluster_rlx(e1 + ps * 8);
      }
      ps = st;
      if (++st == G2_ST) { st = 0; ph ^= 1; }
    }
    wg_wait0();
#ifdef PER
    if (threadIdx.x == 0) atomicMax(&g_end[5], gt32());
#endif
    bar_sync(1, 256);
#pragma unroll
    for (int jj = 0; jj < 8; jj++) {
      const uint32_t q0 = pack_bf16(d[8 * jj], d[8 * jj + 1]), q1 = pack_bf16(d[8 * jj + 2], d[8 * jj + 3]);
      const uint32_t q2 = pack_bf16(d[8 * jj + 4], d[8 * jj + 5]), q3 = pack_bf16(d[8 * jj + 6], d[8 * jj + 7]);
      stsm4t(sb + (jj * 16 + (lane >> 4) * 8 + (lane & 7)) * 272 + (warp * 16 + ((lane >> 3) & 1) * 8) * 2, q0, q1, q2, q3);
    }
    bar_sync(2, 352);
#pragma unroll
    for (int it = 0; it < 8; it++) {
      const int row = it * 16 + (tid >> 4), ch = tid & 15, tok = m0 + row;
      const uint4 av = lds128(sb + row * 272 + ch * 16), tv = lds128(sb + G2_TB + row * 256 + ch * 16);
      const uint32_t g = lds32(bars + 512 + row * 4);
      *reinterpret_cast<uint4*>(out + (size_t)tok * DM + n0 + ch * 8) =
          make_uint4(addb2(mulb2(g, av.x), tv.x), addb2(mulb2(g, av.y), tv.y), addb2(mulb2(g, av.z), tv.z), addb2(mulb2(g, av.w), tv.w));
    }
  }
  asm volatile("barrier.cluster.arrive.relaxed.aligned;\nbarrier.cluster.wait.aligned;" ::: "memory");
#ifdef PER
  if (threadIdx.x == 0) atomicMax(&g_end[2], gt32());
#endif
}
#ifndef WPROM
#define WPROM CU_TENSOR_MAP_L2_PROMOTION_L2_128B
#endif
#ifndef PDL
#define PDL 1
#endif
typedef CUresult (*PFN_encodeTiled)(CUtensorMap*, CUtensorMapDataType, cuuint32_t, void*, const cuuint64_t*, const cuuint64_t*,
                                    const cuuint32_t*, const cuuint32_t*, CUtensorMapInterleave, CUtensorMapSwizzle,
                                    CUtensorMapL2promotion, CUtensorMapFloatOOBfill);

extern "C" void kernel_launch(void* const* d_in, const int* in_sizes, int n_in, void* d_out, int out_size) {
  const bf16* x = (const bf16*)d_in[0];
  const bf16* mem0 = (const bf16*)d_in[1];
  const bf16* Wq = (const bf16*)d_in[2];
  const bf16* Wk = (const bf16*)d_in[3];
  const bf16* Wv = (const bf16*)d_in[4];
  const bf16* Wo = (const bf16*)d_in[5];
  const bf16* w_r = (const bf16*)d_in[8];
  const bf16* w_gate = (const bf16*)d_in[9];
  const bf16* w_up = (const bf16*)d_in[10];
  const bf16* w_down = (const bf16*)d_in[11];
  const bf16* gate_w = (const bf16*)d_in[12];
  bf16* out = (bf16*)d_out;

  static PFN_encodeTiled encode = nullptr;
  if (!encode) {
    void* fn = nullptr; cudaDriverEntryPointQueryResult st;
    cudaGetDriverEntryPoint("cuTensorMapEncodeTiled", &fn, cudaEnableDefault, &st);
    encode = (PFN_encodeTiled)fn;
    cudaFuncSetAttribute(rec_kernel, cudaFuncAttributeMaxDynamicSharedMemorySize, SM_TOTAL);
    cudaFuncSetAttribute(gemm2_kernel, cudaFuncAttributeMaxDynamicSharedMemorySize, G2_SMEM);
  }
  CUtensorMap tmx;
  {
    cuuint64_t gd[3] = {64, S_TOK, DM / 64};
    cuuint64_t gs[2] = {DM * 2, 128};
    cuuint32_t bx[3] = {64, SEG, 4};
    cuuint32_t es[3] = {1, 1, 1};
    encode(&tmx, CU_TENSOR_MAP_DATA_TYPE_BFLOAT16, 3, (void*)x, gd, gs, bx, es, CU_TENSOR_MAP_INTERLEAVE_NONE,
           CU_TENSOR_MAP_SWIZZLE_128B, CU_TENSOR_MAP_L2_PROMOTION_L2_128B, CU_TENSOR_MAP_FLOAT_OOB_FILL_NONE);
  }
  bf16* ox;
  cudaGetSymbolAddress((void**)&ox, g_ox);
  CUtensorMap tmo, tmw, tmw3;
  {
    cuuint64_t gd[2] = {NH * DH, S_TOK}; cuuint64_t gs[1] = {NH * DH * 2}; cuuint32_t bx[2] = {64, 64}; cuuint32_t es[3] = {1, 1, 1};
    encode(&tmo, CU_TENSOR_MAP_DATA_TYPE_BFLOAT16, 2, (void*)ox, gd, gs, bx, es, CU_TENSOR_MAP_INTERLEAVE_NONE,
           CU_TENSOR_MAP_SWIZZLE_128B, CU_TENSOR_MAP_L2_PROMOTION_L2_128B, CU_TENSOR_MAP_FLOAT_OOB_FILL_NONE);
    cuuint64_t gd2[2] = {DM, NH * DH}; cuuint64_t gs2[1] = {DM * 2}; cuuint32_t bx2[2] = {64, 64};
    encode(&tmw, CU_TENSOR_MAP_DATA_TYPE_BFLOAT16, 2, (void*)Wo, gd2, gs2, bx2, es, CU_TENSOR_MAP_INTERLEAVE_NONE,
           CU_TENSOR_MAP_SWIZZLE_128B, CU_TENSOR_MAP_L2_PROMOTION_L2_128B, CU_TENSOR_MAP_FLOAT_OOB_FILL_NONE);
  }
  {
    cuuint64_t gd[3] = {64, NH * DH, DM / 64}; cuuint64_t gs[2] = {DM * 2, 128}; cuuint32_t bx[3] = {64, 64, 2}; cuuint32_t es[3] = {1, 1, 1};
    encode(&tmw3, CU_TENSOR_MAP_DATA_TYPE_BFLOAT16, 3, (void*)Wo, gd, gs, bx, es, CU_TENSOR_MAP_INTERLEAVE_NONE,
           CU_TENSOR_MAP_SWIZZLE_128B, CU_TENSOR_MAP_L2_PROMOTION_L2_128B, CU_TENSOR_MAP_FLOAT_OOB_FILL_NONE);
  }
  unsigned char* win;
  cudaGetSymbolAddress((void**)&win, g_win);
  win = (unsigned char*)(((uintptr_t)win + (2u << 20) - 1) & ~(uintptr_t)((2u << 20) - 1));
  WMaps W;
  {
    cuuint64_t gd[2] = {NH * DH, DM}; cuuint64_t gs[1] = {NH * DH * 2}; cuuint32_t b32[2] = {32, 128}, b64[2] = {64, 128}; cuuint32_t es[2] = {1, 1};
    encode(&W.q, CU_TENSOR_MAP_DATA_TYPE_BFLOAT16, 2, (void*)Wq, gd, gs, b32, es, CU_TENSOR_MAP_INTERLEAVE_NONE,
           CU_TENSOR_MAP_SWIZZLE_64B, WPROM, CU_TENSOR_MAP_FLOAT_OOB_FILL_NONE);
    encode(&W.k, CU_TENSOR_MAP_DATA_TYPE_BFLOAT16, 2, (void*)Wk, gd, gs, b32, es, CU_TENSOR_MAP_INTERLEAVE_NONE,
           CU_TENSOR_MAP_SWIZZLE_64B, WPROM, CU_TENSOR_MAP_FLOAT_OOB_FILL_NONE);
    encode(&W.v, CU_TENSOR_MAP_DATA_TYPE_BFLOAT16, 2, (void*)Wv, gd, gs, b64, es, CU_TENSOR_MAP_INTERLEAVE_NONE,
           CU_TENSOR_MAP_SWIZZLE_128B, WPROM, CU_TENSOR_MAP_FLOAT_OOB_FILL_NONE);
  }
  RecParams P{mem0, win};
  SideParams SP{x, w_r, w_gate, w_up, w_down, gate_w, Wo};
  rec_kernel<<<NCTA + 4, 384, SM_TOTAL, cudaStreamPerThread>>>(tmx, tmw, W, P, SP);
  {
    cudaLaunchConfig_t cfg = {};
    cfg.gridDim = dim3(NCTA); cfg.blockDim = dim3(384); cfg.dynamicSmemBytes = G2_SMEM; cfg.stream = cudaStreamPerThread;
    cudaLaunchAttribute at[1];
    at[0].id = cudaLaunchAttributeProgrammaticStreamSerialization; at[0].val.programmaticStreamSerializationAllowed = 1;
    cfg.attrs = at; cfg.numAttrs = PDL;
    cudaLaunchKernelEx(&cfg, gemm2_kernel, tmo, tmw3, x, out, win);
  }
}
```

```cpp
#include <cuda_runtime.h>
#include <cuda_bf16.h>
#include <cuda_fp16.h>
#include <cuda.h>
#include <stdint.h>

typedef __nv_bfloat16 bf16;

#define S_TOK 2048
#define DM 1024
#define NH 32
#define DH 128
#define SEG 32
#define NSEG 64
#define FF 3584
#define NCTA 128

static __device__ bf16 g_ox[(size_t)S_TOK * NH * DH];
static __device__ float g_gate[S_TOK];
static __device__ float g_r[S_TOK];
static __device__ int g_idx[8];
static __device__ bf16 g_upd[8 * DM];

static __device__ __forceinline__ float rbf(float v) { return __bfloat162float(__float2bfloat16(v)); }
static __device__ __forceinline__ uint32_t smem_u32(const void* p) { return (uint32_t)__cvta_generic_to_shared(p); }
static __device__ __forceinline__ uint32_t pack_bf16(float lo, float hi) {
  __nv_bfloat162 v = __floats2bfloat162_rn(lo, hi);
  return *reinterpret_cast<uint32_t*>(&v);
}

static __device__ __forceinline__ void wg_fence() { asm volatile("wgmma.fence.sync.aligned;" ::: "memory"); }
static __device__ __forceinline__ void wg_commit() { asm volatile("wgmma.commit_group.sync.aligned;" ::: "memory"); }
static __device__ __forceinline__ void wg_wait0() { asm volatile("wgmma.wait_group.sync.aligned 0;" ::: "memory"); }
static __device__ __forceinline__ void fence_async_smem() { asm volatile("fence.proxy.async.shared::cta;" ::: "memory"); }

static __device__ __forceinline__ uint64_t make_desc(uint32_t addr, uint32_t lbo, uint32_t sbo) {
  uint64_t d = 0;
  d |= (uint64_t)((addr & 0x3FFFF) >> 4);
  d |= (uint64_t)((lbo >> 4) & 0x3FFF) << 16;
  d |= (uint64_t)((sbo >> 4) & 0x3FFF) << 32;
  d |= (uint64_t)1 << 62;
  return d;
}

#define DESC_HI(sbo) (((sbo) >> 4) | (1u << 30))
template <int OFF, int SCALE>
static __device__ __forceinline__ void wgmma_n32_ra(float (&d)[16], const uint32_t (&a)[4], uint32_t base16) {
  asm volatile(
      "{\n.reg .b32 t;\n.reg .b64 dd;\nadd.u32 t, %20, %21;\nmov.b64 dd, {t, %22};\n"
      "wgmma.mma_async.sync.aligned.m64n32k16.f32.bf16.bf16 "
      "{%0,%1,%2,%3,%4,%5,%6,%7,%8,%9,%10,%11,%12,%13,%14,%15}, {%16,%17,%18,%19}, dd, %23, 1, 1, 0;\n}"
      : "+f"(d[0]), "+f"(d[1]), "+f"(d[2]), "+f"(d[3]), "+f"(d[4]), "+f"(d[5]), "+f"(d[6]), "+f"(d[7]),
        "+f"(d[8]), "+f"(d[9]), "+f"(d[10]), "+f"(d[11]), "+f"(d[12]), "+f"(d[13]), "+f"(d[14]), "+f"(d[15])
      : "r"(a[0]), "r"(a[1]), "r"(a[2]), "r"(a[3]), "r"(base16), "n"(OFF >> 4), "n"(DESC_HI(1024)), "n"(SCALE));
}
template <int AOFF, int BOFF, int SCALE>
static __device__ __forceinline__ void wgmma_n32_ss_ta(float (&d)[16], uint32_t abase16, uint32_t bbase16) {
  asm volatile(
      "{\n.reg .b32 t, u;\n.reg .b64 da, db;\nadd.u32 t, %16, %18;\nmov.b64 da, {t, %20};\nadd.u32 u, %17, %19;\nmov.b64 db, {u, %20};\n"
      "wgmma.mma_async.sync.aligned.m64n32k16.f32.bf16.bf16 "
      "{%0,%1,%2,%3,%4,%5,%6,%7,%8,%9,%10,%11,%12,%13,%14,%15}, da, db, %21, 1, 1, 1, 0;\n}"
      : "+f"(d[0]), "+f"(d[1]), "+f"(d[2]), "+f"(d[3]), "+f"(d[4]), "+f"(d[5]), "+f"(d[6]), "+f"(d[7]),
        "+f"(d[8]), "+f"(d[9]), "+f"(d[10]), "+f"(d[11]), "+f"(d[12]), "+f"(d[13]), "+f"(d[14]), "+f"(d[15])
      : "r"(abase16), "r"(bbase16), "n"(AOFF >> 4), "n"(BOFF >> 4), "n"(DESC_HI(1024)), "n"(SCALE));
}
static __device__ __forceinline__ void ldmatrix_x4_trans(uint32_t (&r)[4], uint32_t addr) {
  asm volatile("ldmatrix.sync.aligned.m8n8.x4.trans.shared.b16 {%0,%1,%2,%3}, [%4];"
               : "=r"(r[0]), "=r"(r[1]), "=r"(r[2]), "=r"(r[3]) : "r"(addr) : "memory");
}
static __device__ __forceinline__ void mma_16816(float (&d)[4], const uint32_t (&a)[4], uint32_t b0, uint32_t b1) {
  asm volatile("mma.sync.aligned.m16n8k16.row.col.f32.bf16.bf16.f32 {%0,%1,%2,%3}, {%4,%5,%6,%7}, {%8,%9}, {%0,%1,%2,%3};"
               : "+f"(d[0]), "+f"(d[1]), "+f"(d[2]), "+f"(d[3])
               : "r"(a[0]), "r"(a[1]), "r"(a[2]), "r"(a[3]), "r"(b0), "r"(b1));
}

static __device__ __forceinline__ uint32_t mapa(uint32_t addr, uint32_t rank) {
  uint32_t r; asm volatile("mapa.shared::cluster.u32 %0, %1, %2;" : "=r"(r) : "r"(addr), "r"(rank)); return r;
}

static __device__ __forceinline__ void mbar_init(uint32_t bar, int cnt) {
  asm volatile("mbarrier.init.shared::cta.b64 [%0], %1;" :: "r"(bar), "r"(cnt) : "memory");
}
static __device__ __forceinline__ void mbar_expect_tx(uint32_t bar, uint32_t bytes) {
  asm volatile("mbarrier.arrive.expect_tx.shared::cta.b64 _, [%0], %1;" :: "r"(bar), "r"(bytes) : "memory");
}
static __device__ __forceinline__ void tma_load_2d(uint32_t dst, const CUtensorMap* tm, int c0, int c1, uint32_t bar) {
  asm volatile("cp.async.bulk.tensor.2d.shared::cluster.global.mbarrier::complete_tx::bytes [%0], [%1, {%3, %4}], [%2];"
               :: "r"(dst), "l"(tm), "r"(bar), "r"(c0), "r"(c1) : "memory");
}

static __device__ unsigned char g_win[6 << 20];
static __device__ unsigned int g_side[67 * 32];
static __device__ unsigned int g_err;
#define W_UP (1u << 20)
#define W_2 (2u << 20)
static __device__ __forceinline__ uint32_t w_blk(uint32_t off, uint32_t side) { return off | (((__popc((off >> 12) & 0xb3u) ^ side) & 1u) << 12); }
static __device__ __forceinline__ uint32_t w_h1(int c) { return W_UP | (1u << 13) | ((c >> 1) << 14) | ((c & 1) << 11); }
#define W_DS 0x30000u
static __device__ __forceinline__ uint32_t w_ar(int s) { return ((s & 1) << 15) | ((s & 2) << 17); }
static __device__ __forceinline__ uint32_t w_mvx(int c, int s) { return W_2 | ((s & 1) << 20) | ((c >> 1) << 14) | ((c & 1) << 11); }
static __device__ __forceinline__ uint32_t w_mxa(int c, int s) { return W_2 | ((s & 1) << 20) | (1u << 13) | ((c >> 1) << 14) | ((c & 1) << 11); }
#define H1_V (1u << 13)

#define SPIN_LIMIT (1 << 18)

#define SM_X 0
#define SM_WOS 65536
#define SM_WVS 131072
#define SM_MEM 163840
#define SM_QKP 180224
#define SM_VP 184320
#define SM_CW 188416
#define SM_VST 196608
#define SM_VR 196608
#define SM_CQ 200704
#define SM_CV 208896
#define SM_XF 217088
#define SM_VL 221184
#define SM_OF 225280
#define SM_OX 227328
#define SM_PF 229376
#define SM_PX 230016
#define SM_RD 198656
#define SM_QA 223232
#define SM_XS 231168
#define SM_BAR 231808
#define SM_Z 231936
#define SM_TOTAL 232128
#define MB_F 0
#define MB_XE0 16
#define MB_XE1 112
#define MB_INIT 24
#define MB_MEM 32
#define MB_W 256
#define MB_XF 64
#define MB_VR 72
#define MB_X0 80
#define MB_WO 88
#define SM_SIDE (SM_BAR + 96)
#define B_QK 1
#define B_V 2
#define B_P 3
#define B_O 4
#define B_O2 5
#define B_PUB 6
#define B_CQ 7
#define B_QK1 8
#define B_PXF 10
#define B_CV 15
#define B_X2 11
#define B_PX 12
#define B_GO 14
#define B_G1 13

#ifdef PROF
__device__ unsigned int g_ts[NCTA][80][32];
#ifdef GT
#define TCLK() gt32()
#else
#define TCLK() clk32()
#endif
#ifndef TMASK
#define TMASK 0xffffffffu
#endif
#define TST(st, i, c, v) do { if ((TMASK >> (i)) & 1u) asm volatile("{\n.reg .pred q;\nsetp.eq.u32 q, %2, 0;\n@q st.global.u32 [%0], %1;\n}" :: "l"(&g_ts[cta][(st) + 1][i]), "r"((uint32_t)(v)), "r"((uint32_t)(c)) : "memory"); } while (0)
#define TS(i) TST(s, i, l16, TCLK())
#define TV(i, v) TST(s, i, l16, v)
#define TSF(i, w) TST(s, i, l16 | (w8 ^ (w)), TCLK())
#define TSP(i, w) TST(s - 1, i, l16 | (w8 ^ (w)), TCLK())
#define TVF(i, v) TV(i, v)
#else
#define TST(a, b, c, d)
#define TSF(i, w)
#define TSP(i, w)
#define TVF(i, v)
#define TS(i)
#define TV(i, v)
#endif

static __device__ __forceinline__ void bar_sync(int id, int n) { asm volatile("bar.sync %0, %1;" :: "r"(id), "r"(n) : "memory"); }
static __device__ __forceinline__ void bar_arrive(int id, int n) { asm volatile("bar.arrive %0, %1;" :: "r"(id), "r"(n) : "memory"); }
static __device__ __forceinline__ uint4 ldg_r4(const void* p) { uint4 v;
  asm volatile("ld.relaxed.gpu.global.v4.u32 {%0,%1,%2,%3}, [%4];" : "=r"(v.x), "=r"(v.y), "=r"(v.z), "=r"(v.w) : "l"(p) : "memory"); return v; }
static __device__ __forceinline__ uint32_t ldg_r1(const void* p) { uint32_t v;
  asm volatile("ld.relaxed.gpu.global.u32 %0, [%1];" : "=r"(v) : "l"(p) : "memory"); return v; }
static __device__ __forceinline__ void stg_r4(void* p, uint32_t a, uint32_t b, uint32_t c, uint32_t d) {
  asm volatile("st.relaxed.gpu.global.v4.u32 [%0], {%1,%2,%3,%4};" :: "l"(p), "r"(a), "r"(b), "r"(c), "r"(d) : "memory"); }
static __device__ __forceinline__ uint2 ldg_r2(const void* p) { uint2 v;
  asm volatile("ld.relaxed.gpu.global.v2.u32 {%0,%1}, [%2];" : "=r"(v.x), "=r"(v.y) : "l"(p) : "memory"); return v; }
static __device__ __forceinline__ void stg_4(void* p, const uint4& v) {
  asm volatile("st.global.v4.u32 [%0], {%1,%2,%3,%4};" :: "l"(p), "r"(v.x), "r"(v.y), "r"(v.z), "r"(v.w) : "memory"); }
static __device__ __forceinline__ uint32_t f2u(float v) { return __float_as_uint(v); }
static __device__ __forceinline__ void stg_2(void* p, uint32_t a, uint32_t b) {
  asm volatile("st.global.v2.u32 [%0], {%1,%2};" :: "l"(p), "r"(a), "r"(b) : "memory"); }
static __device__ __forceinline__ void stg_r1(void* p, uint32_t a) {
  asm volatile("st.relaxed.gpu.global.u32 [%0], %1;" :: "l"(p), "r"(a) : "memory"); }
static __device__ __forceinline__ void sts128(uint32_t a, uint32_t x, uint32_t y, uint32_t z, uint32_t w) {
  asm volatile("st.shared.v4.u32 [%0], {%1,%2,%3,%4};" :: "r"(a), "r"(x), "r"(y), "r"(z), "r"(w) : "memory"); }
static __device__ __forceinline__ void sts128f(uint32_t a, float x, float y, float z, float w) {
  asm volatile("st.shared.v4.f32 [%0], {%1,%2,%3,%4};" :: "r"(a), "f"(x), "f"(y), "f"(z), "f"(w) : "memory"); }
static __device__ __forceinline__ uint4 lds128(uint32_t a) { uint4 v;
  asm volatile("ld.shared.v4.u32 {%0,%1,%2,%3}, [%4];" : "=r"(v.x), "=r"(v.y), "=r"(v.z), "=r"(v.w) : "r"(a) : "memory"); return v; }
static __device__ __forceinline__ float4 lds128f(uint32_t a) { float4 v;
  asm volatile("ld.shared.v4.f32 {%0,%1,%2,%3}, [%4];" : "=f"(v.x), "=f"(v.y), "=f"(v.z), "=f"(v.w) : "r"(a) : "memory"); return v; }
static __device__ __forceinline__ void sts32(uint32_t a, uint32_t x) { asm volatile("st.shared.u32 [%0], %1;" :: "r"(a), "r"(x) : "memory"); }
static __device__ __forceinline__ uint2 lds64(uint32_t a) { uint2 v;
  asm volatile("ld.shared.v2.u32 {%0,%1}, [%2];" : "=r"(v.x), "=r"(v.y) : "r"(a) : "memory"); return v; }
static __device__ __forceinline__ void st_async4(uint32_t ra, float x, float y, float z, float w, uint32_t rbar) {
  asm volatile("st.async.weak.shared::cluster.mbarrier::complete_tx::bytes.v4.f32 [%0], {%1,%2,%3,%4}, [%5];"
               :: "r"(ra), "f"(x), "f"(y), "f"(z), "f"(w), "r"(rbar) : "memory"); }
static __device__ __forceinline__ void stsm4t(uint32_t a, uint32_t x, uint32_t y, uint32_t z, uint32_t w) {
  asm volatile("stmatrix.sync.aligned.m8n8.x4.trans.shared.b16 [%0], {%1,%2,%3,%4};" :: "r"(a), "r"(x), "r"(y), "r"(z), "r"(w) : "memory"); }
static __device__ __forceinline__ uint32_t hmax2(uint32_t a, uint32_t b) { uint32_t d;
  asm("max.f16x2 %0, %1, %2;" : "=r"(d) : "r"(a), "r"(b)); return d; }
static __device__ __forceinline__ uint32_t hadd2(uint32_t a, uint32_t b) { uint32_t d;
  asm("add.rn.f16x2 %0, %1, %2;" : "=r"(d) : "r"(a), "r"(b)); return d; }
static __device__ __forceinline__ uint32_t packv(float a, float b, float c, float d) { uint32_t r;
  asm volatile("{\n.reg .f32 x, y;\nadd.f32 x, %1, %2;\nadd.f32 y, %3, %4;\ncvt.rn.bf16x2.f32 %0, y, x;\n}" : "=r"(r) : "f"(a), "f"(b), "f"(c), "f"(d)); return r; }
static __device__ __forceinline__ uint32_t packh(float a, float b, float c, float d) { uint32_t r;
  asm volatile("{\n.reg .f32 x, y;\nadd.f32 x, %1, %2;\nadd.f32 y, %3, %4;\ncvt.rn.satfinite.f16x2.f32 %0, y, x;\n}" : "=r"(r) : "f"(a), "f"(b), "f"(c), "f"(d)); return r; }
static __device__ __forceinline__ float ex2v(float a, float b, float c) { float y;
  asm volatile("{\n.reg .f32 x;\nfma.rn.f32 x, %1, %2, %3;\nex2.approx.ftz.f32 %0, x;\n}" : "=f"(y) : "f"(a), "f"(b), "f"(c)); return y; }
static __device__ __forceinline__ uint32_t shfl_x(uint32_t a, int m) { uint32_t d;
  asm volatile("shfl.sync.bfly.b32 %0, %1, %2, 0x1f, 0xffffffff;" : "=r"(d) : "r"(a), "r"(m)); return d; }
static __device__ __forceinline__ void h2f(float& lo, float& hi, uint32_t a) {
  asm volatile("{\n.reg .b16 l, h;\nmov.b32 {l, h}, %2;\ncvt.f32.f16 %0, l;\ncvt.f32.f16 %1, h;\n}" : "=f"(lo), "=f"(hi) : "r"(a)); }
static __device__ __forceinline__ uint4 ldsm4(uint32_t a) { uint4 v;
  asm volatile("ldmatrix.sync.aligned.m8n8.x4.shared.b16 {%0,%1,%2,%3}, [%4];" : "=r"(v.x), "=r"(v.y), "=r"(v.z), "=r"(v.w) : "r"(a) : "memory"); return v; }
static __device__ __forceinline__ uint4 ldsm4t(uint32_t a) { uint4 v;
  asm volatile("ldmatrix.sync.aligned.m8n8.x4.trans.shared.b16 {%0,%1,%2,%3}, [%4];" : "=r"(v.x), "=r"(v.y), "=r"(v.z), "=r"(v.w) : "r"(a) : "memory"); return v; }
static __device__ __forceinline__ uint32_t movm(uint32_t a) { uint32_t d;
  asm volatile("movmatrix.sync.aligned.m8n8.trans.b16 %0, %1;" : "=r"(d) : "r"(a)); return d; }
static __device__ __forceinline__ float u2f(uint32_t v) { return __uint_as_float(v); }
static __device__ __forceinline__ uint32_t tagw(uint32_t w, uint32_t t) { uint32_t d;
  asm("lop3.b32 %0, %1, %2, 1, 0xd8;" : "=r"(d) : "r"(w), "r"(t)); return d; }
static __device__ __forceinline__ uint32_t pack_f16(float lo, float hi) { uint32_t d;
  asm("cvt.rn.satfinite.f16x2.f32 %0, %1, %2;" : "=r"(d) : "f"(hi), "f"(lo)); return d; }
static __device__ __forceinline__ void sum_h4(float& lo, float& hi, uint32_t a, uint32_t b, uint32_t c, uint32_t d) {
  const float2 x = __half22float2(*reinterpret_cast<__half2*>(&a)), y = __half22float2(*reinterpret_cast<__half2*>(&b));
  const float2 z = __half22float2(*reinterpret_cast<__half2*>(&c)), w = __half22float2(*reinterpret_cast<__half2*>(&d));
  lo = (x.x + y.x) + (z.x + w.x); hi = (x.y + y.y) + (z.y + w.y);
}
static __device__ __forceinline__ uint32_t lds32(uint32_t a) { uint32_t v; asm volatile("ld.shared.u32 %0, [%1];" : "=r"(v) : "r"(a) : "memory"); return v; }
static __device__ __forceinline__ uint32_t addb2(uint32_t a, uint32_t b) { uint32_t d;
  asm("add.rn.bf16x2 %0, %1, %2;" : "=r"(d) : "r"(a), "r"(b)); return d; }
static __device__ __forceinline__ uint32_t mulb2(uint32_t a, uint32_t b) { uint32_t d;
  asm("mul.rn.bf16x2 %0, %1, %2;" : "=r"(d) : "r"(a), "r"(b)); return d; }
static __device__ __forceinline__ uint32_t mulb2v(uint32_t a, uint32_t b) { uint32_t d;
  asm volatile("mul.rn.bf16x2 %0, %1, %2;" : "=r"(d) : "r"(a), "r"(b)); return d; }
static __device__ __forceinline__ uint32_t x3(uint32_t a, uint32_t b, uint32_t t) { uint32_t d;
  asm("lop3.b32 %0, %1, %2, %3, 0x7e;" : "=r"(d) : "r"(a), "r"(b), "r"(t)); return d; }
static __device__ __forceinline__ uint32_t or3(uint32_t a, uint32_t b, uint32_t c) { uint32_t d;
  asm("lop3.b32 %0, %1, %2, %3, 0xfe;" : "=r"(d) : "r"(a), "r"(b), "r"(c)); return d; }
static __device__ __forceinline__ float ex2(float x) { float y; asm("ex2.approx.ftz.f32 %0, %1;" : "=f"(y) : "f"(x)); return y; }
static __device__ __forceinline__ float rcpf(float x) { float y; asm("rcp.approx.ftz.f32 %0, %1;" : "=f"(y) : "f"(x)); return y; }
static __device__ __forceinline__ void mbar_wait(uint32_t bar, int parity) {
  asm volatile("{\n.reg .pred p, q;\n.reg .u32 n;\nmbarrier.try_wait.parity.shared::cta.b64 p, [%0], %1;\n@p bra W_DONE;\nmov.u32 n, 0;\n"
               "W_LOOP:\nmbarrier.try_wait.parity.shared::cta.b64 p, [%0], %1;\nadd.u32 n, n, 1;\nsetp.lt.and.u32 q, n, %2, !p;\n@q bra W_LOOP;\nW_DONE:\n}"
               :: "r"(bar), "r"(parity), "n"(SPIN_LIMIT) : "memory");
}
static __device__ __forceinline__ uint32_t mbar_test(uint32_t bar, int parity) { uint32_t ok;
  asm volatile("{\n.reg .pred p;\nmbarrier.test_wait.parity.shared::cta.b64 p, [%1], %2;\nselp.u32 %0, 1, 0, p;\n}" : "=r"(ok) : "r"(bar), "r"(parity) : "memory"); return ok; }
static __device__ __forceinline__ void mbar_arrive(uint32_t bar) {
  asm volatile("mbarrier.arrive.shared::cta.b64 _, [%0];" :: "r"(bar) : "memory"); }
static __device__ __forceinline__ void mbar_arrive_cluster_rlx(uint32_t raddr) {
  asm volatile("mbarrier.arrive.relaxed.cluster.shared::cluster.b64 _, [%0];" :: "r"(raddr) : "memory"); }
static __device__ __forceinline__ void tma_load_mc(uint32_t dst, const CUtensorMap* tm, int c1, int c2, uint32_t bar) {
#ifdef NOTMA
  if ((NOTMA >> (c2 >> 3)) & 1) asm volatile("mbarrier.complete_tx.relaxed.cta.shared::cta.b64 [%0], 32768;" :: "r"(bar) : "memory"); else
#endif
  asm volatile("cp.async.bulk.tensor.3d.shared::cluster.global.mbarrier::complete_tx::bytes.multicast::cluster [%0], [%1, {%3, %4, %5}], [%2], %6;"
               :: "r"(dst), "l"(tm), "r"(bar), "r"(0), "r"(c1), "r"(c2), "h"((uint16_t)3) : "memory"); }
static __device__ __forceinline__ void cp16(uint32_t dst, const void* src) {
  asm volatile("cp.async.cg.shared.global [%0], [%1], 16;" :: "r"(dst), "l"(src) : "memory"); }
static __device__ __forceinline__ void mma_1688(float (&d)[4], uint32_t a0, uint32_t a1, uint32_t b0) {
  asm volatile("mma.sync.aligned.m16n8k8.row.col.f32.bf16.bf16.f32 {%0,%1,%2,%3}, {%4,%5}, {%6}, {%0,%1,%2,%3};"
               : "+f"(d[0]), "+f"(d[1]), "+f"(d[2]), "+f"(d[3]) : "r"(a0), "r"(a1), "r"(b0)); }
static __device__ __forceinline__ void mma4(float (&d)[4], uint32_t a0, uint32_t a1, uint32_t a2, uint32_t a3, uint32_t b0, uint32_t b1) {
  asm volatile("mma.sync.aligned.m16n8k16.row.col.f32.bf16.bf16.f32 {%0,%1,%2,%3}, {%4,%5,%6,%7}, {%8,%9}, {%0,%1,%2,%3};"
               : "+f"(d[0]), "+f"(d[1]), "+f"(d[2]), "+f"(d[3]) : "r"(a0), "r"(a1), "r"(a2), "r"(a3), "r"(b0), "r"(b1)); }
static __device__ __forceinline__ void mma4z(float (&d)[4], uint32_t a0, uint32_t a1, uint32_t a2, uint32_t a3, uint32_t b0, uint32_t b1) {
  asm volatile("mma.sync.aligned.m16n8k16.row.col.f32.bf16.bf16.f32 {%0,%1,%2,%3}, {%4,%5,%6,%7}, {%8,%9}, {%10,%10,%10,%10};"
               : "=f"(d[0]), "=f"(d[1]), "=f"(d[2]), "=f"(d[3]) : "r"(a0), "r"(a1), "r"(a2), "r"(a3), "r"(b0), "r"(b1), "f"(0.f)); }
static __device__ __forceinline__ uint32_t clk32() { uint32_t t; asm volatile("mov.u32 %0, %%clock;" : "=r"(t)); return t; }
static __device__ __forceinline__ uint32_t gt32() { uint32_t t; asm volatile("mov.u32 %0, %%globaltimer_lo;" : "=r"(t)); return t; }
static __device__ __forceinline__ void spin(int clk) { if (clk > 0) { uint32_t t = clk32(); while (clk32() - t < (uint32_t)clk) {} } }
static __device__ __forceinline__ void spinv(int clk, uint32_t z) { const uint32_t t = clk32() + (z >> 31); while (clk32() - t < (uint32_t)clk) {} }
#define FENCE() asm volatile("griddepcontrol.launch_dependents;" ::: "memory")
#define OPAQUE_L(p) asm volatile("" : "+l"(p))
#define OPAQUE_R(p) asm volatile("" : "+r"(p))

template <int KK, int K1, int W0, int NW, int FIRST> struct XR {
  static __device__ __forceinline__ void run(float (&d)[16], const uint32_t (&w)[NW][4], uint32_t b16) {
#ifdef NOWG
    if (KK % NOWG == 0)
#endif
    wgmma_n32_ra<(KK >> 2) * 4096 + (KK & 3) * 32, !FIRST>(d, w[W0 + KK], b16);
    XR<KK + 1, K1, W0, NW, 0>::run(d, w, b16);
  }
};
template <int K1, int W0, int NW, int FIRST> struct XR<K1, K1, W0, NW, FIRST> { static __device__ __forceinline__ void run(float (&)[16], const uint32_t (&)[NW][4], uint32_t) {} };
template <int KK, int K0, int K1, int FIRST> struct XS {
  static __device__ __forceinline__ void run(float (&d)[16], uint32_t a16, uint32_t b16) {
#ifdef NOWG
    if (KK % NOWG == 0)
#endif
    wgmma_n32_ss_ta<(KK - K0) * 2048, (KK >> 2) * 4096 + (KK & 3) * 32, !FIRST>(d, a16, b16);
    XS<KK + 1, K0, K1, 0>::run(d, a16, b16);
  }
};
template <int K0, int K1, int FIRST> struct XS<K1, K0, K1, FIRST> { static __device__ __forceinline__ void run(float (&)[16], uint32_t, uint32_t) {} };

static __device__ bf16 g_h[8 * FF];
static __device__ unsigned int g_sbar;
struct SideParams { const bf16* x; const bf16* w_r; const bf16* w_gate; const bf16* w_up; const bf16* w_down; const bf16* gate_w; const bf16* Wo; };

static __device__ __forceinline__ void side_barrier(unsigned int target) {
  __syncthreads();
  if (threadIdx.x == 0) {
    __threadfence();
    atomicAdd(&g_sbar, 1u);
    int n = 0;
    while (*(volatile unsigned int*)&g_sbar < target) { if (++n > (1 << 22)) { g_err = 50; break; } }
    __threadfence();
  }
  __syncthreads();
}
static __device__ __forceinline__ uint4 ldg_nc(const void* p) { uint4 v;
  asm volatile("ld.global.nc.L1::no_allocate.v4.u32 {%0,%1,%2,%3}, [%4];" : "=r"(v.x), "=r"(v.y), "=r"(v.z), "=r"(v.w) : "l"(p)); return v; }
#ifndef SPD
#define SPD 3
#endif
static __device__ __forceinline__ void l2pf(const void* p) { asm volatile("prefetch.global.L2 [%0];" :: "l"(p)); }
static __device__ __forceinline__ void mm8(float (&acc)[8][4], const bf16* W, const bf16* Wn, int ldw, int nk16, uint32_t abase, uint32_t ring, int lane) {
  const int rw = lane >> 3, ch = lane & 7;
  const bf16* wp = W + (size_t)rw * ldw + ch * 8;
  const uint32_t wd = ring + rw * 128, rd = ring + ((rw & 1) * 8 + ch) * 128;
#define MM_LD(k) do { if ((k) < nk16) { const bf16* q = wp + (size_t)(k) * 16 * ldw; \
    _Pragma("unroll") for (int i = 0; i < 4; i++) cp16(wd + ((k) & 3) * 2048 + i * 512 + ((ch ^ (rw + (i & 1) * 4)) << 4), q + (size_t)(4 * i) * ldw); } \
    asm volatile("cp.async.commit_group;" ::: "memory"); } while (0)
  __syncwarp();
  MM_LD(0); MM_LD(1); MM_LD(2);
#pragma unroll 1
  for (int k = 0; k < nk16; k++) {
    if (SPD && (k & 1) == 0) {
      const int kp = k + 4 * SPD;
      const bf16* pf = kp < nk16 ? W + (size_t)(kp * 16) * ldw : Wn ? Wn + (size_t)((kp - nk16) * 16) * ldw : nullptr;
      if (pf) l2pf(pf + (size_t)lane * ldw);
    }
    asm volatile("cp.async.wait_group 2;" ::: "memory");
    __syncwarp();
    MM_LD(k + 3);
    const uint32_t a0 = lds32(abase + k * 32), a2 = lds32(abase + k * 32 + 16);
#pragma unroll
    for (int i = 0; i < 4; i++) {
      const uint4 b = ldsm4t(rd + (k & 3) * 2048 + (((2 * i + (rw >> 1)) ^ ch) << 4));
      mma4(acc[2 * i], a0, 0u, a2, 0u, b.x, b.y); mma4(acc[2 * i + 1], a0, 0u, a2, 0u, b.z, b.w);
    }
  }
}
static __device__ __noinline__ void side_work(const SideParams& P, unsigned char* smem, int q) {
  const int tid = threadIdx.x, lane = tid & 31, warp = tid >> 5, g = lane >> 2, t = lane & 3;
  const uint32_t sb = smem_u32(smem);
  unsigned int* cand = reinterpret_cast<unsigned int*>(smem);
  bf16* xs = reinterpret_cast<bf16*>(smem + 1024);
  float* part = reinterpret_cast<float*>(smem + 65536);
  {
    for (int i = tid; i < 256; i += 384) *reinterpret_cast<uint4*>(smem + 1024 + i * 16) = ldg_nc((i < 128 ? P.gate_w : P.w_r - DM) + i * 8);
    __syncthreads();
#pragma unroll 1
    for (int it = warp; it < 64; it += 12) {
      const bf16* xp = P.x + (size_t)(q * 512 + (it >> 1) * 16 + g) * DM + (it & 1) * 512 + t * 8;
      for (int a = it == warp ? 0 : 1; a < 2 && it + 12 * a < 64; a++)
#pragma unroll
        for (int i = 0; i < 4; i++) l2pf(P.x + (size_t)(q * 512 + (it >> 1) * 16 + a * 96 + i * 4 + (lane >> 3)) * DM + (it & 1) * 512 + (lane & 7) * 64);
      const uint32_t xb = sb + 16384 + warp * 16384 + lane * 16;
#pragma unroll
      for (int i = 0; i < 16; i++) { cp16(xb + i * 1024, xp + i * 32); cp16(xb + i * 1024 + 512, xp + 8 * DM + i * 32); }
      asm volatile("cp.async.commit_group;\ncp.async.wait_group 0;" ::: "memory");
      float sg[4] = {0.f, 0.f, 0.f, 0.f}, sr[4] = {0.f, 0.f, 0.f, 0.f};
#pragma unroll
      for (int i = 0; i < 16; i++) {
        const uint4 gw = lds128(sb + 1024 + (it & 1) * 1024 + i * 64 + t * 16), wr = lds128(sb + 3072 + (it & 1) * 1024 + i * 64 + t * 16);
        const uint4 lo = lds128(xb + i * 1024), hi = lds128(xb + i * 1024 + 512);
        mma4(sr, lo.x, hi.x, lo.y, hi.y, wr.x, wr.y); mma4(sr, lo.z, hi.z, lo.w, hi.w, wr.z, wr.w);
        mma4(sg, mulb2(lo.x, gw.x), mulb2(hi.x, gw.x), mulb2(lo.y, gw.y), mulb2(hi.y, gw.y), 0x3F803F80u, 0x3F803F80u);
        mma4(sg, mulb2(lo.z, gw.z), mulb2(hi.z, gw.z), mulb2(lo.w, gw.w), mulb2(hi.w, gw.w), 0x3F803F80u, 0x3F803F80u);
      }
      if (t == 0) {
        float* pp = reinterpret_cast<float*>(smem + 8192) + (it & 1) * 1024 + (it >> 1) * 16 + g;
        pp[0] = sg[0]; pp[8] = sg[2]; pp[512] = sr[0]; pp[520] = sr[2];
      }
    }
    __syncthreads();
    for (int i = tid; i < 512; i += 384) {
      const float* pp = reinterpret_cast<const float*>(smem + 8192);
      g_gate[q * 512 + i] = rbf(1.f / (1.f + expf(-rbf(pp[i] + pp[1024 + i]))));
      g_r[q * 512 + i] = rbf(pp[512 + i] + pp[1536 + i]);
    }
    for (int i = tid; i < 16 * 896; i += 384) part[i] = 0.f;
  }
#define GU(u) (((u) % 28) / 14 ? P.w_up : P.w_gate) + (size_t)((u) / 28) * 512 * FF + q * 896 + ((u) % 14) * 64
  for (int i = lane; i < 64 * SPD; i += 32) l2pf(GU(warp) + (size_t)i * FF);
  side_barrier(4);
  {
    unsigned int key[8];
#pragma unroll
    for (int i = 0; i < 8; i++) {
      const int tok = (warp & 7) * 256 + i * 32 + lane;
      const uint32_t b = __float_as_uint(__ldcg(&g_r[tok]) + 0.f) >> 16;
      key[i] = (((b & 0x8000u) ? (~b & 0xffffu) : (b | 0x8000u)) << 16) | (uint32_t)(2047 - tok);
    }
    for (int pass = 0; pass < 2; pass++) {
      if (pass == 0 ? warp < 8 : warp == 0) {
        for (int c = 0; c < 8; c++) {
          const unsigned int m = __reduce_max_sync(~0u, max(max(max(key[0], key[1]), max(key[2], key[3])), max(max(key[4], key[5]), max(key[6], key[7]))));
#pragma unroll
          for (int i = 0; i < 8; i++) if (key[i] == m) key[i] = 0u;
          if (lane == 0) cand[pass ? 128 + c : warp * 8 + c] = m;
        }
      }
      __syncthreads();
      if (pass == 0 && warp == 0) {
#pragma unroll
        for (int i = 0; i < 8; i++) key[i] = i < 2 ? cand[i * 32 + lane] : 0u;
      }
    }
    if (q == 0 && tid < 8) g_idx[tid] = 2047 - (int)(cand[128 + tid] & 0xffffu);
    for (int i = tid; i < 1024; i += 384) {
      const int c = i >> 7, tok = 2047 - (int)(cand[128 + c] & 0xffffu);
      *reinterpret_cast<uint4*>(xs + c * (FF + 8) + (i & 127) * 8) = ldg_nc(P.x + (size_t)tok * DM + (i & 127) * 8);
    }
    __syncthreads();
  }
  const uint32_t abase = sb + 1024 + g * (FF + 8) * 2 + t * 4, ring = sb + 131072 + warp * 8192;
  for (int u = warp; u < 56; u += 12) {
    const int kh = u / 28, mat = (u % 28) / 14, cb = u % 14;
    float acc[8][4];
#pragma unroll
    for (int i = 0; i < 8; i++) acc[i][0] = acc[i][1] = acc[i][2] = acc[i][3] = 0.f;
    mm8(acc, GU(u), u + 12 < 56 ? GU(u + 12) : nullptr, FF, DM / 32, abase + kh * 1024, ring, lane);
    float* pp = part + (mat * 8 + g) * 896 + cb * 64 + 2 * t;
#pragma unroll
    for (int i = 0; i < 8; i++) { atomicAdd(pp + 8 * i, acc[i][0]); atomicAdd(pp + 8 * i + 1, acc[i][1]); }
  }
  for (int i = lane; i < 64 * SPD; i += 32) l2pf(P.w_down + (size_t)((warp >> 2) * 1216 + i) * DM + q * 256 + (warp & 3) * 64);
  __syncthreads();
  for (int i = tid; i < 8 * 896; i += 384) {
    const float ag = rbf(part[i]), au = rbf(part[8 * 896 + i]);
    g_h[(i / 896) * FF + q * 896 + i % 896] = __float2bfloat16(rbf(ag / (1.f + expf(-ag))) * au);
  }
  side_barrier(8);
  for (int i = tid; i < 8 * FF / 8; i += 384) {
    const int c = i / (FF / 8), o = i % (FF / 8);
    *reinterpret_cast<uint4*>(xs + c * (FF + 8) + o * 8) = __ldcg(reinterpret_cast<const uint4*>(g_h + c * FF + o * 8));
  }
  __syncthreads();
  {
    const int cb = warp & 3, kq = warp >> 2;
    float acc[8][4];
#pragma unroll
    for (int i = 0; i < 8; i++) acc[i][0] = acc[i][1] = acc[i][2] = acc[i][3] = 0.f;
    mm8(acc, P.w_down + (size_t)kq * 1216 * DM + q * 256 + cb * 64, nullptr, DM, kq == 2 ? 72 : 76, abase + kq * 1216 * 2, ring, lane);
#pragma unroll
    for (int i = 0; i < 8; i++) { part[(kq * 8 + g) * 256 + cb * 64 + 2 * t + 8 * i] = acc[i][0]; part[(kq * 8 + g) * 256 + cb * 64 + 2 * t + 8 * i + 1] = acc[i][1]; }
    __syncthreads();
    for (int i = tid; i < 2048; i += 384) {
      const int c = i >> 8, tok = 2047 - (int)(cand[128 + c] & 0xffffu);
      const float y = (part[i] + part[2048 + i]) + part[4096 + i];
      const float rs = rbf(1.f / (1.f + expf(-__ldcg(&g_r[tok]))));
      g_upd[c * DM + q * 256 + (i & 255)] = __float2bfloat16(rbf(y) * rs);
    }
  }
}
struct RecParams { const bf16* mem0; unsigned char* win; };
struct WMaps { CUtensorMap q, k, v; };
#ifndef KB
#define KB 8
#endif
#ifndef WPF
#define WPF 7
#endif
#ifndef WPA
#define WPA 3
#endif
#ifndef XPF
#define XPF 4
#endif
#ifndef O2P
#define O2P 4
#endif
#ifndef XG
#define XG 1
#endif
#ifndef Z0
#define Z0 1
#endif
#ifndef Z1
#define Z1 1
#endif
#ifndef WKP
#define WKP 0
#endif
#ifndef XSD
#define XSD 0
#endif
#ifndef OS
#define OS 1
#endif
#ifndef SO
#define SO 1
#endif
#define RF_FAT 208
#define RF_CTL 88
#define WSPL 1
#define NPROBE 3
#define DLY_TB 700
#ifndef DLY_SIDE
#define DLY_SIDE 16000
#endif
#define KU 32
#define KD 4
#ifndef DLYS
#define DLYS 560, 200, 225, 150, 770, 250, 1224, 850, 460
#endif
#define NTUNE 9
#define TUNE_NAMES {"OM3", "XL", "S", "XD", "WO", "V", "OK", "OKS", "ORR"}
__constant__ int g_tune[NTUNE] = {DLYS};
#define DLY_M3 g_tune[0]
#define DLY_XL g_tune[1]
#define DLY_S g_tune[2]
#define DLY_XD g_tune[3]
#define DLY_WO g_tune[4]
#define DLY_V g_tune[5]
#define DLY_K g_tune[6]
#define DLY_KS g_tune[7]
#define DLY_RR g_tune[8]
#ifdef PRO
__device__ unsigned g_pro[NCTA][16];
#define PT(i, c) do { if (c) g_pro[cta][i] = gt32(); } while (0)
#else
#define PT(i, c)
#endif
#ifdef PER
__device__ unsigned g_pk[NCTA][64], g_pclk[NCTA][64], g_per[NCTA][64], g_end[8] = {0, 0, 0, 0, 0, 0, 0, 100000};
#endif
#define STR2(x) #x
#define STR(x) STR2(x)

static __device__ __forceinline__ void cp16p(uint32_t dst, const void* src, uint32_t v) {
  asm volatile("{\n.reg .pred q;\nsetp.ne.u32 q, %2, 0;\n@q cp.async.cg.shared.global [%0], [%1], 16;\n}" :: "r"(dst), "l"(src), "r"(v) : "memory"); }
static __device__ __forceinline__ void red_bf2(void* p, uint32_t v) {
  asm volatile("red.relaxed.gpu.global.add.noftz.bf16x2 [%0], %1;" :: "l"(p), "r"(v) : "memory"); }
static __device__ __forceinline__ void red_bf2p4(void* p, uint32_t v, uint32_t e) {
  asm volatile("{\n.reg .pred q;\nsetp.lt.u32 q, %2, 4;\n@q red.relaxed.gpu.global.add.noftz.bf16x2 [%0], %1;\n}" :: "l"(p), "r"(v), "r"(e) : "memory"); }
static __device__ __forceinline__ void eta2(void* p, uint32_t t, uint32_t first, uint32_t l16) {
  asm volatile("{\n.reg .pred q;\nsetp.lt.u32 q, %3, 32;\n@q red.relaxed.gpu.global.max.u32 [%0+4], %1;\n@q red.relaxed.gpu.global.add.u32 [%0], %2;\n}" :: "l"(p), "r"(t), "r"(first), "r"(l16) : "memory"); }
static __device__ __forceinline__ void sts16(uint32_t a, uint32_t x) { asm volatile("{\n.reg .b16 h;\ncvt.u16.u32 h, %1;\nst.shared.u16 [%0], h;\n}" :: "r"(a), "r"(x) : "memory"); }
static __device__ __forceinline__ uint32_t cnt_word(uint32_t L) { return (L & 17u) | ((L & 6u) << 1) | ((L & 8u) >> 2); }
static __device__ __forceinline__ uint32_t cnt_line(uint32_t l) { return (l & 17u) | ((l & 12u) >> 1) | ((l & 2u) << 2); }
static __device__ __forceinline__ int m3_check(uint32_t sb, const unsigned char* p3, const unsigned char* pd, int dq, uint32_t l16, uint32_t mc, int hf, int s) {
  const uint32_t md = l16 + (sb + SM_MEM + hf * 8192), dd = l16 + (sb + SM_RD + hf * 256), dc = (l16 >> 2) + (sb + SM_RD + hf * 256);
  int n = 0;
  uint32_t c0 = 0, c1 = 0, d0 = 0, d1 = 0, todo = 1;
#pragma unroll 1
  do {
    if (n) {
      const int src = cnt_word(l16 >> 4);
      const uint32_t m0 = __ballot_sync(~0u, (__shfl_sync(~0u, c0, src) >> 16) != 0x4200u) >> (l16 >> 7), m1 = __ballot_sync(~0u, (__shfl_sync(~0u, c1, src) >> 16) != 0x4200u) >> (l16 >> 7);
      const uint32_t m2 = __ballot_sync(~0u, (d0 >> 16) != 0x4200u), m3 = __ballot_sync(~0u, (d1 >> 16) != 0x4200u);
#pragma unroll
      for (int i = 0; i < 8; i++) { cp16p(md + i * 512, p3 + i * 1024, m0 & (1u << (4 * i))); cp16p(md + 4096 + i * 512, p3 + dq + i * 1024, m1 & (1u << (4 * i))); }
      cp16p(dd, pd, l16 < 256u ? (((l16 & 128u) ? m3 : m2) >> ((l16 >> 2) & 28u)) & 15u : 0u);
      sts32(sb + SM_Z + 40, s);
    }
    n++;
    asm volatile("cp.async.commit_group;\ncp.async.wait_group 0;" ::: "memory");
    __syncwarp();
    asm volatile("{\n.reg .pred p, q;\n.reg .b32 a, b;\n.reg .b16 h, g;\nsetp.ne.u32 p, %4, 0;\n"
                 "@p ld.shared.u32 %2, [%6];\n@p ld.shared.u32 %3, [%6+128];\n@p ld.shared.u32 %0, [%5];\n@p ld.shared.u32 %1, [%5+4096];\n"
                 "lop3.b32 a, %2, %3, 0x42000000, 0x7e;\nlop3.b32 b, %0, %1, 0x42000000, 0x7e;\nor.b32 a, a, b;\nsetp.lt.and.u32 q, a, %8, p;\n"
                 "cvt.u16.u32 h, %2;\ncvt.u16.u32 g, %3;\n@q st.shared.u16 [%5+2], h;\n@q st.shared.u16 [%5+4098], g;\n@q mbarrier.arrive.shared::cta.b64 _, [%7];\n"
                 "@q mov.u32 %4, 0;\n}"
                 : "+r"(c0), "+r"(c1), "+r"(d0), "+r"(d1), "+r"(todo) : "r"(mc), "r"(dc), "r"(sb + SM_BAR + MB_MEM + hf * 8), "r"(n < SPIN_LIMIT ? 0x10000u : ~0u) : "memory");
  } while (__any_sync(~0u, todo));
  return n - 1;
}

__global__ void __cluster_dims__(2, 1, 1) __launch_bounds__(384, 1)
rec_kernel(const __grid_constant__ CUtensorMap tmx, const __grid_constant__ CUtensorMap tmw, const __grid_constant__ WMaps W, RecParams P, const __grid_constant__ SideParams SP) {
  extern __shared__ __align__(1024) unsigned char smem[];
  asm volatile("griddepcontrol.launch_dependents;");
  const uint32_t sb = smem_u32(smem);
  const int tid = threadIdx.x, lane = tid & 31, t128 = tid & 127;
  const int wg = __shfl_sync(~0u, tid >> 7, 0), wq = __shfl_sync(~0u, (tid >> 5) & 3, 0);
  const int r = blockIdx.x & 1, pp = blockIdx.x >> 1;
  const int mi = lane >> 3, r8 = lane & 7;
  const uint32_t xb16 = __shfl_sync(~0u, (((sb + SM_X + (tid >> 7) * 32768 + r * 16384) & 0x3FFFF) >> 4) | (1u << 16), 0);
  const uint32_t va16 = __shfl_sync(~0u, (((sb + SM_WVS + (tid >> 7) * 16384) & 0x3FFFF) >> 4) | (64u << 16), 0);
#if defined(PER) || defined(PRO)
  const uint32_t tstart = gt32();
#endif

  if (tid == 0) {
    mbar_init(sb + SM_BAR + MB_F, 1); mbar_init(sb + SM_BAR + MB_F + 8, 1); mbar_init(sb + SM_BAR + MB_XE0, 2); mbar_init(sb + SM_BAR + MB_XE1, 2); mbar_init(sb + SM_BAR + MB_INIT, 2);
    mbar_init(sb + SM_BAR + MB_MEM, 32); mbar_init(sb + SM_BAR + MB_MEM + 8, 32); for (int i = 0; i < 8; i++) mbar_init(sb + SM_BAR + MB_W + i * 8, 1);
    mbar_init(sb + SM_BAR + MB_XF, 8); mbar_init(sb + SM_BAR + MB_X0, 1); mbar_init(sb + SM_BAR + MB_WO, 1); mbar_init(sb + SM_BAR + MB_VR, 5);
    sts32(sb + SM_Z + 40, ~0u);
    asm volatile("fence.mbarrier_init.release.cluster;" ::: "memory");
  }
  if (tid == 32) {
    asm volatile("prefetch.tensormap [%0];" :: "l"(&W.q) : "memory"); asm volatile("prefetch.tensormap [%0];" :: "l"(&W.k) : "memory");
    asm volatile("prefetch.tensormap [%0];" :: "l"(&W.v) : "memory"); asm volatile("prefetch.tensormap [%0];" :: "l"(&tmx) : "memory");
  }
  if (tid >= 256 && tid < 320) {
    unsigned char* pl = P.win + r * W_2 + (W_UP | (1u << 19) | ((pp >> 5) << 14)) + (pp & 31) * 128 + wq * 4096;
    stg_r1(pl + lane * 4, 0u);
    uint32_t best = 1u << 30;
    if (lane == 0) {
#pragma unroll 1
      for (int rep = 0; rep < NPROBE; rep++) {
        uint32_t dt;
        asm volatile("{\n.reg .u32 a, b, v;\nmov.u32 a, %%clock;\natom.relaxed.gpu.global.exch.b32 v, [%1], 0;\n"
                     "st.volatile.shared.u32 [%2], v;\nmov.u32 b, %%clock;\nsub.u32 %0, b, a;\n}" : "=r"(dt) : "l"(pl), "r"(sb + SM_SIDE + wq * 4) : "memory");
        best = min(best, dt);
      }
    }
    if (lane == 0) sts32(sb + SM_SIDE + wq * 4, best);
    bar_sync(B_P, 64);
    if (wq == 0) {
      const uint2 bt = lds64(sb + SM_SIDE);
      if (lane < 8 && (r == 0 || pp == 0)) stg_r1(&g_side[(r ? 66 : pp) * 32 + lane], 2u | (bt.x < bt.y ? 1u : 0u));
      spin(DLY_TB);
      uint32_t a, b, c; int n = 0;
#pragma unroll 1
      do {
        a = ldg_r1(&g_side[lane * 32]); b = ldg_r1(&g_side[(32 + lane) * 32]); c = ldg_r1(&g_side[(64 + min(lane, 2)) * 32]);
      } while (!__all_sync(~0u, a & b & c & 2u) && ++n < SPIN_LIMIT);
      a = __ballot_sync(~0u, a & 1u); b = __ballot_sync(~0u, b & 1u); c = __ballot_sync(~0u, c & 1u);
      const uint32_t pol2 = (a ^ (c >> 2)) & 1u;
      c &= 3u;
      const unsigned long long ab = ((unsigned long long)b << 32) | a;
      const int sd = pp < 64 ? (int)(ab >> pp) & 1 : (int)(c >> (pp - 64)) & 1;
      const int n1 = __popcll(ab) + __popc(c), n0 = 66 - n1;
      const int below1 = pp < 64 ? __popcll(ab & ((1ull << pp) - 1)) : __popcll(ab) + (pp == 65 ? (int)(c & 1u) : 0);
      const int rk = sd ? below1 : pp - below1;
      const int k0 = (n0 & 1) ? n0 - 1 : n0 >= n1 ? n0 - 2 : n0, k1 = 64 - k0;
      const int role = rk >= (sd ? k1 : k0) ? 64 + ((n0 & 1) ? sd : rk - (sd ? k1 : k0)) : sd ? k0 + rk : rk;
      __syncwarp();
      if (lane == 0) sts128(sb + SM_SIDE, 2 * k0, 0u, pol2, role * 2 + r);
#ifdef PER
      if (lane == 0) { atomicMax(&g_end[6], gt32()); atomicMin(&g_end[7], max(bt.x, bt.y) - min(bt.x, bt.y)); }
#endif
    }
  }
  __syncthreads();
  const int cta = __shfl_sync(~0u, (int)lds32(sb + SM_SIDE + 12), 0), h = cta >> 2, j = cta & 3, p = j >> 1;
  const int sw = (cta >= __shfl_sync(~0u, (int)lds32(sb + SM_SIDE), 0) ? 1 : 0) ^ r;
  if (cta >= NCTA) {
    spin(DLY_SIDE);
#ifndef NOSIDE
    side_work(SP, smem, cta - NCTA);
#endif
#ifdef PER
    if (threadIdx.x == 0) atomicMax(&g_end[1], gt32());
#endif
    return;
  }
#ifdef PER
  if (threadIdx.x == 0) g_per[cta][63] = tstart;
#endif
#ifdef PRO
  if (tid == 0) { g_pro[cta][0] = tstart; g_pro[cta][1] = gt32(); }
#endif
  asm volatile("barrier.cluster.arrive.relaxed.aligned;" ::: "memory");
#define WLOAD(i0, i1) _Pragma("unroll 1") for (int u = i0; u < i1; u++) {        \
    const int g2 = u >> 2, i = u & 3, k = g2 * 512 + ((i * 128 + r * 256) & 511); \
    const uint32_t mb = sb + SM_BAR + MB_W + u * 8; \
    mbar_expect_tx(mb, i < 2 ? 32768 : 16384); \
    tma_load_2d(sb + g2 * 65536 + i * 8192, &W.q, h * DH + j * 32, k, mb); \
    tma_load_2d(sb + g2 * 65536 + 32768 + i * 8192, &W.k, h * DH + j * 32, k, mb); \
    if (i < 2) tma_load_2d(sb + (i ? SM_WVS : SM_VST) + g2 * 16384, &W.v, h * DH + p * 64, k, mb); }
  if (tid == 288) {
    mbar_expect_tx(sb + SM_BAR + MB_X0, 32768);
#pragma unroll 1
    for (int i = 0; i < 2; i++)
      asm volatile("cp.async.bulk.tensor.3d.shared::cluster.global.mbarrier::complete_tx::bytes [%0], [%1, {%3, %3, %4}], [%2];"
                   :: "r"(sb + SM_MEM + i * 16384), "l"(&tmx), "r"(sb + SM_BAR + MB_X0), "r"(0), "r"(i * 4) : "memory");
    WLOAD(0, 4 + WSPL);
  }
  __syncwarp();
  asm volatile("barrier.cluster.wait.acquire.aligned;" ::: "memory");
#define SIDES() const uint4 sm2 = lds128(sb + SM_SIDE); const int nlo = sm2.x; const uint32_t me = cta >= nlo

#define XLOAD(t, sg) tma_load_mc(sb + SM_X + ((t) * 8 + r * 4) * 4096, &tmx, (sg) * SEG, (t) * 8 + r * 4, sb + SM_BAR + MB_F + (t) * 8)
#define F0LOAD() do { mbar_wait(sb + SM_BAR + MB_XE0, s & 1); \
    if (l16 == 0) XLOAD(0, s + 2); \
    __syncwarp(); } while (0)
  if (wg < 2) {
    asm volatile("setmaxnreg.inc.sync.aligned.u32 " STR(RF_FAT) ";");
    uint32_t w[32][4], wv[8][4];
    uint32_t lm = ((mi >> 1) * 8 + r8) * 128 + (((wq * 2 + (mi & 1)) ^ r8) << 4), l16 = lane * 16;
    lm = __shfl_sync(~0u, lm, lane); l16 = __shfl_sync(~0u, l16, lane);
    {
      const uint32_t lq0 = sb + wg * 65536 + (wq >> 1) * 32768 + ((mi >> 1) * 8 + r8) * 64 + ((((wq & 1) * 2 + (mi & 1)) ^ (r8 >> 1)) << 4);
      const uint32_t f = wq < 2 ? 0x3D003D00u : 0x3F803F80u;
#pragma unroll
      for (int i = 0; i < 4; i++) {
        mbar_wait(sb + SM_BAR + MB_W + (wg * 4 + i) * 8, 0);
        if (i == 3) PT(2 + wg, t128 == 0);
#pragma unroll
        for (int kk = 8 * i; kk < 8 * i + 8; kk++) ldmatrix_x4_trans(w[kk], lq0 + kk * 1024);
        if (i == 0) {
#pragma unroll
          for (int kk = 0; kk < 8; kk++) ldmatrix_x4_trans(wv[kk], sb + SM_VST + wg * 16384 + kk * 2048 + lm);
        }
#pragma unroll
        for (int kk = 32 * i; kk < 32 * i + 32; kk++) w[kk >> 2][kk & 3] = mulb2v(w[kk >> 2][kk & 3], f);
      }
    }
    if (wg == 0) bar_sync(B_V, 160);
    else bar_arrive(B_P, 160);
    const int w8 = wg * 4 + wq;
    const int cw = sw ^ wg;
    const uint32_t xh16 = xb16 ^ 1024u;
    const uint32_t rsb = mapa(sb, r ^ 1);
#define MT (l16 + (sb + SM_MEM + wg * 8192))
#define WA (lm + (sb + SM_WVS + wg * 16384))
#define WOF(f) (lm + (sb + SM_WOS + wg * 32768 + ((f) & 1) * 16384 + ((f) >> 1) * 2048))
#define TH(base) (l16 + (sb + (base) + w8 * 512))
#define TQ(base) (l16 + (sb + (base) + wq * 512))
#define DUMP(base) _Pragma("unroll") for (int n = 0; n < 4; n++) sts128f(TQ((base) + n * 2048), d[4 * n], d[4 * n + 1], d[4 * n + 2], d[4 * n + 3])
#define INIT(base) _Pragma("unroll") for (int n = 0; n < 4; n++) { const float4 t = lds128f(TQ((base) + n * 2048)); d[4 * n] = t.x; d[4 * n + 1] = t.y; d[4 * n + 2] = t.z; d[4 * n + 3] = t.w; }
#define XQK(first, b0, b1) do { wg_fence(); XR<0, 16, 0, 32, first>::run(d, w, b0); XR<0, 16, 16, 32, 0>::run(d, w, b1); wg_commit(); wg_wait0(); } while (0)
#define XVS(first, b0) do { wg_fence(); XS<8, 8, 16, first>::run(d, va16, b0); XR<0, 8, 0, 8, 0>::run(d, wv, b0); wg_commit(); wg_wait0(); } while (0)
#define XREL(mb) do { if (wq == 0 && l16 == 0) { mbar_arrive_cluster_rlx(rsb + SM_BAR + (mb)); mbar_arrive(sb + SM_BAR + (mb)); } } while (0)
#define XFOUT() do { \
          _Pragma("unroll") for (int hf = 0; hf < 2; hf++) \
            stsm4t(l16 + (sb + SM_XF + (wq * 2 + hf) * 512), pack_bf16(d[8 * hf], d[8 * hf + 1]), pack_bf16(d[8 * hf + 2], d[8 * hf + 3]), \
                   pack_bf16(d[8 * hf + 4], d[8 * hf + 5]), pack_bf16(d[8 * hf + 6], d[8 * hf + 7])); \
          __syncwarp(); \
          if (l16 < 32) mbar_arrive(sb + SM_BAR + MB_XF); } while (0)
#define VDUMP(base) _Pragma("unroll") for (int n = 0; n < 2; n++) sts128(TQ((base) + n * 2048), pack_bf16(d[8 * n], d[8 * n + 1]), pack_bf16(d[8 * n + 2], d[8 * n + 3]), pack_bf16(d[8 * n + 4], d[8 * n + 5]), pack_bf16(d[8 * n + 6], d[8 * n + 7]))

    if (wg == 0) {
      float d[16];
      const uint32_t x0 = (((sb + SM_MEM + r * 16384) & 0x3FFFF) >> 4) | (1u << 16), x1 = (((sb + SM_MEM + (r ^ 1) * 16384) & 0x3FFFF) >> 4) | (1u << 16);
      mbar_wait(sb + SM_BAR + MB_X0, 0);
      XQK(1, x0, x1);
      DUMP(SM_CQ);
      XVS(1, x0);
      bar_arrive(B_X2, 256);
      VDUMP(SM_CV);
      bar_sync(B_CQ, 256);
    } else {
      float d[16];
      bar_sync(B_CQ, 256);
      INIT(SM_CQ);
      mbar_wait(sb + SM_BAR + MB_F + 8, 0);
      PT(4, t128 == 0);
      XQK(0, xb16, xh16);
      XFOUT();
      PT(5, t128 == 0);
    }
#define QA (l16 + (sb + SM_QA + (w8 >> 1) * 512 + (w8 & 1) * 8))
    {
      const uint32_t qa = (((l16 & 0x30u) << 3) | ((l16 & 0x10u) << 2) | ((l16 >> 3) & 0x30u) | ((l16 >> 4) & 4u)) + w8 * 512;
      sts32(QA, qa + (sb + SM_QKP)); sts32(QA + 4, (qa ^ 64u) + (sb + SM_QKP));
    }
    if (wg == 0) mbar_wait(sb + SM_BAR + MB_F, 0);
    for (int s = -1;; s++) {
      if (s >= 0) {
        OPAQUE_R(lm); OPAQUE_R(l16);
        {
          uint32_t sa[4][4];
#pragma unroll
          for (int i = 0; i < 2; i++) ldmatrix_x4_trans(sa[i], WA + i * 2048);
          float a[2][4], v[2][4]; uint4 c[4]; uint2 qa;
          FENCE();
          mbar_wait(sb + SM_BAR + MB_MEM + wg * 8, s & 1);
#define QP(i) ((i) >= 12 ? (i) - 8 : (i) % 3 == 1 ? (i) / 3 : 8 + (i) - ((i) + 2) / 3)
#pragma unroll
          for (int i = 0; i < 3; i++) c[i] = ldsm4t(MT + QP(i) * 512);
#pragma unroll
          for (int i = 0; i < 16; i++) {
            if (i + 3 < 16) c[(i + 3) & 3] = ldsm4t(MT + QP(i + 3) * 512);
            if (i == 13) qa = lds64(QA);
            if (i == 0) {
              mma4z(a[0], w[2 * QP(i)][0], w[2 * QP(i)][1], w[2 * QP(i)][2], w[2 * QP(i)][3], c[i & 3].x, c[i & 3].y);
              mma4z(a[1], w[2 * QP(i) + 1][0], w[2 * QP(i) + 1][1], w[2 * QP(i) + 1][2], w[2 * QP(i) + 1][3], c[i & 3].z, c[i & 3].w);
            } else {
              mma_16816(a[0], w[2 * QP(i)], c[i & 3].x, c[i & 3].y);
              mma_16816(a[1], w[2 * QP(i) + 1], c[i & 3].z, c[i & 3].w);
            }
            if (QP(i) == 0) {
              mma4z(v[0], wv[0][0], wv[0][1], wv[0][2], wv[0][3], c[i & 3].x, c[i & 3].y);
              mma4z(v[1], wv[1][0], wv[1][1], wv[1][2], wv[1][3], c[i & 3].z, c[i & 3].w);
            } else if (QP(i) < 4) {
              mma_16816(v[0], wv[2 * (QP(i) & 3)], c[i & 3].x, c[i & 3].y);
              mma_16816(v[1], wv[2 * (QP(i) & 3) + 1], c[i & 3].z, c[i & 3].w);
            }
            if (i == 12) {
              mma_16816(v[0], sa[0], c[0].x, c[0].y); mma_16816(v[1], sa[1], c[0].z, c[0].w);
            }
            if (i == 13) { ldmatrix_x4_trans(sa[0], WA + 2 * 2048); ldmatrix_x4_trans(sa[1], WA + 3 * 2048); ldmatrix_x4_trans(sa[2], WA + 4 * 2048); }
            FENCE();
          }
#pragma unroll
          for (int i = 0; i < 4; i++) sts32(((i & 1) ? qa.y : qa.x) + (i >> 1) * 8, f2u(a[0][i] + a[1][i]));
          bar_arrive(B_QK, 288);
          bar_arrive(B_QK1, 288);
          FENCE();
          uint32_t sc2[4];
          ldmatrix_x4_trans(sa[3], WA + 5 * 2048); ldmatrix_x4_trans(sc2, WA + 6 * 2048);
          mma_16816(v[0], sa[0], c[1].x, c[1].y); mma_16816(v[1], sa[1], c[1].z, c[1].w);
          FENCE();
          ldmatrix_x4_trans(sa[0], WA + 7 * 2048);
          FENCE();
          mma_16816(v[0], sa[2], c[2].x, c[2].y); mma_16816(v[1], sa[3], c[2].z, c[2].w);
          mma_16816(v[0], sc2, c[3].x, c[3].y); mma_16816(v[1], sa[0], c[3].z, c[3].w);
          FENCE();
          sts128f(TH(SM_VP), v[0][0] + v[1][0], v[0][1] + v[1][1], v[0][2] + v[1][2], v[0][3] + v[1][3]);
          bar_arrive(B_V, 320);
        }
        if (s == NSEG - 1) break;
        OPAQUE_R(lm); OPAQUE_R(l16);
        uint32_t wo[WPF][4];
        {
          float d[16];
#define XOUT(g) _Pragma("unroll") for (int n = 0; n < 2; n++) sts128f(TQ(SM_CQ + ((g) * 2 + n) * 2048), d[8 - 8 * (g) + 4 * n], d[9 - 8 * (g) + 4 * n], d[10 - 8 * (g) + 4 * n], d[11 - 8 * (g) + 4 * n])
#define XIN(g) do { \
            const float4 t0 = lds128f(TQ(SM_CQ + (2 - 2 * (g)) * 2048)), t1 = lds128f(TQ(SM_CQ + (3 - 2 * (g)) * 2048)); \
            stsm4t(l16 + (sb + SM_XF + (wq * 2 + (g)) * 512), pack_bf16(d[8 * (g)] + t0.x, d[8 * (g) + 1] + t0.y), pack_bf16(d[8 * (g) + 2] + t0.z, d[8 * (g) + 3] + t0.w), \
                   pack_bf16(d[8 * (g) + 4] + t1.x, d[8 * (g) + 5] + t1.y), pack_bf16(d[8 * (g) + 6] + t1.z, d[8 * (g) + 7] + t1.w)); } while (0)
          if (wg == 0) {
            INIT(SM_CW);
            bar_sync(B_PUB, 320);
            wg_fence();
            XR<KB, 16, 0, 32, 0>::run(d, w, xb16); XR<0, 16, 16, 32, 0>::run(d, w, xh16);
            wg_commit(); wg_wait0();
            TSF(13, 1);
            OPAQUE_R(l16);
            XOUT(0);
            bar_arrive(B_G1, 256);
            XREL(MB_XE0);
            bar_sync(B_CQ, 256);
            XIN(0);
#pragma unroll
            for (int f = 0; f < WPA; f++) ldmatrix_x4_trans(wo[f], WOF(f));
          } else {
            const uint32_t ok = mbar_test(sb + SM_BAR + MB_F + 8, (s + 1) & 1);
            bar_sync(B_PUB, 320);
            if (!ok) mbar_wait(sb + SM_BAR + MB_F + 8, (s + 1) & 1);
            wg_fence();
#if WKP
            XR<0, 16, 0, 32, 1>::run(d, w, xb16); XR<0, WKP - 16, 16, 32, 0>::run(d, w, xh16);
            wg_commit(); wg_fence();
            XR<WKP - 16, WKP - 15, 16, 32, 0>::run(d, w, xh16);
#pragma unroll
            for (int f = 0; f < WPA; f++) ldmatrix_x4_trans(wo[f], WOF(f));
            wg_commit(); wg_fence();
            XR<WKP - 15, 16, 16, 32, 0>::run(d, w, xh16);
            wg_commit();
#else
            XR<0, 16, 0, 32, 1>::run(d, w, xb16); XR<0, 16, 16, 32, 0>::run(d, w, xh16);
            wg_commit();
#pragma unroll
            for (int f = 0; f < WPA; f++) ldmatrix_x4_trans(wo[f], WOF(f));
#endif
            wg_wait0();
            TSF(31, 5);
            OPAQUE_R(l16);
            XOUT(1);
            bar_arrive(B_CQ, 256);
            bar_sync(B_G1, 256);
            XIN(1);
          }
          __syncwarp();
          if (l16 == 0) mbar_arrive(sb + SM_BAR + MB_XF);
          TSF(3, 5);
        }
        if (Z1 && s == 0) {
          mbar_wait(sb + SM_BAR + MB_WO, 0);
#pragma unroll
          for (int f = 0; f < WPA; f++) ldmatrix_x4_trans(wo[f], WOF(f));
        }
#pragma unroll
        for (int f = WPA; f < WPF; f++) ldmatrix_x4_trans(wo[f], WOF(f));
        unsigned char* pa = P.win + (w_ar(s) + (j * 32 + cw * 16 + wq * 2) * 256 + (l16 >> 2));
        uint32_t ce = (l16 >> 4) - 4 * (cw * 4 + wq);
        OPAQUE_L(pa); OPAQUE_R(ce);
        FENCE();
        bar_sync(wg ? B_O : B_O2, wg || !XG ? 192 : 224);
        uint4 ob[2];
        ob[0] = ldsm4(l16 + (sb + SM_OF)); ob[1] = ldsm4(l16 + (sb + SM_OF + 512));
        float acc[2][4]; uint32_t f0ok;
#pragma unroll
        for (int f = 0; f < 16; f++) {
          const int ks = f >> 1;
          const uint32_t b0 = (ks & 1) ? ob[(ks >> 1) & 1].z : ob[(ks >> 1) & 1].x, b1 = (ks & 1) ? ob[(ks >> 1) & 1].w : ob[(ks >> 1) & 1].y;
          if (f < 2) mma4z(acc[f], wo[f][0], wo[f][1], wo[f][2], wo[f][3], b0, b1);
          else mma_16816(acc[f % 2], wo[f < WPF ? f : 2 + (f - WPF) % (WPF - 2)], b0, b1);
          if (f - 1 >= 2 && f - 1 + (WPF - 2) < 16) {
            const int nf = f - 1 + (WPF - 2);
            ldmatrix_x4_trans(wo[2 + (nf - WPF) % (WPF - 2)], WOF(nf));
          }
          if (f == 4 || f == 8) ob[((f >> 2) - 1) & 1] = ldsm4(l16 + (sb + SM_OF + (1 + (f >> 2)) * 512));
          if (f == 12) f0ok = mbar_test(sb + SM_BAR + MB_F, (s + 1) & 1);
          if (f < 15) FENCE();
        }
        if (!wg) bar_arrive(B_CV, 256);
        red_bf2(pa, pack_bf16(acc[0][0], ce == 0 ? 1.f : acc[0][1])); red_bf2(pa + 256, pack_bf16(acc[0][2], ce == 1 ? 1.f : acc[0][3]));
        red_bf2(pa + 2048, pack_bf16(acc[1][0], ce == 2 ? 1.f : acc[1][1])); red_bf2(pa + 2304, pack_bf16(acc[1][2], ce == 3 ? 1.f : acc[1][3]));
        red_bf2p4(pa + (W_DS + (wq & 1) * 256), pack_bf16(ce == 0 ? acc[0][1] : ce == 1 ? acc[0][3] : ce == 2 ? acc[1][1] : acc[1][3], 1.f), ce);
        TSF(4, 1); TSF(2, 6);
        if (wg) bar_sync(B_CV, 256);
        else if (!f0ok) mbar_wait(sb + SM_BAR + MB_F, (s + 1) & 1);
      }
      OPAQUE_R(lm); OPAQUE_R(l16);
      {
        float d[16];
        const uint32_t cv = TQ(SM_CV + ((s ^ wg) & 1) * 4096);
        TSF(9, 1);
        wg_fence();
        XR<0, 1, 0, 8, 1>::run(d, wv, xb16); XS<8, 8, 9, 0>::run(d, va16, xb16); XR<1, 2, 0, 8, 0>::run(d, wv, xb16); XS<9, 8, 10, 0>::run(d, va16, xb16);
        XR<2, 3, 0, 8, 0>::run(d, wv, xb16); XS<10, 8, 11, 0>::run(d, va16, xb16); XR<3, 4, 0, 8, 0>::run(d, wv, xb16); XS<11, 8, 12, 0>::run(d, va16, xb16);
        XR<4, 5, 0, 8, 0>::run(d, wv, xb16); XS<12, 8, 13, 0>::run(d, va16, xb16); XR<5, 6, 0, 8, 0>::run(d, wv, xb16); XS<13, 8, 14, 0>::run(d, va16, xb16);
        XR<6, 7, 0, 8, 0>::run(d, wv, xb16); XS<14, 8, 15, 0>::run(d, va16, xb16); XR<7, 8, 0, 8, 0>::run(d, wv, xb16); XS<15, 8, 16, 0>::run(d, va16, xb16);
        wg_commit(); wg_wait0();
        uint32_t q[8];
#pragma unroll
        for (int i = 0; i < 8; i++) q[i] = pack_bf16(d[2 * i], d[2 * i + 1]);
        if (wg == 0) {
          sts128(cv, q[0], q[1], q[2], q[3]); sts128(cv + 2048, q[4], q[5], q[6], q[7]);
          wg_fence(); XR<0, KB, 0, 32, 1>::run(d, w, xb16); wg_commit(); wg_wait0();
          OPAQUE_R(l16);
          DUMP(SM_CW);
          TSF(5, 1);
        } else {
          const uint4 o = lds128(cv + (r ^ 1) * 2048), k = lds128(cv + r * 2048);
          XREL(MB_XE1);
          st_async4(l16 + (rsb + SM_VR + wq * 512), u2f(addb2(r ? q[0] : q[4], o.x)), u2f(addb2(r ? q[1] : q[5], o.y)), u2f(addb2(r ? q[2] : q[6], o.z)), u2f(addb2(r ? q[3] : q[7], o.w)),
                    rsb + SM_BAR + MB_VR);
          sts128(TQ(SM_VL), addb2(r ? q[4] : q[0], k.x), addb2(r ? q[5] : q[1], k.y), addb2(r ? q[6] : q[2], k.z), addb2(r ? q[7] : q[3], k.w));
          __syncwarp();
          if (l16 == 0) mbar_arrive(sb + SM_BAR + MB_VR);
          TSF(28, 5);
        }
      }
    }
  } else {
    asm volatile("setmaxnreg.dec.sync.aligned.u32 " STR(RF_CTL) ";");
    const int g = lane >> 2, tq = lane & 3;
    if (wq == 0) {
      if (lane < 12) asm volatile("prefetch.global.L2 [%0];" :: "l"(SP.x + (size_t)(cta * 12 + lane) * 64));
      __syncwarp();
      {
        SIDES();
        const uint32_t o[6] = {w_blk(w_h1(cta), me), w_blk(w_h1(cta) ^ H1_V, me), w_blk(w_mvx(cta, 0), me ^ sm2.z), w_blk(w_mvx(cta, 1), me ^ sm2.z),
                               w_blk(w_mxa(cta, 0), me ^ sm2.z), w_blk(w_mxa(cta, 1), me ^ sm2.z)};
#pragma unroll
        for (int i = 0; i < 24; i++) stg_r4(P.win + (o[i >> 2] + (i & 3) * 512 + lane * 16), 0u, 0u, 0u, 0u);
#pragma unroll
        for (int i = 0; i < 6; i++) stg_r1(P.win + (w_ar(i >> 1) + cta * 256 + (i & 1) * W_DS + lane * 4), 0u);
        __threadfence();
        __syncwarp();
      }
      {
        const uint32_t wv = movm(*reinterpret_cast<const uint32_t*>(P.mem0 + g * DM + cta * 8 + tq * 2));
        const bool sp = lane == cnt_word(cta & 31);
        stg_r1(P.win + (w_ar(-1) + cta * 256 + lane * 4), sp ? (wv & 0xffffu) | 0x42000000u : wv);
        if (sp) stg_r1(P.win + (w_ar(-1) + ((cta & ~9) + ((cta >> 1) & 1)) * 256 + W_DS + lane * 4), (wv >> 16) | 0x42000000u);
      }
      bar_sync(B_V, 160);
      if (lane == 0) {
        fence_async_smem(); mbar_arrive_cluster_rlx(mapa(sb + SM_BAR + MB_INIT, 0)); mbar_arrive_cluster_rlx(mapa(sb + SM_BAR + MB_INIT, 1));
        mbar_wait(sb + SM_BAR + MB_INIT, 0);
        mbar_expect_tx(sb + SM_BAR + MB_F, 32768);
        mbar_expect_tx(sb + SM_BAR + MB_F + 8, 32768);
        XLOAD(1, 0); XLOAD(0, 1);
        WLOAD(4 + WSPL, 8);
      }
      __syncwarp();
#ifdef PER
      if (lane == 0) atomicMax(&g_end[5], gt32());
#endif
    }
    bar_sync(B_X2, 256);
    SIDES();
    uint32_t l16 = __shfl_sync(~0u, lane * 16, lane);
    const uint32_t me2 = me ^ sm2.z;
    const float sc = 32.f * 0.08838834764831845f * 1.4426950408889634f;
    uint32_t ls = l16 + sb;
#define PVM(o, zs, p0, p2, M1, M2, M3) do { \
        FENCE(); \
        mma4z(zs, 0x3F803F80u, 0x3F803F80u, 0x3F803F80u, 0x3F803F80u, p0.x, p0.y); \
        FENCE(); M1; \
        _Pragma("unroll") for (int t = 0; t < 4; t++) mma4z(o[t], va[2 * t].x, va[2 * t].y, va[2 * t].z, va[2 * t].w, p0.x, p0.y); \
        FENCE(); M2; \
        mma4(zs, 0x3F803F80u, 0x3F803F80u, 0x3F803F80u, 0x3F803F80u, p0.z, p0.w); \
        _Pragma("unroll") for (int t = 0; t < 2; t++) mma4(o[t], va[2 * t + 1].x, va[2 * t + 1].y, va[2 * t + 1].z, va[2 * t + 1].w, p0.z, p0.w); \
        FENCE(); M3; \
        mma_1688(zs, 0x3F803F80u, 0x3F803F80u, p2); \
        _Pragma("unroll") for (int t = 2; t < 4; t++) mma4(o[t], va[2 * t + 1].x, va[2 * t + 1].y, va[2 * t + 1].z, va[2 * t + 1].w, p0.z, p0.w); \
        mma_1688(o[0], vm[0].x, vm[0].y, p2); mma_1688(o[1], vm[0].z, vm[0].w, p2); mma_1688(o[2], vm[1].x, vm[1].y, p2); mma_1688(o[3], vm[1].z, vm[1].w, p2); } while (0)
#define PVE(o, z, dst) do { \
        const float i0 = rcpf(z[0]), i1 = rcpf(z[1]); \
        _Pragma("unroll") for (int u = 0; u < 2; u++) \
          stsm4t((dst) + u * 1024, pack_bf16(o[2 * u][0] * i0, o[2 * u][1] * i1), pack_bf16(o[2 * u][2] * i0, o[2 * u][3] * i1), \
                 pack_bf16(o[2 * u + 1][0] * i0, o[2 * u + 1][1] * i1), pack_bf16(o[2 * u + 1][2] * i0, o[2 * u + 1][3] * i1)); } while (0)
    const uint32_t lq = (l16 ^ ((l16 >> 1) & 64u)) + sb, l12 = (l16 >> 2) * 3;
#define M3PTR(sl) \
            const uint32_t tf = me ^ 1 ^ r, m3i = w_ar(sl) + (wq & 1) * 16384 + (l16 & 0x70u) + ((l16 & 0x180u) << 1); \
            const unsigned char* p0f = P.win + (m3i + r * 8192 + tf * 4096); const unsigned char* p0n = P.win + (m3i + r * 8192 + (tf ^ 1) * 4096); \
            const unsigned char* p1f = P.win + (m3i + (r ^ 1) * 8192 + (tf ^ 1) * 4096); const unsigned char* p1n = P.win + (m3i + (r ^ 1) * 8192 + tf * 4096); \
            const unsigned char* pd = P.win + (w_ar(sl) + (wq & 1) * 16384 + (((l16 >> 7) ^ r) & 1u) * 8192 + ((l16 & 64u) * 4 + (l16 & 48u) * 2 + (l16 & 16u)) * 16 + W_DS + (l16 & 0x70u)); \
            uint32_t mf = ls + SM_MEM + (wq & 1) * 8192 + tf * 2048, mn = ls + SM_MEM + (wq & 1) * 8192 + (tf ^ 1) * 2048, nr = l16 < 256u ? 1u + (((l16 >> 6) ^ (l16 >> 7) ^ tf) & 1u) : 0u; \
            OPAQUE_L(p0f); OPAQUE_L(p0n); OPAQUE_L(p1f); OPAQUE_L(p1n); OPAQUE_L(pd); OPAQUE_R(mf); OPAQUE_R(mn); OPAQUE_R(nr); FENCE()
#define M3REQ() \
            _Pragma("unroll") for (int i = 0; i < 4; i++) { cp16(mn + 4096 + i * 512, p1f + i * 1024); cp16(mf + i * 512, p0f + i * 1024); } \
            cp16p(ls + SM_RD + (wq & 1) * 256, pd, nr & 1u); \
            _Pragma("unroll") for (int i = 0; i < 4; i++) { cp16(mf + 4096 + i * 512, p1n + i * 1024); cp16(mn + i * 512, p0n + i * 1024); } \
            cp16p(ls + SM_RD + (wq & 1) * 256, pd, nr & 2u)
    if (wq >= 2) { M3PTR(-1); M3REQ(); }
    if (wq == 0) {
      bar_sync(B_P, 160);
      if (l16 == 0) {
        fence_async_smem();
        mbar_expect_tx(sb + SM_BAR + MB_WO, 65536);
        for (int i = 0; i < 8; i++) tma_load_2d(sb + SM_WOS + i * 8192, &tmw, j * 256 + ((i >> 1) ^ (2 * sw)) * 64, h * DH + (i & 1) * 64, sb + SM_BAR + MB_WO);
      }
      __syncwarp();
    }
#define ETA(k, first) ETAT(gt32() + (k), first)
#define ETAT(tm, first) do { unsigned char* pt = P.win + (w_ar(s) + (W_DS + 256) + (cta >> 5) * 8192 + ((cta >> 4) & 1) * 2048 + (l16 & 16u) * 256); \
          asm volatile("{\n.reg .pred q;\nsetp.lt.u32 q, %2, 32;\n@q red.relaxed.gpu.global.max.u32 [%0+4], %1;\n}" :: "l"(pt), "r"(tm), "r"(l16) : "memory"); \
          if (first) asm volatile("{\n.reg .pred q;\nsetp.lt.u32 q, %1, 32;\n@q red.relaxed.gpu.global.add.u32 [%0], 1;\n}" :: "l"(pt), "r"(l16) : "memory"); } while (0)
    if (wq == 1) {
      const uint32_t xin = w_blk(w_mxa(cta, 0), me2) + l16;
      const uint32_t lsq = sb + ((l16 & 0x70u) | ((l16 & 0x80u) << 1) | ((l16 & 0x100u) >> 1));
      mbar_wait(sb + SM_BAR + MB_MEM, 0); mbar_wait(sb + SM_BAR + MB_MEM + 8, 0);
      for (int s = 0; s < NSEG; s++) {
        const uint32_t t2 = ((s >> 1) & 1) ^ 1;
        mbar_wait(sb + SM_BAR + MB_XF, s & 1);
        {
        uint4 kx[4], qx[4];
#pragma unroll
        for (int i = 0; i < 4; i++) { kx[i] = ldsm4(ls + (SM_XF + (4 + i) * 512)); qx[i] = ldsm4(lsq + (SM_XF + i * 512)); }
        const uint32_t db = w_blk(w_mxa(h * 4, s), me2) + l16 - 512;
        {
          float S[2][4][4];
          if (XG == 2 && s > 0) bar_arrive(B_O2, 224);
          FENCE();
#pragma unroll
          for (int mt = 0; mt < 2; mt++) {
            const uint4 q0 = qx[mt];
            mma4z(S[mt][0], q0.x, q0.y, q0.z, q0.w, kx[0].x, kx[0].y); mma4z(S[mt][1], q0.x, q0.y, q0.z, q0.w, kx[0].z, kx[0].w);
            mma4z(S[mt][2], q0.x, q0.y, q0.z, q0.w, kx[1].x, kx[1].y); mma4z(S[mt][3], q0.x, q0.y, q0.z, q0.w, kx[1].z, kx[1].w);
          }
#pragma unroll
          for (int mt = 0; mt < 2; mt++) {
            const uint4 q1 = qx[2 + mt];
            mma4(S[mt][0], q1.x, q1.y, q1.z, q1.w, kx[2].x, kx[2].y); mma4(S[mt][1], q1.x, q1.y, q1.z, q1.w, kx[2].z, kx[2].w);
            mma4(S[mt][2], q1.x, q1.y, q1.z, q1.w, kx[3].x, kx[3].y); mma4(S[mt][3], q1.x, q1.y, q1.z, q1.w, kx[3].z, kx[3].w);
          }
          FENCE();
          if (XG == 1 && s > 0) bar_arrive(B_O2, 224);
          if (XSD && s > 0) spin(XSD);
          FENCE();
#pragma unroll
          for (int u = 0; u < 4; u++) {
            const int mt = u >> 1, c = 2 * (u & 1);
            const uint32_t m0 = tagw(pack_f16(S[mt][0][c], S[mt][0][c + 1]), t2), m1 = pack_f16(S[mt][1][c], S[mt][1][c + 1]),
                           m2 = pack_f16(S[mt][2][c], S[mt][2][c + 1]), m3 = pack_f16(S[mt][3][c], S[mt][3][c + 1]);
            const int e = u ^ j;
            if (e) stg_r4(P.win + (db + mt * 16384 + (u & 1) * 2048 + e * 512), m0, m1, m2, m3);
            else sts128(ls + SM_XS, m0, m1, m2, m3);
          }
        }
        TS(15);
        float sx[10];
        const unsigned char* pa = P.win + (xin + ((s & 1) << 20));
        uint4 xv[3];
        if (s > 0) spin(DLY_XD);
#pragma unroll
        for (int i = 0; i < 3; i++) xv[i] = ldg_r4(pa + i * 512);
        FENCE();
        int n = 0; float mx;
        auto xsum = [&]() {
#pragma unroll 1
        while (__any_sync(~0u, (x3(xv[0].x, xv[1].x, t2) | (xv[2].x ^ t2)) & 1u) && ++n < SPIN_LIMIT) {
#pragma unroll
          for (int i = 0; i < 3; i++) xv[i] = ldg_r4(pa + i * 512);
        }
        {
          const uint4 v3 = lds128(ls + SM_XS);
          sum_h4(sx[2], sx[3], xv[0].x, xv[1].x, xv[2].x, v3.x); sum_h4(sx[4], sx[5], xv[0].y, xv[1].y, xv[2].y, v3.y);
          sum_h4(sx[6], sx[7], xv[0].z, xv[1].z, xv[2].z, v3.z); sum_h4(sx[8], sx[9], xv[0].w, xv[1].w, xv[2].w, v3.w);
          const int row = 8 * j + g - 2 * tq;
#pragma unroll
          for (int i = 0; i < 8; i++) if ((i >> 1) * 8 + (i & 1) > row) sx[2 + i] = -INFINITY;
        }
        mx = fmaxf(fmaxf(fmaxf(sx[2], sx[3]), fmaxf(sx[4], sx[5])), fmaxf(fmaxf(sx[6], sx[7]), fmaxf(sx[8], sx[9])));
        };
        if (!Z0 || s > 0) xsum();
        else {
#pragma unroll
          for (int i = 2; i < 10; i++) sx[i] = 0.f;
          mx = 0.f;
        }
        sts32(ls - l12 + SM_XS + 512, f2u(mx));
        {
          if (l16 == 0) mbar_expect_tx(sb + SM_BAR + MB_VR, 2048);
          unsigned char* d = P.win + (w_blk(w_mvx(cta, s), me2) + l16);
          OPAQUE_L(d); FENCE();
          mbar_wait(sb + SM_BAR + MB_VR, s & 1);
#pragma unroll
          for (int t = 0; t < 4; t++) {
            const uint4 a0 = lds128(ls + (SM_VL + t * 512)), a1 = lds128(ls + (SM_VR + t * 512));
            stg_r4(d + t * 512, tagw(addb2(a0.x, a1.x), t2), addb2(a0.y, a1.y), addb2(a0.z, a1.z), addb2(a0.w, a1.w));
          }
          TS(23);
        }
        unsigned char* pm = P.win + (db + 2048 + j * 128 - l12);
        const unsigned char* py = pa + 1536 - l12;
        OPAQUE_L(pm); OPAQUE_L(py);
        if (s > 0) bar_sync(B_PXF, 96);
        FENCE();
        bar_sync(B_QK1, 288);
        uint32_t kb[2][2];
#pragma unroll
        for (int t = 0; t < 2; t++) {
          const float4 u = lds128f(lq + (SM_QKP + (2 + t) * 512)), v4 = lds128f(lq + (SM_QKP + 2048 + (2 + t) * 512));
          kb[t][0] = pack_bf16(u.x + v4.x, u.y + v4.y); kb[t][1] = pack_bf16(u.z + v4.z, u.w + v4.w);
        }
        float S[2][4];
#pragma unroll
        for (int mt = 0; mt < 2; mt++) mma4z(S[mt], qx[mt].x, qx[mt].y, qx[mt].z, qx[mt].w, kb[0][0], kb[0][1]);
#pragma unroll
        for (int mt = 0; mt < 2; mt++) mma4(S[mt], qx[2 + mt].x, qx[2 + mt].y, qx[2 + mt].z, qx[2 + mt].w, kb[1][0], kb[1][1]);
        PT(14, s == 0 && l16 == 0);
        if (!Z1 && s == 0) mbar_wait(sb + SM_BAR + MB_WO, 0);
        PT(15, s == 0 && l16 == 0);
        if (s < NSEG - 1) bar_arrive(B_PUB, 320);
        FENCE();
#pragma unroll
        for (int u = 0; u < 4; u++) stg_r1(pm + (u >> 1) * 16384 + (u & 1) * 2048, tagw(pack_f16(S[u >> 1][2 * (u & 1)], S[u >> 1][2 * (u & 1) + 1]), t2));
        TS(30);
        FENCE();
        if (Z0 && s == 0) xsum();
        spin(DLY_XL);
        uint32_t xy[4];
#pragma unroll
        for (int i = 0; i < 4; i++) xy[i] = ldg_r1(py + i * 128);
        FENCE();

        n = 0;
#pragma unroll 1
        while (__any_sync(~0u, (x3(xy[0], xy[1], t2) | x3(xy[2], xy[3], t2)) & 1u) && ++n < SPIN_LIMIT) {
#pragma unroll
          for (int i = 0; i < 4; i++) xy[i] = ldg_r1(py + i * 128);
        }
        sum_h4(sx[0], sx[1], xy[0], xy[1], xy[2], xy[3]);
        mx = fmaxf(mx, fmaxf(sx[0], sx[1]));
        mx = fmaxf(fmaxf(mx, __shfl_xor_sync(~0u, mx, 1)), fmaxf(__shfl_xor_sync(~0u, mx, 2), __shfl_xor_sync(~0u, mx, 3)));
#pragma unroll
        for (int i = 0; i < 10; i++) sx[i] = ex2(fmaf(sx[i], sc, -sc * mx));
        sts128(ls + SM_PX, pack_bf16(sx[2], sx[3]), pack_bf16(sx[4], sx[5]), pack_bf16(sx[6], sx[7]), pack_bf16(sx[8], sx[9]));
        sts32(ls - l12 + SM_PX + 512, pack_bf16(sx[0], sx[1]));
        bar_arrive(B_PX, 96);
        TS(1);
        }
      }
    } else {
      const uint32_t ho = (wq & 1) * 512 + l16, hv = wq == 0 ? 0u : H1_V;
      uint32_t ow = w_blk(w_h1(cta) ^ hv, me) + ho, or0 = w_blk(w_h1(cta ^ 1) ^ hv, me) + ho, or1 = w_blk(w_h1((cta ^ 2) & ~1) ^ hv, me) + ho;
#define PTRS() OPAQUE_R(ow); OPAQUE_R(or0); OPAQUE_R(or1); \
      unsigned char* pw0 = P.win + ow; const unsigned char* pr0 = P.win + or0; const unsigned char* pr1 = P.win + or1; \
      OPAQUE_L(pw0); OPAQUE_L(pr0); OPAQUE_L(pr1); FENCE()
      if (wq == 0) {
        const uint32_t xcnt = me ? NCTA - nlo : nlo, xrank = (me ? cta - nlo : cta) + lane * xcnt;
        int kd = DLY_K;
        mbar_wait(sb + SM_BAR + MB_XE1, 0);
        if (l16 == 0) { mbar_expect_tx(sb + SM_BAR + MB_F + 8, 32768); XLOAD(1, 1); }
        __syncwarp();
        for (int s = 0; s < NSEG - 1; s++) {
          const uint32_t tg = (s & 1) ^ 1;
          mbar_wait(sb + SM_BAR + MB_XF, s & 1);
          uint4 xf[4];
#pragma unroll
          for (int i = 0; i < 4; i++) xf[i] = ldsm4(ls + (SM_XF + (4 + i) * 512));
          FENCE();
          if (s > 0) {
            mbar_wait(sb + SM_BAR + MB_XE1, s & 1);
            if (l16 == 0) mbar_expect_tx(sb + SM_BAR + MB_F + 8, 32768);
            mbar_wait(sb + SM_BAR + MB_MEM, s & 1); mbar_wait(sb + SM_BAR + MB_MEM + 8, s & 1);
            if (l16 == 0) XLOAD(1, s + 1);
            __syncwarp();
          }
          kd = lds32(sb + SM_Z + 40) == (uint32_t)s && s ? min(kd + KU, DLY_K + 256) : max(kd - KD, DLY_K);
          kd = __shfl_sync(~0u, kd, l16 >> 4);
#ifdef PER
          if (l16 == 0) { g_per[cta][max(s - 1, 0)] = gt32(); g_pclk[cta][max(s - 1, 0)] = clk32(); g_pk[cta][max(s - 1, 0)] = kd - DLY_K; }
#endif
          PTRS();
          unsigned char* pw1 = pw0 + 512 - l12; OPAQUE_L(pw1);
          bar_sync(B_QK, 288);
          float4 u[4], v4[4];
#pragma unroll
          for (int t = 0; t < 4; t++) { u[t] = lds128f(lq + (SM_QKP + t * 512)); v4[t] = lds128f(lq + (SM_QKP + 2048 + t * 512)); }
          FENCE();
          uint32_t f[4][2], m[5];
#pragma unroll
          for (int t = 0; t < 2; t++) { f[t][0] = pack_bf16(u[t].x + v4[t].x, u[t].y + v4[t].y); f[t][1] = pack_bf16(u[t].z + v4[t].z, u[t].w + v4[t].w); }
          float S[5][4], T[5][4];
          mma4z(S[1], f[0][0], f[1][0], f[0][1], f[1][1], xf[0].x, xf[0].y); mma4z(T[1], f[0][0], f[1][0], f[0][1], f[1][1], xf[2].x, xf[2].y);
          mma4z(S[2], f[0][0], f[1][0], f[0][1], f[1][1], xf[0].z, xf[0].w); mma4z(T[2], f[0][0], f[1][0], f[0][1], f[1][1], xf[2].z, xf[2].w);
          FENCE();
#pragma unroll
          for (int t = 2; t < 4; t++) { f[t][0] = packv(u[t].x, v4[t].x, u[t].y, v4[t].y); f[t][1] = packv(u[t].z, v4[t].z, u[t].w, v4[t].w); }
          mma4z(S[3], f[0][0], f[1][0], f[0][1], f[1][1], xf[1].x, xf[1].y); mma4z(T[3], f[0][0], f[1][0], f[0][1], f[1][1], xf[3].x, xf[3].y);
          mma4z(S[4], f[0][0], f[1][0], f[0][1], f[1][1], xf[1].z, xf[1].w); mma4z(T[4], f[0][0], f[1][0], f[0][1], f[1][1], xf[3].z, xf[3].w);
          FENCE();
          mma4z(S[0], f[0][0], f[1][0], f[0][1], f[1][1], f[2][0], f[2][1]); mma4z(T[0], f[0][0], f[1][0], f[0][1], f[1][1], f[3][0], f[3][1]);
          bar_arrive(B_PUB, 320);
          FENCE();
#if SO
#pragma unroll
          for (int i = 1; i < 5; i++) m[i] = packh(S[i][0], T[i][2], S[i][1], T[i][3]);
          m[1] = tagw(m[1], tg);
          stg_r4(pw0, m[1], m[2], m[3], m[4]);
          FENCE();
          m[0] = tagw(packh(S[0][0], T[0][2], S[0][1], T[0][3]), tg);
          stg_r1(pw1, m[0]);
#else
#pragma unroll
          for (int i = 1; i < 5; i++) m[i] = pack_f16(S[i][0] + T[i][2], S[i][1] + T[i][3]);
          stg_r4(pw0, tagw(m[1], tg), m[2], m[3], m[4]);
          m[0] = pack_f16(S[0][0] + T[0][2], S[0][1] + T[0][3]);
          stg_r1(pw1, tagw(m[0], tg));
#endif
          TS(6); PT(11, s == 0 && l16 == 0);
          FENCE();
          const uint32_t ts = clk32();
          uint32_t te = gt32() + kd;
          const unsigned char* py0 = pr0 + 512 - l12; const unsigned char* py1 = pr1 + 512 - l12;
          OPAQUE_L(py0); OPAQUE_L(py1);
          unsigned char* pt = P.win + (w_ar(s) + (W_DS + 256) + (cta >> 5) * 8192 + ((cta >> 4) & 1) * 2048 + (l16 & 16u) * 256);
          OPAQUE_L(pt);
          if (l16 == 0) mbar_expect_tx(sb + SM_BAR + MB_F, s < NSEG - 2 ? 32768 : 0);
          FENCE();
          while (clk32() - ts < (uint32_t)DLY_S) {}
          {
            float sx[10]; uint32_t x, x1, x2, x3_; int n = 0; bool bad;
#pragma unroll 1
            do {
              uint4 v[3]; uint32_t y[3], t[5];
              v[0] = ldg_r4(pr0); v[1] = ldg_r4(pr1); v[2] = ldg_r4(pr1 + 2048);
              y[0] = ldg_r1(py0); y[1] = ldg_r1(py1); y[2] = ldg_r1(py1 + 2048);
              if (n) te = gt32() + DLY_KS;
              eta2(pt, te, n == 0, l16);
              n++;
              FENCE();
#define Q3(o, a, b, c) hadd2(hadd2(o, a), hadd2(b, c))
              t[1] = Q3(m[1], v[0].x, v[1].x, v[2].x); t[2] = Q3(m[2], v[0].y, v[1].y, v[2].y); t[3] = Q3(m[3], v[0].z, v[1].z, v[2].z); t[4] = Q3(m[4], v[0].w, v[1].w, v[2].w);
              t[0] = Q3(m[0], y[0], y[1], y[2]);
              bad = __any_sync(~0u, or3(x3(v[0].x, v[1].x, tg), x3(v[2].x, y[0], tg), x3(y[1], y[2], tg)) & (n < SPIN_LIMIT ? 1u : 0u));
              x = hmax2(hmax2(hmax2(t[1], t[2]), hmax2(t[3], t[4])), t[0]);
              const float2 xm = __half22float2(*reinterpret_cast<__half2*>(&x));
              x = f2u(fmaxf(xm.x, xm.y) * -sc);
              x1 = shfl_x(x, 1); x2 = shfl_x(x, 2); x3_ = shfl_x(x, 3);
              FENCE();
#if OS
#pragma unroll
              for (int i = 1; i < 6; i++) {
                h2f(sx[2 * (i % 5)], sx[2 * (i % 5) + 1], t[i % 5]);
                sx[2 * (i % 5)] = ex2v(sx[2 * (i % 5)], sc, u2f(x)); sx[2 * (i % 5) + 1] = ex2v(sx[2 * (i % 5) + 1], sc, u2f(x));
              }
              FENCE();
            } while (bad);
            const float cr = ex2(fminf(fminf(u2f(x), u2f(x1)), fminf(u2f(x2), u2f(x3_))) - u2f(x));
#pragma unroll
            for (int i = 1; i < 6; i++) m[i % 5] = pack_bf16(sx[2 * (i % 5)] * cr, sx[2 * (i % 5) + 1] * cr);
#else
#pragma unroll
              for (int i = 1; i < 6; i++) h2f(sx[2 * (i % 5)], sx[2 * (i % 5) + 1], t[i % 5]);
              FENCE();
            } while (bad);
            const float mx = fminf(fminf(u2f(x), u2f(x1)), fminf(u2f(x2), u2f(x3_)));
#pragma unroll
            for (int i = 2; i < 12; i++) sx[i % 10] = ex2v(sx[i % 10], sc, mx);
#pragma unroll
            for (int i = 1; i < 6; i++) m[i % 5] = pack_bf16(sx[2 * (i % 5)], sx[2 * (i % 5) + 1]);
#endif
            sts128(ls + SM_PF, m[1], m[2], m[3], m[4]);
            sts32(ls - l12 + SM_PF + 512, m[0]);
            TV(19, n - 1);
          }
          TS(12);
          bar_sync(B_P, 96);
          PT(12, s == 0 && l16 == 0);
          OPAQUE_R(l16);
          {
            const unsigned char* pe = P.win + w_blk(w_ar(s) + (W_DS + 256) + (l16 & 0x60u) * 256 + (l16 & 16u) * 128, me);
            const uint32_t tp = gt32() + DLY_M3;
            if (s < NSEG - 2) F0LOAD();
            ETAT(tp, 0);
            uint32_t tg0; int n = 0;
#pragma unroll 1
            for (;;) {
              const uint2 e = ldg_r2(pe);
              tg0 = __reduce_max_sync(~0u, e.y);
              if (tg0 - tp >= 4096u) tg0 = tp;
              if ((!__any_sync(~0u, e.x != 16u) && (int)(tg0 - gt32()) < DLY_RR) || ++n >= SPIN_LIMIT) break;
            }
            sts32(sb + SM_Z + 32, tg0);
            TV(16, tg0); TV(7, kd - DLY_K);
            bar_arrive(B_GO, 96);
          }
          if (XPF && s + XPF < NSEG) {
            for (uint32_t i = xrank; i < 512; i += 32 * xcnt)
              asm volatile("prefetch.global.L2 [%0];" :: "l"(SP.x + (size_t)(s + XPF) * (SEG * DM) + i * 64));
            __syncwarp();
          }
          stg_2(P.win + (w_ar(s + 2) + cta * 256 + (l16 >> 8) * W_DS + ((l16 >> 1) & 127u)), 0u, 0u);
        }
        bar_sync(B_QK, 288);
      } else {
        const int mt = wq - 2;
        const uint32_t lt = ls + mt * 1024;
        const uint32_t vi0 = w_blk(w_mvx(h * 4, 0), me2) + mt * 1024;
        const int m3d = r ? -8192 : 8192;
#ifdef PROF
        const uint32_t epoch = gt32(); TST(-1, 30 + mt, l16, epoch);
#endif
        float ox[4][4], zx[4];
#pragma unroll
        for (int i = 0; i < 16; i++) ox[i >> 2][i & 3] = zx[i & 3] = 1.f;
        for (int s = 0;; s++) {
          const uint32_t tg = (s & 1) ^ 1, t2 = ((s >> 1) & 1) ^ 1;
          {
            OPAQUE_R(l16);
            const uint32_t m3i = (mt * 2 + r) * 8192 + (l16 & 0x70u) + ((l16 & 0x180u) << 1);
            const uint32_t m3j = (mt * 2 + (r ^ (l16 >> 7 & 1))) * 8192 + ((l16 & 64u) * 4 + (l16 & 48u) * 2 + (l16 & 16u)) * 16 + W_DS + (l16 & 0x70u);
            uint32_t m3c = sb + SM_MEM + mt * 8192 + cnt_line(l16 >> 4) * 128 + (l16 >> 2);
            const unsigned char* p3 = P.win + (m3i + w_ar(s - 1)); const unsigned char* pd = P.win + (m3j + w_ar(s - 1));
            OPAQUE_L(pd); OPAQUE_R(m3c);
#define XEPI() do { \
              const float i0 = rcpf(zx[0]), i1 = rcpf(zx[1]); \
              unsigned char* o = reinterpret_cast<unsigned char*>(g_ox + (size_t)((s - 1) * SEG + 8 * j) * (NH * DH) + h * DH + mt * 64) + ((l16 & 48u) * (NH * DH / 4) + ((l16 >> 2) & 0x70u)); \
              stg_4(o, make_uint4(pack_bf16(ox[0][0] * i0, ox[0][2] * i0), pack_bf16(ox[1][0] * i0, ox[1][2] * i0), pack_bf16(ox[2][0] * i0, ox[2][2] * i0), pack_bf16(ox[3][0] * i0, ox[3][2] * i0))); \
              stg_4(o + NH * DH * 2, make_uint4(pack_bf16(ox[0][1] * i1, ox[0][3] * i1), pack_bf16(ox[1][1] * i1, ox[1][3] * i1), pack_bf16(ox[2][1] * i1, ox[2][3] * i1), pack_bf16(ox[3][1] * i1, ox[3][3] * i1))); \
              TST(s - 1, 18, l16 | mt, TCLK()); } while (0)
            if (s > 0) XEPI();
            if (s == NSEG) break;
            if (s > 0) {
              M3PTR(s - 1);
              bar_sync(B_GO, 96);
              const uint32_t tg0 = lds32(sb + SM_Z + 32);
              while (tg0 - gt32() - 1u < 8192u) {}
              M3REQ();
            }
            FENCE();
            const int n = m3_check(sb, p3, pd, m3d, l16, m3c, mt, s);
            FENCE();
            TST(s, mt ? 21 : 0, l16, TCLK());
            TST(s, mt ? 22 : 17, l16, n);
            PT(6 + s, s < 5 && (l16 | mt) == 0);
          }
          uint4 va[8], vm[2], p0, q0; uint32_t p2, q2;
          const unsigned char* a0 = P.win + (vi0 + ((s & 1) << 20) + l16);
#define VALD() _Pragma("unroll") for (int i = 0; i < 4; i++) { va[i] = ldg_r4(a0 + (i >> 1) * 512 + (i & 1) * 2048); va[4 + i] = ldg_r4(a0 + 16384 + (i >> 1) * 512 + (i & 1) * 2048); }
          spin(DLY_WO);
          VALD();
          {
          PTRS();
          bar_sync(B_V, 320);
            const float4 u0 = lds128f(lt + SM_VP), w0 = lds128f(lt + SM_VP + 2048), u1 = lds128f(lt + SM_VP + 512), w1 = lds128f(lt + SM_VP + 2560);
            const uint32_t m0 = tagw(pack_bf16(u0.x + w0.x, u0.y + w0.y), tg), m1 = pack_bf16(u0.z + w0.z, u0.w + w0.w),
                           m2 = pack_bf16(u1.x + w1.x, u1.y + w1.y), m3 = pack_bf16(u1.z + w1.z, u1.w + w1.w);
            stg_r4(pw0, m0, m1, m2, m3);
            if (wq == 2) TS(10);
            FENCE();
            const uint32_t tv = clk32();
            while (clk32() - tv < (uint32_t)DLY_V) {}
            uint4 v[3]; int n = 0; uint32_t bada = 0;
#pragma unroll 1
            do {
              v[0] = ldg_r4(pr0); v[1] = ldg_r4(pr1); v[2] = ldg_r4(pr1 + 2048);
              if (n) {
                TST(s, __any_sync(~0u, bada & 1u) ? 26 : 24, l16, epoch);
                if (__any_sync(~0u, bada & 1u)) { VALD(); }
                if (s < NSEG - 1) ETA(DLY_KS - 192, 0);
              }
              n++;
              FENCE();
              bada = or3(x3(va[0].x, va[1].x, t2), x3(va[2].x, va[3].x, t2), x3(va[4].x, va[5].x, t2)) | x3(va[6].x, va[7].x, t2);
            } while (__any_sync(~0u, or3(bada, x3(v[0].x, v[1].x, tg), v[2].x ^ tg) & 1u) && n < SPIN_LIMIT);
            const uint4 A = make_uint4(addb2(m0, v[0].x), addb2(m1, v[0].y), addb2(m2, v[0].z), addb2(m3, v[0].w));
            const uint4 B = make_uint4(addb2(v[1].x, v[2].x), addb2(v[1].y, v[2].y), addb2(v[1].z, v[2].z), addb2(v[1].w, v[2].w));
            vm[0] = p ? B : A; vm[1] = p ? A : B;
            TST(s, 11, l16 | mt, TCLK()); TST(s, 29, l16 | (mt ^ 1), TCLK());
          }
          FENCE();
          if (s < NSEG - 1) {
          bar_sync(B_P, 96);
          p0 = lds128(ls + SM_PF); p2 = lds32(ls - l12 + SM_PF + 512);
          float o[4][4], z[4];
          PVM(o, z, p0, p2, , , );
          PVE(o, z, ls + (SM_OF + mt * 512));
          bar_arrive(B_O, 192);
          }
          FENCE();
          TST(s, 8, l16 | mt, TCLK());
          bar_sync(B_PX, 96);
          q0 = lds128(ls + SM_PX); q2 = lds32(ls - l12 + SM_PX + 512);
#define O2A(k) if (O2P == k) { if (s < NSEG - 1) bar_arrive(B_O2, XG ? 224 : 192); FENCE(); }
          O2A(0);
          PVM(ox, zx, q0, q2, O2A(1), O2A(2), O2A(3));
          O2A(4);
          FENCE();
          if (s < NSEG - 1) bar_arrive(B_PXF, 96);
        }
      }
    }
  }
  asm volatile("barrier.cluster.arrive.relaxed.aligned;\nbarrier.cluster.wait.aligned;" ::: "memory");
#ifdef PER
  if (threadIdx.x == 0) atomicMax(&g_end[0], gt32());
#endif
}
#ifndef PW
#define PW 2
#endif
#ifndef G2_PD
#define G2_PD 300
#endif
#ifndef G2_HD
#define G2_HD 8000
#endif
#ifndef G2_B
#define G2_B 4
#endif
#ifndef G2_ST
#define G2_ST 6
#endif
#define G2_TB (G2_ST * 32768 + 1024)
#define G2_SMEM (G2_TB + 32768)
template <int AOFF, int BOFF>
static __device__ __forceinline__ void wgmma_n128_ta(float (&d)[64], uint32_t a16, uint32_t b16) {
  asm volatile(
      "{\n.reg .b32 t, u;\n.reg .b64 da, db;\nadd.u32 t, %64, %66;\nmov.b64 da, {t, %68};\nadd.u32 u, %65, %67;\nmov.b64 db, {u, %68};\n"
      "wgmma.mma_async.sync.aligned.m64n128k16.f32.bf16.bf16 "
      "{%0,%1,%2,%3,%4,%5,%6,%7,%8,%9,%10,%11,%12,%13,%14,%15,%16,%17,%18,%19,%20,%21,%22,%23,%24,%25,%26,%27,%28,%29,%30,%31,"
      "%32,%33,%34,%35,%36,%37,%38,%39,%40,%41,%42,%43,%44,%45,%46,%47,%48,%49,%50,%51,%52,%53,%54,%55,%56,%57,%58,%59,%60,%61,%62,%63}, "
      "da, db, 1, 1, 1, 1, 0;\n}"
      : "+f"(d[0]), "+f"(d[1]), "+f"(d[2]), "+f"(d[3]), "+f"(d[4]), "+f"(d[5]), "+f"(d[6]), "+f"(d[7]), "+f"(d[8]), "+f"(d[9]), "+f"(d[10]), "+f"(d[11]),
        "+f"(d[12]), "+f"(d[13]), "+f"(d[14]), "+f"(d[15]), "+f"(d[16]), "+f"(d[17]), "+f"(d[18]), "+f"(d[19]), "+f"(d[20]), "+f"(d[21]), "+f"(d[22]), "+f"(d[23]),
        "+f"(d[24]), "+f"(d[25]), "+f"(d[26]), "+f"(d[27]), "+f"(d[28]), "+f"(d[29]), "+f"(d[30]), "+f"(d[31]), "+f"(d[32]), "+f"(d[33]), "+f"(d[34]), "+f"(d[35]),
        "+f"(d[36]), "+f"(d[37]), "+f"(d[38]), "+f"(d[39]), "+f"(d[40]), "+f"(d[41]), "+f"(d[42]), "+f"(d[43]), "+f"(d[44]), "+f"(d[45]), "+f"(d[46]), "+f"(d[47]),
        "+f"(d[48]), "+f"(d[49]), "+f"(d[50]), "+f"(d[51]), "+f"(d[52]), "+f"(d[53]), "+f"(d[54]), "+f"(d[55]), "+f"(d[56]), "+f"(d[57]), "+f"(d[58]), "+f"(d[59]),
        "+f"(d[60]), "+f"(d[61]), "+f"(d[62]), "+f"(d[63])
      : "r"(a16), "r"(b16), "n"(AOFF >> 4), "n"(BOFF >> 4), "n"(DESC_HI(1024)));
}
__global__ void __cluster_dims__(2, 1, 1) __launch_bounds__(384, 1)
gemm2_kernel(const __grid_constant__ CUtensorMap tmo, const __grid_constant__ CUtensorMap tmw, const bf16* __restrict__ x, bf16* __restrict__ out, unsigned char* win) {
  extern __shared__ __align__(1024) unsigned char smem[];
  const uint32_t sb = smem_u32(smem), bars = sb + G2_ST * 32768;
  const int tid = threadIdx.x, lane = tid & 31, warp = __shfl_sync(~0u, tid >> 5, 0);
  const int r = blockIdx.x & 1, pp = blockIdx.x >> 1;
  const int n0 = (((pp >> G2_B) & 3) * 2 + r) * 128, m0 = ((pp & ((1 << G2_B) - 1)) | ((pp >> (G2_B + 2)) << G2_B)) * 128;
  if (tid == 0) {
    for (int i = 0; i < G2_ST; i++) { mbar_init(bars + i * 8, 1); mbar_init(bars + 64 + i * 8, 4); }
    asm volatile("fence.mbarrier_init.release.cluster;" ::: "memory");
  }
  if (tid == 32) { asm volatile("prefetch.tensormap [%0];" :: "l"(&tmw) : "memory"); asm volatile("prefetch.tensormap [%0];" :: "l"(&tmo) : "memory"); }
  __syncthreads();
  asm volatile("barrier.cluster.arrive.relaxed.aligned;" ::: "memory");
#define LW(kt, st) asm volatile("cp.async.bulk.tensor.5d.shared::cluster.global.mbarrier::complete_tx::bytes [%0], [%1, {%3, %4, %3, %3, %5}], [%2];" \
                     :: "r"(sb + (st) * 32768), "l"(&tmw), "r"(bars + (st) * 8), "r"(0), "r"(((kt) >> 1) * 16 + ((kt) & 1) * 4), "r"(n0 >> 6) : "memory")
#define LO(kt, st) asm volatile("cp.async.bulk.tensor.2d.shared::cluster.global.mbarrier::complete_tx::bytes.multicast::cluster [%0], [%1, {%3, %4}], [%2], %5;" \
                     :: "r"(sb + (st) * 32768 + 16384 + r * 8192), "l"(&tmo), "r"(bars + (st) * 8), "r"((kt) * 64), "r"(m0 + r * 64), "h"((uint16_t)3) : "memory")
  if (tid == 256) for (int kt = 0; kt < G2_ST; kt++) { mbar_expect_tx(bars + kt * 8, 32768); if (kt < PW) LW(kt, kt); }
  __syncwarp();
  asm volatile("barrier.cluster.wait.acquire.aligned;" ::: "memory");
  if (warp == 8) {
    if (lane == 0) {
      asm volatile("griddepcontrol.wait;" ::: "memory");
      for (int kt = 0; kt < G2_ST; kt++) { LO(kt, kt); if (kt >= PW) LW(kt, kt); spin(G2_PD); }
#pragma unroll 1
      for (int kt = G2_ST, st = 0, ph = 0; kt < 64; kt++) {
        mbar_wait(bars + 64 + st * 8, ph);
        mbar_expect_tx(bars + st * 8, 32768);
        LO(kt, st); LW(kt, st);
        if (++st == G2_ST) { st = 0; ph ^= 1; }
      }
    }
  } else if (warp > 8) {
    const int t = tid - 288, ch = t & 15;
    asm volatile("griddepcontrol.wait;" ::: "memory");
#ifdef PER
    if (t == 0) atomicMax(&g_end[3], gt32());
#endif
    spin(G2_HD);
    int idx[8];
#pragma unroll
    for (int c = 0; c < 8; c++) idx[c] = g_idx[c];
    const int gi = blockIdx.x * 96 + t;
    if (gi < 67) g_side[gi * 32] = 0u;
    if (gi == 0) g_sbar = 0u;
#pragma unroll 4
    for (int row = t >> 4; row < 128; row += 6) {
      const int tok = m0 + row;
      const uint4 xv = *reinterpret_cast<const uint4*>(x + (size_t)tok * DM + n0 + ch * 8);
      const float g = g_gate[tok], omg = rbf(1.f - g);
      int sel = -1;
#pragma unroll
      for (int c = 0; c < 8; c++) if (idx[c] == tok) sel = c;
      uint4 uv = make_uint4(0u, 0u, 0u, 0u);
      if (sel >= 0) uv = *reinterpret_cast<const uint4*>(g_upd + sel * DM + n0 + ch * 8);
      const uint32_t x4[4] = {xv.x, xv.y, xv.z, xv.w}, u4[4] = {uv.x, uv.y, uv.z, uv.w};
      uint32_t o4[4];
#pragma unroll
      for (int e = 0; e < 4; e++) {
        const float b0 = rbf(u2f(x4[e] << 16) + u2f(u4[e] << 16)), b1 = rbf(u2f(x4[e] & 0xffff0000u) + u2f(u4[e] & 0xffff0000u));
        o4[e] = pack_bf16(omg * b0, omg * b1);
      }
      sts128(sb + G2_TB + row * 256 + ch * 16, o4[0], o4[1], o4[2], o4[3]);
      if (ch == 0) sts32(bars + 512 + row * 4, pack_bf16(g, g));
    }
    bar_arrive(2, 352);
  } else {
    const int wg = warp >> 2;
    float d[64];
#pragma unroll
    for (int i = 0; i < 64; i++) d[i] = 0.f;
    const uint32_t e0 = mapa(bars + 64, 0), e1 = mapa(bars + 64, 1);
#ifdef PER
    if (threadIdx.x == 0) { mbar_wait(bars, 0); atomicMax(&g_end[4], gt32()); }
    __syncwarp();
#endif
    const uint32_t a16 = (((sb + wg * 8192) & 0x3FFFF) >> 4) | (64u << 16), b16 = (((sb + 16384) & 0x3FFFF) >> 4) | (1u << 16);
#pragma unroll 1
    for (int kt = 0, st = 0, ph = 0, ps = -1; kt < 64; kt++) {
      mbar_wait(bars + st * 8, ph);
      wg_fence();
      wgmma_n128_ta<0, 0>(d, a16 + st * 2048, b16 + st * 2048); wgmma_n128_ta<2048, 32>(d, a16 + st * 2048, b16 + st * 2048);
      wgmma_n128_ta<4096, 64>(d, a16 + st * 2048, b16 + st * 2048); wgmma_n128_ta<6144, 96>(d, a16 + st * 2048, b16 + st * 2048);
      wg_commit();
      asm volatile("wgmma.wait_group.sync.aligned 1;" ::: "memory");
      if (ps >= 0 && (tid & 127) == 0) {
        mbar_arrive_cluster_rlx(e0 + ps * 8); mbar_arrive_cluster_rlx(e1 + ps * 8);
      }
      ps = st;
      if (++st == G2_ST) { st = 0; ph ^= 1; }
    }
    wg_wait0();
#ifdef PER
    if (threadIdx.x == 0) atomicMax(&g_end[5], gt32());
#endif
    bar_sync(1, 256);
#pragma unroll
    for (int jj = 0; jj < 8; jj++) {
      const uint32_t q0 = pack_bf16(d[8 * jj], d[8 * jj + 1]), q1 = pack_bf16(d[8 * jj + 2], d[8 * jj + 3]);
      const uint32_t q2 = pack_bf16(d[8 * jj + 4], d[8 * jj + 5]), q3 = pack_bf16(d[8 * jj + 6], d[8 * jj + 7]);
      stsm4t(sb + (jj * 16 + (lane >> 4) * 8 + (lane & 7)) * 272 + (warp * 16 + ((lane >> 3) & 1) * 8) * 2, q0, q1, q2, q3);
    }
    bar_sync(2, 352);
#pragma unroll
    for (int it = 0; it < 8; it++) {
      const int row = it * 16 + (tid >> 4), ch = tid & 15, tok = m0 + row;
      const uint4 av = lds128(sb + row * 272 + ch * 16), tv = lds128(sb + G2_TB + row * 256 + ch * 16);
      const uint32_t g = lds32(bars + 512 + row * 4);
      *reinterpret_cast<uint4*>(out + (size_t)tok * DM + n0 + ch * 8) =
          make_uint4(addb2(mulb2(g, av.x), tv.x), addb2(mulb2(g, av.y), tv.y), addb2(mulb2(g, av.z), tv.z), addb2(mulb2(g, av.w), tv.w));
    }
  }
  asm volatile("barrier.cluster.arrive.relaxed.aligned;\nbarrier.cluster.wait.aligned;" ::: "memory");
#ifdef PER
  if (threadIdx.x == 0) atomicMax(&g_end[2], gt32());
#endif
}
#ifndef WPROM
#define WPROM CU_TENSOR_MAP_L2_PROMOTION_L2_128B
#endif
#ifndef PDL
#define PDL 1
#endif
typedef CUresult (*PFN_encodeTiled)(CUtensorMap*, CUtensorMapDataType, cuuint32_t, void*, const cuuint64_t*, const cuuint64_t*,
                                    const cuuint32_t*, const cuuint32_t*, CUtensorMapInterleave, CUtensorMapSwizzle,
                                    CUtensorMapL2promotion, CUtensorMapFloatOOBfill);

extern "C" void kernel_launch(void* const* d_in, const int* in_sizes, int n_in, void* d_out, int out_size) {
  const bf16* x = (const bf16*)d_in[0];
  const bf16* mem0 = (const bf16*)d_in[1];
  const bf16* Wq = (const bf16*)d_in[2];
  const bf16* Wk = (const bf16*)d_in[3];
  const bf16* Wv = (const bf16*)d_in[4];
  const bf16* Wo = (const bf16*)d_in[5];
  const bf16* w_r = (const bf16*)d_in[8];
  const bf16* w_gate = (const bf16*)d_in[9];
  const bf16* w_up = (const bf16*)d_in[10];
  const bf16* w_down = (const bf16*)d_in[11];
  const bf16* gate_w = (const bf16*)d_in[12];
  bf16* out = (bf16*)d_out;

  static PFN_encodeTiled encode = nullptr;
  if (!encode) {
    void* fn = nullptr; cudaDriverEntryPointQueryResult st;
    cudaGetDriverEntryPoint("cuTensorMapEncodeTiled", &fn, cudaEnableDefault, &st);
    encode = (PFN_encodeTiled)fn;
    cudaFuncSetAttribute(rec_kernel, cudaFuncAttributeMaxDynamicSharedMemorySize, SM_TOTAL);
    cudaFuncSetAttribute(gemm2_kernel, cudaFuncAttributeMaxDynamicSharedMemorySize, G2_SMEM);
  }
  CUtensorMap tmx;
  {
    cuuint64_t gd[3] = {64, S_TOK, DM / 64};
    cuuint64_t gs[2] = {DM * 2, 128};
    cuuint32_t bx[3] = {64, SEG, 4};
    cuuint32_t es[3] = {1, 1, 1};
    encode(&tmx, CU_TENSOR_MAP_DATA_TYPE_BFLOAT16, 3, (void*)x, gd, gs, bx, es, CU_TENSOR_MAP_INTERLEAVE_NONE,
           CU_TENSOR_MAP_SWIZZLE_128B, CU_TENSOR_MAP_L2_PROMOTION_L2_128B, CU_TENSOR_MAP_FLOAT_OOB_FILL_NONE);
  }
  bf16* ox;
  cudaGetSymbolAddress((void**)&ox, g_ox);
  CUtensorMap tmo, tmw, tmw3;
  {
    cuuint64_t gd[2] = {NH * DH, S_TOK}; cuuint64_t gs[1] = {NH * DH * 2}; cuuint32_t bx[2] = {64, 64}; cuuint32_t es[3] = {1, 1, 1};
    encode(&tmo, CU_TENSOR_MAP_DATA_TYPE_BFLOAT16, 2, (void*)ox, gd, gs, bx, es, CU_TENSOR_MAP_INTERLEAVE_NONE,
           CU_TENSOR_MAP_SWIZZLE_128B, CU_TENSOR_MAP_L2_PROMOTION_L2_128B, CU_TENSOR_MAP_FLOAT_OOB_FILL_NONE);
    cuuint64_t gd2[2] = {DM, NH * DH}; cuuint64_t gs2[1] = {DM * 2}; cuuint32_t bx2[2] = {64, 64};
    encode(&tmw, CU_TENSOR_MAP_DATA_TYPE_BFLOAT16, 2, (void*)Wo, gd2, gs2, bx2, es, CU_TENSOR_MAP_INTERLEAVE_NONE,
           CU_TENSOR_MAP_SWIZZLE_128B, CU_TENSOR_MAP_L2_PROMOTION_L2_128B, CU_TENSOR_MAP_FLOAT_OOB_FILL_NONE);
  }
  {
    cuuint64_t gd[5] = {64, NH * DH / 8, 2, 8, DM / 64}; cuuint64_t gs[4] = {8 * DM * 2, 64 * DM * 2, DM * 2, 128}; cuuint32_t bx[5] = {64, 4, 2, 8, 2}; cuuint32_t es[5] = {1, 1, 1, 1, 1};
    encode(&tmw3, CU_TENSOR_MAP_DATA_TYPE_BFLOAT16, 5, (void*)Wo, gd, gs, bx, es, CU_TENSOR_MAP_INTERLEAVE_NONE,
           CU_TENSOR_MAP_SWIZZLE_128B, CU_TENSOR_MAP_L2_PROMOTION_L2_128B, CU_TENSOR_MAP_FLOAT_OOB_FILL_NONE);
  }
  unsigned char* win;
  cudaGetSymbolAddress((void**)&win, g_win);
  win = (unsigned char*)(((uintptr_t)win + (2u << 20) - 1) & ~(uintptr_t)((2u << 20) - 1));
  WMaps W;
  {
    cuuint64_t gd[2] = {NH * DH, DM}; cuuint64_t gs[1] = {NH * DH * 2}; cuuint32_t b32[2] = {32, 128}, b64[2] = {64, 128}; cuuint32_t es[2] = {1, 1};
    encode(&W.q, CU_TENSOR_MAP_DATA_TYPE_BFLOAT16, 2, (void*)Wq, gd, gs, b32, es, CU_TENSOR_MAP_INTERLEAVE_NONE,
           CU_TENSOR_MAP_SWIZZLE_64B, WPROM, CU_TENSOR_MAP_FLOAT_OOB_FILL_NONE);
    encode(&W.k, CU_TENSOR_MAP_DATA_TYPE_BFLOAT16, 2, (void*)Wk, gd, gs, b32, es, CU_TENSOR_MAP_INTERLEAVE_NONE,
           CU_TENSOR_MAP_SWIZZLE_64B, WPROM, CU_TENSOR_MAP_FLOAT_OOB_FILL_NONE);
    encode(&W.v, CU_TENSOR_MAP_DATA_TYPE_BFLOAT16, 2, (void*)Wv, gd, gs, b64, es, CU_TENSOR_MAP_INTERLEAVE_NONE,
           CU_TENSOR_MAP_SWIZZLE_128B, WPROM, CU_TENSOR_MAP_FLOAT_OOB_FILL_NONE);
  }
  RecParams P{mem0, win};
  SideParams SP{x, w_r, w_gate, w_up, w_down, gate_w, Wo};
  rec_kernel<<<NCTA + 4, 384, SM_TOTAL, cudaStreamPerThread>>>(tmx, tmw, W, P, SP);
  {
    cudaLaunchConfig_t cfg = {};
    cfg.gridDim = dim3(NCTA); cfg.blockDim = dim3(384); cfg.dynamicSmemBytes = G2_SMEM; cfg.stream = cudaStreamPerThread;
    cudaLaunchAttribute at[1];
    at[0].id = cudaLaunchAttributeProgrammaticStreamSerialization; at[0].val.programmaticStreamSerializationAllowed = 1;
    cfg.attrs = at; cfg.numAttrs = PDL;
    cudaLaunchKernelEx(&cfg, gemm2_kernel, tmo, tmw3, x, out, win);
  }
}
```

```cpp
#include <cuda_runtime.h>
#include <cuda_bf16.h>
#include <cuda_fp16.h>
#include <cuda.h>
#include <stdint.h>

typedef __nv_bfloat16 bf16;

#define S_TOK 2048
#define DM 1024
#define NH 32
#define DH 128
#define SEG 32
#define NSEG 64
#define FF 3584
#define NCTA 128

static __device__ bf16 g_ox[(size_t)S_TOK * NH * DH];
static __device__ float g_gate[S_TOK];
static __device__ float g_r[S_TOK];
static __device__ int g_idx[8];
static __device__ bf16 g_upd[8 * DM];

static __device__ __forceinline__ float rbf(float v) { return __bfloat162float(__float2bfloat16(v)); }
static __device__ __forceinline__ uint32_t smem_u32(const void* p) { return (uint32_t)__cvta_generic_to_shared(p); }
static __device__ __forceinline__ uint32_t pack_bf16(float lo, float hi) {
  __nv_bfloat162 v = __floats2bfloat162_rn(lo, hi);
  return *reinterpret_cast<uint32_t*>(&v);
}

static __device__ __forceinline__ void wg_fence() { asm volatile("wgmma.fence.sync.aligned;" ::: "memory"); }
static __device__ __forceinline__ void wg_commit() { asm volatile("wgmma.commit_group.sync.aligned;" ::: "memory"); }
static __device__ __forceinline__ void wg_wait0() { asm volatile("wgmma.wait_group.sync.aligned 0;" ::: "memory"); }
static __device__ __forceinline__ void fence_async_smem() { asm volatile("fence.proxy.async.shared::cta;" ::: "memory"); }

#define DESC_HI(sbo) (((sbo) >> 4) | (1u << 30))
template <int OFF, int SCALE>
static __device__ __forceinline__ void wgmma_n32_ra(float (&d)[16], const uint32_t (&a)[4], uint32_t base16) {
  asm volatile(
      "{\n.reg .b32 t;\n.reg .b64 dd;\nadd.u32 t, %20, %21;\nmov.b64 dd, {t, %22};\n"
      "wgmma.mma_async.sync.aligned.m64n32k16.f32.bf16.bf16 "
      "{%0,%1,%2,%3,%4,%5,%6,%7,%8,%9,%10,%11,%12,%13,%14,%15}, {%16,%17,%18,%19}, dd, %23, 1, 1, 0;\n}"
      : "+f"(d[0]), "+f"(d[1]), "+f"(d[2]), "+f"(d[3]), "+f"(d[4]), "+f"(d[5]), "+f"(d[6]), "+f"(d[7]),
        "+f"(d[8]), "+f"(d[9]), "+f"(d[10]), "+f"(d[11]), "+f"(d[12]), "+f"(d[13]), "+f"(d[14]), "+f"(d[15])
      : "r"(a[0]), "r"(a[1]), "r"(a[2]), "r"(a[3]), "r"(base16), "n"(OFF >> 4), "n"(DESC_HI(1024)), "n"(SCALE));
}
template <int AOFF, int BOFF, int SCALE>
static __device__ __forceinline__ void wgmma_n32_ss_ta(float (&d)[16], uint32_t abase16, uint32_t bbase16) {
  asm volatile(
      "{\n.reg .b32 t, u;\n.reg .b64 da, db;\nadd.u32 t, %16, %18;\nmov.b64 da, {t, %20};\nadd.u32 u, %17, %19;\nmov.b64 db, {u, %20};\n"
      "wgmma.mma_async.sync.aligned.m64n32k16.f32.bf16.bf16 "
      "{%0,%1,%2,%3,%4,%5,%6,%7,%8,%9,%10,%11,%12,%13,%14,%15}, da, db, %21, 1, 1, 1, 0;\n}"
      : "+f"(d[0]), "+f"(d[1]), "+f"(d[2]), "+f"(d[3]), "+f"(d[4]), "+f"(d[5]), "+f"(d[6]), "+f"(d[7]),
        "+f"(d[8]), "+f"(d[9]), "+f"(d[10]), "+f"(d[11]), "+f"(d[12]), "+f"(d[13]), "+f"(d[14]), "+f"(d[15])
      : "r"(abase16), "r"(bbase16), "n"(AOFF >> 4), "n"(BOFF >> 4), "n"(DESC_HI(1024)), "n"(SCALE));
}
static __device__ __forceinline__ void ldmatrix_x4_trans(uint32_t (&r)[4], uint32_t addr) {
  asm volatile("ldmatrix.sync.aligned.m8n8.x4.trans.shared.b16 {%0,%1,%2,%3}, [%4];"
               : "=r"(r[0]), "=r"(r[1]), "=r"(r[2]), "=r"(r[3]) : "r"(addr) : "memory");
}
static __device__ __forceinline__ void mma_16816(float (&d)[4], const uint32_t (&a)[4], uint32_t b0, uint32_t b1) {
  asm volatile("mma.sync.aligned.m16n8k16.row.col.f32.bf16.bf16.f32 {%0,%1,%2,%3}, {%4,%5,%6,%7}, {%8,%9}, {%0,%1,%2,%3};"
               : "+f"(d[0]), "+f"(d[1]), "+f"(d[2]), "+f"(d[3])
               : "r"(a[0]), "r"(a[1]), "r"(a[2]), "r"(a[3]), "r"(b0), "r"(b1));
}

static __device__ __forceinline__ uint32_t mapa(uint32_t addr, uint32_t rank) {
  uint32_t r; asm volatile("mapa.shared::cluster.u32 %0, %1, %2;" : "=r"(r) : "r"(addr), "r"(rank)); return r;
}

static __device__ __forceinline__ void mbar_init(uint32_t bar, int cnt) {
  asm volatile("mbarrier.init.shared::cta.b64 [%0], %1;" :: "r"(bar), "r"(cnt) : "memory");
}
static __device__ __forceinline__ void mbar_expect_tx(uint32_t bar, uint32_t bytes) {
  asm volatile("mbarrier.arrive.expect_tx.shared::cta.b64 _, [%0], %1;" :: "r"(bar), "r"(bytes) : "memory");
}
static __device__ __forceinline__ void tma_load_2d(uint32_t dst, const CUtensorMap* tm, int c0, int c1, uint32_t bar) {
  asm volatile("cp.async.bulk.tensor.2d.shared::cluster.global.mbarrier::complete_tx::bytes [%0], [%1, {%3, %4}], [%2];"
               :: "r"(dst), "l"(tm), "r"(bar), "r"(c0), "r"(c1) : "memory");
}

static __device__ unsigned char g_win[6 << 20];
static __device__ unsigned int g_side[67 * 32];
static __device__ unsigned int g_err;
#define W_UP (1u << 20)
#define W_2 (2u << 20)
static __device__ __forceinline__ uint32_t w_blk(uint32_t off, uint32_t side) { return off | (((__popc((off >> 12) & 0xb3u) ^ side) & 1u) << 12); }
static __device__ __forceinline__ uint32_t w_h1(int c) { return W_UP | (1u << 13) | ((c >> 1) << 14) | ((c & 1) << 11); }
#define W_DS 0x30000u
static __device__ __forceinline__ uint32_t w_ar(int s) { return ((s & 1) << 15) | ((s & 2) << 17); }
static __device__ __forceinline__ uint32_t w_mvx(int c, int s) { return W_2 | ((s & 1) << 20) | ((c >> 1) << 14) | ((c & 1) << 11); }
static __device__ __forceinline__ uint32_t w_mxa(int c, int s) { return W_2 | ((s & 1) << 20) | (1u << 13) | ((c >> 1) << 14) | ((c & 1) << 11); }
#define H1_V (1u << 13)

#define SPIN_LIMIT (1 << 18)

#define SM_X 0
#define SM_WOS 65536
#define SM_WVS 131072
#define SM_MEM 163840
#define SM_QKP 180224
#define SM_VP 184320
#define SM_CW 188416
#define SM_VST 196608
#define SM_VR 196608
#define SM_CQ 200704
#define SM_CV 208896
#define SM_XF 217088
#define SM_VL 221184
#define SM_OF 225280
#define SM_PF 229376
#define SM_PX 230016
#define SM_RD 198656
#define SM_QA 223232
#define SM_XS 231168
#define SM_BAR 231808
#define SM_Z 231936
#define SM_TOTAL 232128
#define MB_F 0
#define MB_XE0 16
#define MB_XE1 112
#define MB_INIT 24
#define MB_MEM 32
#define MB_W 256
#define MB_XF 64
#define MB_VR 72
#define MB_X0 80
#define MB_WO 88
#define SM_SIDE (SM_BAR + 96)
#define B_QK 1
#define B_V 2
#define B_P 3
#define B_O 4
#define B_O2 5
#define B_PUB 6
#define B_CQ 7
#define B_QK1 8
#define B_PXF 10
#define B_CV 15
#define B_X2 11
#define B_PX 12
#define B_GO 14
#define B_G1 13

#ifdef PROF
__device__ unsigned int g_ts[NCTA][80][32];
#ifdef GT
#define TCLK() gt32()
#else
#define TCLK() clk32()
#endif
#ifndef TMASK
#define TMASK 0xffffffffu
#endif
#define TST(st, i, c, v) do { if ((TMASK >> (i)) & 1u) asm volatile("{\n.reg .pred q;\nsetp.eq.u32 q, %2, 0;\n@q st.global.u32 [%0], %1;\n}" :: "l"(&g_ts[cta][(st) + 1][i]), "r"((uint32_t)(v)), "r"((uint32_t)(c)) : "memory"); } while (0)
#define TS(i) TST(s, i, l16, TCLK())
#define TV(i, v) TST(s, i, l16, v)
#define TSF(i, w) TST(s, i, l16 | (w8 ^ (w)), TCLK())
#define TSP(i, w) TST(s - 1, i, l16 | (w8 ^ (w)), TCLK())
#define TVF(i, v) TV(i, v)
#else
#define TST(a, b, c, d)
#define TSF(i, w)
#define TSP(i, w)
#define TVF(i, v)
#define TS(i)
#define TV(i, v)
#endif

static __device__ __forceinline__ void bar_sync(int id, int n) { asm volatile("bar.sync %0, %1;" :: "r"(id), "r"(n) : "memory"); }
static __device__ __forceinline__ void bar_arrive(int id, int n) { asm volatile("bar.arrive %0, %1;" :: "r"(id), "r"(n) : "memory"); }
static __device__ __forceinline__ uint4 ldg_r4(const void* p) { uint4 v;
  asm volatile("ld.relaxed.gpu.global.v4.u32 {%0,%1,%2,%3}, [%4];" : "=r"(v.x), "=r"(v.y), "=r"(v.z), "=r"(v.w) : "l"(p) : "memory"); return v; }
static __device__ __forceinline__ uint32_t ldg_r1(const void* p) { uint32_t v;
  asm volatile("ld.relaxed.gpu.global.u32 %0, [%1];" : "=r"(v) : "l"(p) : "memory"); return v; }
static __device__ __forceinline__ void stg_r4(void* p, uint32_t a, uint32_t b, uint32_t c, uint32_t d) {
  asm volatile("st.relaxed.gpu.global.v4.u32 [%0], {%1,%2,%3,%4};" :: "l"(p), "r"(a), "r"(b), "r"(c), "r"(d) : "memory"); }
static __device__ __forceinline__ uint2 ldg_r2(const void* p) { uint2 v;
  asm volatile("ld.relaxed.gpu.global.v2.u32 {%0,%1}, [%2];" : "=r"(v.x), "=r"(v.y) : "l"(p) : "memory"); return v; }
static __device__ __forceinline__ void stg_4(void* p, const uint4& v) {
  asm volatile("st.global.v4.u32 [%0], {%1,%2,%3,%4};" :: "l"(p), "r"(v.x), "r"(v.y), "r"(v.z), "r"(v.w) : "memory"); }
static __device__ __forceinline__ uint32_t f2u(float v) { return __float_as_uint(v); }
static __device__ __forceinline__ void stg_2(void* p, uint32_t a, uint32_t b) {
  asm volatile("st.global.v2.u32 [%0], {%1,%2};" :: "l"(p), "r"(a), "r"(b) : "memory"); }
static __device__ __forceinline__ void stg_r1(void* p, uint32_t a) {
  asm volatile("st.relaxed.gpu.global.u32 [%0], %1;" :: "l"(p), "r"(a) : "memory"); }
static __device__ __forceinline__ void sts128(uint32_t a, uint32_t x, uint32_t y, uint32_t z, uint32_t w) {
  asm volatile("st.shared.v4.u32 [%0], {%1,%2,%3,%4};" :: "r"(a), "r"(x), "r"(y), "r"(z), "r"(w) : "memory"); }
static __device__ __forceinline__ void sts128f(uint32_t a, float x, float y, float z, float w) {
  asm volatile("st.shared.v4.f32 [%0], {%1,%2,%3,%4};" :: "r"(a), "f"(x), "f"(y), "f"(z), "f"(w) : "memory"); }
static __device__ __forceinline__ uint4 lds128(uint32_t a) { uint4 v;
  asm volatile("ld.shared.v4.u32 {%0,%1,%2,%3}, [%4];" : "=r"(v.x), "=r"(v.y), "=r"(v.z), "=r"(v.w) : "r"(a) : "memory"); return v; }
static __device__ __forceinline__ float4 lds128f(uint32_t a) { float4 v;
  asm volatile("ld.shared.v4.f32 {%0,%1,%2,%3}, [%4];" : "=f"(v.x), "=f"(v.y), "=f"(v.z), "=f"(v.w) : "r"(a) : "memory"); return v; }
static __device__ __forceinline__ void sts32(uint32_t a, uint32_t x) { asm volatile("st.shared.u32 [%0], %1;" :: "r"(a), "r"(x) : "memory"); }
static __device__ __forceinline__ uint2 lds64(uint32_t a) { uint2 v;
  asm volatile("ld.shared.v2.u32 {%0,%1}, [%2];" : "=r"(v.x), "=r"(v.y) : "r"(a) : "memory"); return v; }
static __device__ __forceinline__ void st_async4(uint32_t ra, float x, float y, float z, float w, uint32_t rbar) {
  asm volatile("st.async.weak.shared::cluster.mbarrier::complete_tx::bytes.v4.f32 [%0], {%1,%2,%3,%4}, [%5];"
               :: "r"(ra), "f"(x), "f"(y), "f"(z), "f"(w), "r"(rbar) : "memory"); }
static __device__ __forceinline__ void stsm4t(uint32_t a, uint32_t x, uint32_t y, uint32_t z, uint32_t w) {
  asm volatile("stmatrix.sync.aligned.m8n8.x4.trans.shared.b16 [%0], {%1,%2,%3,%4};" :: "r"(a), "r"(x), "r"(y), "r"(z), "r"(w) : "memory"); }
static __device__ __forceinline__ uint32_t hmax2(uint32_t a, uint32_t b) { uint32_t d;
  asm("max.f16x2 %0, %1, %2;" : "=r"(d) : "r"(a), "r"(b)); return d; }
static __device__ __forceinline__ uint32_t hadd2(uint32_t a, uint32_t b) { uint32_t d;
  asm("add.rn.f16x2 %0, %1, %2;" : "=r"(d) : "r"(a), "r"(b)); return d; }
static __device__ __forceinline__ uint32_t packv(float a, float b, float c, float d) { uint32_t r;
  asm volatile("{\n.reg .f32 x, y;\nadd.f32 x, %1, %2;\nadd.f32 y, %3, %4;\ncvt.rn.bf16x2.f32 %0, y, x;\n}" : "=r"(r) : "f"(a), "f"(b), "f"(c), "f"(d)); return r; }
static __device__ __forceinline__ uint32_t packh(float a, float b, float c, float d) { uint32_t r;
  asm volatile("{\n.reg .f32 x, y;\nadd.f32 x, %1, %2;\nadd.f32 y, %3, %4;\ncvt.rn.satfinite.f16x2.f32 %0, y, x;\n}" : "=r"(r) : "f"(a), "f"(b), "f"(c), "f"(d)); return r; }
static __device__ __forceinline__ float ex2v(float a, float b, float c) { float y;
  asm volatile("{\n.reg .f32 x;\nfma.rn.f32 x, %1, %2, %3;\nex2.approx.ftz.f32 %0, x;\n}" : "=f"(y) : "f"(a), "f"(b), "f"(c)); return y; }
static __device__ __forceinline__ uint32_t shfl_x(uint32_t a, int m) { uint32_t d;
  asm volatile("shfl.sync.bfly.b32 %0, %1, %2, 0x1f, 0xffffffff;" : "=r"(d) : "r"(a), "r"(m)); return d; }
static __device__ __forceinline__ void h2f(float& lo, float& hi, uint32_t a) {
  asm volatile("{\n.reg .b16 l, h;\nmov.b32 {l, h}, %2;\ncvt.f32.f16 %0, l;\ncvt.f32.f16 %1, h;\n}" : "=f"(lo), "=f"(hi) : "r"(a)); }
static __device__ __forceinline__ uint4 ldsm4(uint32_t a) { uint4 v;
  asm volatile("ldmatrix.sync.aligned.m8n8.x4.shared.b16 {%0,%1,%2,%3}, [%4];" : "=r"(v.x), "=r"(v.y), "=r"(v.z), "=r"(v.w) : "r"(a) : "memory"); return v; }
static __device__ __forceinline__ uint4 ldsm4t(uint32_t a) { uint4 v;
  asm volatile("ldmatrix.sync.aligned.m8n8.x4.trans.shared.b16 {%0,%1,%2,%3}, [%4];" : "=r"(v.x), "=r"(v.y), "=r"(v.z), "=r"(v.w) : "r"(a) : "memory"); return v; }
static __device__ __forceinline__ uint32_t movm(uint32_t a) { uint32_t d;
  asm volatile("movmatrix.sync.aligned.m8n8.trans.b16 %0, %1;" : "=r"(d) : "r"(a)); return d; }
static __device__ __forceinline__ float u2f(uint32_t v) { return __uint_as_float(v); }
static __device__ __forceinline__ uint32_t tagw(uint32_t w, uint32_t t) { uint32_t d;
  asm("lop3.b32 %0, %1, %2, 1, 0xd8;" : "=r"(d) : "r"(w), "r"(t)); return d; }
static __device__ __forceinline__ uint32_t pack_f16(float lo, float hi) { uint32_t d;
  asm("cvt.rn.satfinite.f16x2.f32 %0, %1, %2;" : "=r"(d) : "f"(hi), "f"(lo)); return d; }
static __device__ __forceinline__ void sum_h4(float& lo, float& hi, uint32_t a, uint32_t b, uint32_t c, uint32_t d) {
  const float2 x = __half22float2(*reinterpret_cast<__half2*>(&a)), y = __half22float2(*reinterpret_cast<__half2*>(&b));
  const float2 z = __half22float2(*reinterpret_cast<__half2*>(&c)), w = __half22float2(*reinterpret_cast<__half2*>(&d));
  lo = (x.x + y.x) + (z.x + w.x); hi = (x.y + y.y) + (z.y + w.y);
}
static __device__ __forceinline__ uint32_t lds32(uint32_t a) { uint32_t v; asm volatile("ld.shared.u32 %0, [%1];" : "=r"(v) : "r"(a) : "memory"); return v; }
static __device__ __forceinline__ uint32_t addb2(uint32_t a, uint32_t b) { uint32_t d;
  asm("add.rn.bf16x2 %0, %1, %2;" : "=r"(d) : "r"(a), "r"(b)); return d; }
static __device__ __forceinline__ uint32_t mulb2(uint32_t a, uint32_t b) { uint32_t d;
  asm("mul.rn.bf16x2 %0, %1, %2;" : "=r"(d) : "r"(a), "r"(b)); return d; }
static __device__ __forceinline__ uint32_t mulb2v(uint32_t a, uint32_t b) { uint32_t d;
  asm volatile("mul.rn.bf16x2 %0, %1, %2;" : "=r"(d) : "r"(a), "r"(b)); return d; }
static __device__ __forceinline__ uint32_t x3(uint32_t a, uint32_t b, uint32_t t) { uint32_t d;
  asm("lop3.b32 %0, %1, %2, %3, 0x7e;" : "=r"(d) : "r"(a), "r"(b), "r"(t)); return d; }
static __device__ __forceinline__ uint32_t or3(uint32_t a, uint32_t b, uint32_t c) { uint32_t d;
  asm("lop3.b32 %0, %1, %2, %3, 0xfe;" : "=r"(d) : "r"(a), "r"(b), "r"(c)); return d; }
static __device__ __forceinline__ float ex2(float x) { float y; asm("ex2.approx.ftz.f32 %0, %1;" : "=f"(y) : "f"(x)); return y; }
static __device__ __forceinline__ float rcpf(float x) { float y; asm("rcp.approx.ftz.f32 %0, %1;" : "=f"(y) : "f"(x)); return y; }
static __device__ __forceinline__ void mbar_wait(uint32_t bar, int parity) {
  asm volatile("{\n.reg .pred p, q;\n.reg .u32 n;\nmbarrier.try_wait.parity.shared::cta.b64 p, [%0], %1;\n@p bra W_DONE;\nmov.u32 n, 0;\n"
               "W_LOOP:\nmbarrier.try_wait.parity.shared::cta.b64 p, [%0], %1;\nadd.u32 n, n, 1;\nsetp.lt.and.u32 q, n, %2, !p;\n@q bra W_LOOP;\nW_DONE:\n}"
               :: "r"(bar), "r"(parity), "n"(SPIN_LIMIT) : "memory");
}
static __device__ __forceinline__ uint32_t mbar_test(uint32_t bar, int parity) { uint32_t ok;
  asm volatile("{\n.reg .pred p;\nmbarrier.test_wait.parity.shared::cta.b64 p, [%1], %2;\nselp.u32 %0, 1, 0, p;\n}" : "=r"(ok) : "r"(bar), "r"(parity) : "memory"); return ok; }
static __device__ __forceinline__ void mbar_arrive(uint32_t bar) {
  asm volatile("mbarrier.arrive.shared::cta.b64 _, [%0];" :: "r"(bar) : "memory"); }
static __device__ __forceinline__ void mbar_arrive_cluster_rlx(uint32_t raddr) {
  asm volatile("mbarrier.arrive.relaxed.cluster.shared::cluster.b64 _, [%0];" :: "r"(raddr) : "memory"); }
static __device__ __forceinline__ void tma_load_mc(uint32_t dst, const CUtensorMap* tm, int c1, int c2, uint32_t bar) {
#ifdef NOTMA
  if ((NOTMA >> (c2 >> 3)) & 1) asm volatile("mbarrier.complete_tx.relaxed.cta.shared::cta.b64 [%0], 32768;" :: "r"(bar) : "memory"); else
#endif
  asm volatile("cp.async.bulk.tensor.3d.shared::cluster.global.mbarrier::complete_tx::bytes.multicast::cluster [%0], [%1, {%3, %4, %5}], [%2], %6;"
               :: "r"(dst), "l"(tm), "r"(bar), "r"(0), "r"(c1), "r"(c2), "h"((uint16_t)3) : "memory"); }
static __device__ __forceinline__ void cp16(uint32_t dst, const void* src) {
  asm volatile("cp.async.cg.shared.global [%0], [%1], 16;" :: "r"(dst), "l"(src) : "memory"); }
static __device__ __forceinline__ void mma_1688(float (&d)[4], uint32_t a0, uint32_t a1, uint32_t b0) {
  asm volatile("mma.sync.aligned.m16n8k8.row.col.f32.bf16.bf16.f32 {%0,%1,%2,%3}, {%4,%5}, {%6}, {%0,%1,%2,%3};"
               : "+f"(d[0]), "+f"(d[1]), "+f"(d[2]), "+f"(d[3]) : "r"(a0), "r"(a1), "r"(b0)); }
static __device__ __forceinline__ void mma4(float (&d)[4], uint32_t a0, uint32_t a1, uint32_t a2, uint32_t a3, uint32_t b0, uint32_t b1) {
  asm volatile("mma.sync.aligned.m16n8k16.row.col.f32.bf16.bf16.f32 {%0,%1,%2,%3}, {%4,%5,%6,%7}, {%8,%9}, {%0,%1,%2,%3};"
               : "+f"(d[0]), "+f"(d[1]), "+f"(d[2]), "+f"(d[3]) : "r"(a0), "r"(a1), "r"(a2), "r"(a3), "r"(b0), "r"(b1)); }
static __device__ __forceinline__ void mma4z(float (&d)[4], uint32_t a0, uint32_t a1, uint32_t a2, uint32_t a3, uint32_t b0, uint32_t b1) {
  asm volatile("mma.sync.aligned.m16n8k16.row.col.f32.bf16.bf16.f32 {%0,%1,%2,%3}, {%4,%5,%6,%7}, {%8,%9}, {%10,%10,%10,%10};"
               : "=f"(d[0]), "=f"(d[1]), "=f"(d[2]), "=f"(d[3]) : "r"(a0), "r"(a1), "r"(a2), "r"(a3), "r"(b0), "r"(b1), "f"(0.f)); }
static __device__ __forceinline__ uint32_t clk32() { uint32_t t; asm volatile("mov.u32 %0, %%clock;" : "=r"(t)); return t; }
static __device__ __forceinline__ uint32_t gt32() { uint32_t t; asm volatile("mov.u32 %0, %%globaltimer_lo;" : "=r"(t)); return t; }
static __device__ __forceinline__ void spin(int clk) { if (clk > 0) { uint32_t t = clk32(); while (clk32() - t < (uint32_t)clk) {} } }
#define FENCE() asm volatile("griddepcontrol.launch_dependents;" ::: "memory")
#define OPAQUE_L(p) asm volatile("" : "+l"(p))
#define OPAQUE_R(p) asm volatile("" : "+r"(p))

template <int KK, int K1, int W0, int NW, int FIRST> struct XR {
  static __device__ __forceinline__ void run(float (&d)[16], const uint32_t (&w)[NW][4], uint32_t b16) {
#ifdef NOWG
    if (KK % NOWG == 0)
#endif
    wgmma_n32_ra<(KK >> 2) * 4096 + (KK & 3) * 32, !FIRST>(d, w[W0 + KK], b16);
    XR<KK + 1, K1, W0, NW, 0>::run(d, w, b16);
  }
};
template <int K1, int W0, int NW, int FIRST> struct XR<K1, K1, W0, NW, FIRST> { static __device__ __forceinline__ void run(float (&)[16], const uint32_t (&)[NW][4], uint32_t) {} };
template <int KK, int K0, int K1, int FIRST> struct XS {
  static __device__ __forceinline__ void run(float (&d)[16], uint32_t a16, uint32_t b16) {
#ifdef NOWG
    if (KK % NOWG == 0)
#endif
    wgmma_n32_ss_ta<(KK - K0) * 2048, (KK >> 2) * 4096 + (KK & 3) * 32, !FIRST>(d, a16, b16);
    XS<KK + 1, K0, K1, 0>::run(d, a16, b16);
  }
};
template <int K0, int K1, int FIRST> struct XS<K1, K0, K1, FIRST> { static __device__ __forceinline__ void run(float (&)[16], uint32_t, uint32_t) {} };

static __device__ bf16 g_h[8 * FF];
static __device__ unsigned int g_sbar;
struct SideParams { const bf16* x; const bf16* w_r; const bf16* w_gate; const bf16* w_up; const bf16* w_down; const bf16* gate_w; const bf16* Wo; };

static __device__ __forceinline__ void side_barrier(unsigned int target) {
  __syncthreads();
  if (threadIdx.x == 0) {
    __threadfence();
    atomicAdd(&g_sbar, 1u);
    int n = 0;
    while (*(volatile unsigned int*)&g_sbar < target) { if (++n > (1 << 22)) { g_err = 50; break; } }
    __threadfence();
  }
  __syncthreads();
}
static __device__ __forceinline__ uint4 ldg_nc(const void* p) { uint4 v;
  asm volatile("ld.global.nc.L1::no_allocate.v4.u32 {%0,%1,%2,%3}, [%4];" : "=r"(v.x), "=r"(v.y), "=r"(v.z), "=r"(v.w) : "l"(p)); return v; }
#ifndef SPD
#define SPD 3
#endif
static __device__ __forceinline__ void l2pf(const void* p) { asm volatile("prefetch.global.L2 [%0];" :: "l"(p)); }
static __device__ __forceinline__ void mm8(float (&acc)[8][4], const bf16* W, const bf16* Wn, int ldw, int nk16, uint32_t abase, uint32_t ring, int lane) {
  const int rw = lane >> 3, ch = lane & 7;
  const bf16* wp = W + (size_t)rw * ldw + ch * 8;
  const uint32_t wd = ring + rw * 128, rd = ring + ((rw & 1) * 8 + ch) * 128;
#define MM_LD(k) do { if ((k) < nk16) { const bf16* q = wp + (size_t)(k) * 16 * ldw; \
    _Pragma("unroll") for (int i = 0; i < 4; i++) cp16(wd + ((k) & 3) * 2048 + i * 512 + ((ch ^ (rw + (i & 1) * 4)) << 4), q + (size_t)(4 * i) * ldw); } \
    asm volatile("cp.async.commit_group;" ::: "memory"); } while (0)
  __syncwarp();
  MM_LD(0); MM_LD(1); MM_LD(2);
#pragma unroll 1
  for (int k = 0; k < nk16; k++) {
    if (SPD && (k & 1) == 0) {
      const int kp = k + 4 * SPD;
      const bf16* pf = kp < nk16 ? W + (size_t)(kp * 16) * ldw : Wn ? Wn + (size_t)((kp - nk16) * 16) * ldw : nullptr;
      if (pf) l2pf(pf + (size_t)lane * ldw);
    }
    asm volatile("cp.async.wait_group 2;" ::: "memory");
    __syncwarp();
    MM_LD(k + 3);
    const uint32_t a0 = lds32(abase + k * 32), a2 = lds32(abase + k * 32 + 16);
#pragma unroll
    for (int i = 0; i < 4; i++) {
      const uint4 b = ldsm4t(rd + (k & 3) * 2048 + (((2 * i + (rw >> 1)) ^ ch) << 4));
      mma4(acc[2 * i], a0, 0u, a2, 0u, b.x, b.y); mma4(acc[2 * i + 1], a0, 0u, a2, 0u, b.z, b.w);
    }
  }
}
static __device__ __noinline__ void side_work(const SideParams& P, unsigned char* smem, int q) {
  const int tid = threadIdx.x, lane = tid & 31, warp = tid >> 5, g = lane >> 2, t = lane & 3;
  const uint32_t sb = smem_u32(smem);
  unsigned int* cand = reinterpret_cast<unsigned int*>(smem);
  bf16* xs = reinterpret_cast<bf16*>(smem + 1024);
  float* part = reinterpret_cast<float*>(smem + 65536);
  {
    for (int i = tid; i < 256; i += 384) *reinterpret_cast<uint4*>(smem + 1024 + i * 16) = ldg_nc((i < 128 ? P.gate_w : P.w_r - DM) + i * 8);
    __syncthreads();
#pragma unroll 1
    for (int it = warp; it < 64; it += 12) {
      const bf16* xp = P.x + (size_t)(q * 512 + (it >> 1) * 16 + g) * DM + (it & 1) * 512 + t * 8;
      for (int a = it == warp ? 0 : 1; a < 2 && it + 12 * a < 64; a++)
#pragma unroll
        for (int i = 0; i < 4; i++) l2pf(P.x + (size_t)(q * 512 + (it >> 1) * 16 + a * 96 + i * 4 + (lane >> 3)) * DM + (it & 1) * 512 + (lane & 7) * 64);
      const uint32_t xb = sb + 16384 + warp * 16384 + lane * 16;
#pragma unroll
      for (int i = 0; i < 16; i++) { cp16(xb + i * 1024, xp + i * 32); cp16(xb + i * 1024 + 512, xp + 8 * DM + i * 32); }
      asm volatile("cp.async.commit_group;\ncp.async.wait_group 0;" ::: "memory");
      float sg[4] = {0.f, 0.f, 0.f, 0.f}, sr[4] = {0.f, 0.f, 0.f, 0.f};
#pragma unroll
      for (int i = 0; i < 16; i++) {
        const uint4 gw = lds128(sb + 1024 + (it & 1) * 1024 + i * 64 + t * 16), wr = lds128(sb + 3072 + (it & 1) * 1024 + i * 64 + t * 16);
        const uint4 lo = lds128(xb + i * 1024), hi = lds128(xb + i * 1024 + 512);
        mma4(sr, lo.x, hi.x, lo.y, hi.y, wr.x, wr.y); mma4(sr, lo.z, hi.z, lo.w, hi.w, wr.z, wr.w);
        mma4(sg, mulb2(lo.x, gw.x), mulb2(hi.x, gw.x), mulb2(lo.y, gw.y), mulb2(hi.y, gw.y), 0x3F803F80u, 0x3F803F80u);
        mma4(sg, mulb2(lo.z, gw.z), mulb2(hi.z, gw.z), mulb2(lo.w, gw.w), mulb2(hi.w, gw.w), 0x3F803F80u, 0x3F803F80u);
      }
      if (t == 0) {
        float* pp = reinterpret_cast<float*>(smem + 8192) + (it & 1) * 1024 + (it >> 1) * 16 + g;
        pp[0] = sg[0]; pp[8] = sg[2]; pp[512] = sr[0]; pp[520] = sr[2];
      }
    }
    __syncthreads();
    for (int i = tid; i < 512; i += 384) {
      const float* pp = reinterpret_cast<const float*>(smem + 8192);
      g_gate[q * 512 + i] = rbf(1.f / (1.f + expf(-rbf(pp[i] + pp[1024 + i]))));
      g_r[q * 512 + i] = rbf(pp[512 + i] + pp[1536 + i]);
    }
    for (int i = tid; i < 16 * 896; i += 384) part[i] = 0.f;
  }
#define GU(u) (((u) % 28) / 14 ? P.w_up : P.w_gate) + (size_t)((u) / 28) * 512 * FF + q * 896 + ((u) % 14) * 64
  for (int i = lane; i < 64 * SPD; i += 32) l2pf(GU(warp) + (size_t)i * FF);
  side_barrier(4);
  {
    unsigned int key[8];
#pragma unroll
    for (int i = 0; i < 8; i++) {
      const int tok = (warp & 7) * 256 + i * 32 + lane;
      const uint32_t b = __float_as_uint(__ldcg(&g_r[tok]) + 0.f) >> 16;
      key[i] = (((b & 0x8000u) ? (~b & 0xffffu) : (b | 0x8000u)) << 16) | (uint32_t)(2047 - tok);
    }
    for (int pass = 0; pass < 2; pass++) {
      if (pass == 0 ? warp < 8 : warp == 0) {
        for (int c = 0; c < 8; c++) {
          const unsigned int m = __reduce_max_sync(~0u, max(max(max(key[0], key[1]), max(key[2], key[3])), max(max(key[4], key[5]), max(key[6], key[7]))));
#pragma unroll
          for (int i = 0; i < 8; i++) if (key[i] == m) key[i] = 0u;
          if (lane == 0) cand[pass ? 128 + c : warp * 8 + c] = m;
        }
      }
      __syncthreads();
      if (pass == 0 && warp == 0) {
#pragma unroll
        for (int i = 0; i < 8; i++) key[i] = i < 2 ? cand[i * 32 + lane] : 0u;
      }
    }
    if (q == 0 && tid < 8) g_idx[tid] = 2047 - (int)(cand[128 + tid] & 0xffffu);
    for (int i = tid; i < 1024; i += 384) {
      const int c = i >> 7, tok = 2047 - (int)(cand[128 + c] & 0xffffu);
      *reinterpret_cast<uint4*>(xs + c * (FF + 8) + (i & 127) * 8) = ldg_nc(P.x + (size_t)tok * DM + (i & 127) * 8);
    }
    __syncthreads();
  }
  const uint32_t abase = sb + 1024 + g * (FF + 8) * 2 + t * 4, ring = sb + 131072 + warp * 8192;
  for (int u = warp; u < 56; u += 12) {
    const int kh = u / 28, mat = (u % 28) / 14, cb = u % 14;
    float acc[8][4];
#pragma unroll
    for (int i = 0; i < 8; i++) acc[i][0] = acc[i][1] = acc[i][2] = acc[i][3] = 0.f;
    mm8(acc, GU(u), u + 12 < 56 ? GU(u + 12) : nullptr, FF, DM / 32, abase + kh * 1024, ring, lane);
    float* pp = part + (mat * 8 + g) * 896 + cb * 64 + 2 * t;
#pragma unroll
    for (int i = 0; i < 8; i++) { atomicAdd(pp + 8 * i, acc[i][0]); atomicAdd(pp + 8 * i + 1, acc[i][1]); }
  }
  for (int i = lane; i < 64 * SPD; i += 32) l2pf(P.w_down + (size_t)((warp >> 2) * 1216 + i) * DM + q * 256 + (warp & 3) * 64);
  __syncthreads();
  for (int i = tid; i < 8 * 896; i += 384) {
    const float ag = rbf(part[i]), au = rbf(part[8 * 896 + i]);
    g_h[(i / 896) * FF + q * 896 + i % 896] = __float2bfloat16(rbf(ag / (1.f + expf(-ag))) * au);
  }
  side_barrier(8);
  for (int i = tid; i < 8 * FF / 8; i += 384) {
    const int c = i / (FF / 8), o = i % (FF / 8);
    *reinterpret_cast<uint4*>(xs + c * (FF + 8) + o * 8) = __ldcg(reinterpret_cast<const uint4*>(g_h + c * FF + o * 8));
  }
  __syncthreads();
  {
    const int cb = warp & 3, kq = warp >> 2;
    float acc[8][4];
#pragma unroll
    for (int i = 0; i < 8; i++) acc[i][0] = acc[i][1] = acc[i][2] = acc[i][3] = 0.f;
    mm8(acc, P.w_down + (size_t)kq * 1216 * DM + q * 256 + cb * 64, nullptr, DM, kq == 2 ? 72 : 76, abase + kq * 1216 * 2, ring, lane);
#pragma unroll
    for (int i = 0; i < 8; i++) { part[(kq * 8 + g) * 256 + cb * 64 + 2 * t + 8 * i] = acc[i][0]; part[(kq * 8 + g) * 256 + cb * 64 + 2 * t + 8 * i + 1] = acc[i][1]; }
    __syncthreads();
    for (int i = tid; i < 2048; i += 384) {
      const int c = i >> 8, tok = 2047 - (int)(cand[128 + c] & 0xffffu);
      const float y = (part[i] + part[2048 + i]) + part[4096 + i];
      const float rs = rbf(1.f / (1.f + expf(-__ldcg(&g_r[tok]))));
      g_upd[c * DM + q * 256 + (i & 255)] = __float2bfloat16(rbf(y) * rs);
    }
  }
}
struct RecParams { const bf16* mem0; unsigned char* win; };
struct WMaps { CUtensorMap q, k, v; };
#ifndef KB
#define KB 8
#endif
#ifndef WPF
#define WPF 7
#endif
#ifndef WPA
#define WPA 3
#endif
#ifndef XPF
#define XPF 4
#endif
#ifndef WPP
#define WPP 6
#endif
#define RF_FAT 208
#define RF_CTL 88
#define WSPL 1
#define NPROBE 3
#define DLY_TB 700
#ifndef DLY_SIDE
#define DLY_SIDE 16000
#endif
#define KU 32
#define KD 4
#ifndef DLYS
#define DLYS 560, 200, 215, 60, 770, 250, 1220, 880, 460
#endif
#define NTUNE 9
#define TUNE_NAMES {"OM3", "XL", "S", "XD", "WO", "V", "OK", "OKS", "ORR"}
__constant__ int g_tune[NTUNE] = {DLYS};
#define DLY_M3 g_tune[0]
#define DLY_XL g_tune[1]
#define DLY_S g_tune[2]
#define DLY_XD g_tune[3]
#define DLY_WO g_tune[4]
#define DLY_V g_tune[5]
#define DLY_K g_tune[6]
#define DLY_KS g_tune[7]
#define DLY_RR g_tune[8]
#ifdef PRO
__device__ unsigned g_pro[NCTA][16];
#define PT(i, c) do { if (c) g_pro[cta][i] = gt32(); } while (0)
#else
#define PT(i, c)
#endif
#ifdef PER
__device__ unsigned g_pk[NCTA][64], g_pclk[NCTA][64], g_per[NCTA][64], g_end[8] = {0, 0, 0, 0, 0, 0, 0, 100000};
#endif
#define STR2(x) #x
#define STR(x) STR2(x)

#ifndef BPAT
#define BPAT 0xAAAA
#endif
template <int I, int NR, int NS> struct XV {
  static __device__ __forceinline__ void run(float (&d)[16], const uint32_t (&wv)[8][4], uint32_t a16, uint32_t b16) {
    if ((BPAT >> I) & 1) XS<8 + (NS & 7), 8, 9 + (NS & 7), I == 0>::run(d, a16, b16); else XR<(NR & 7), (NR & 7) + 1, 0, 8, I == 0>::run(d, wv, b16);
    XV<I + 1, NR + !((BPAT >> I) & 1), NS + ((BPAT >> I) & 1)>::run(d, wv, a16, b16);
  }
};
template <int NR, int NS> struct XV<16, NR, NS> { static __device__ __forceinline__ void run(float (&)[16], const uint32_t (&)[8][4], uint32_t, uint32_t) {} };
static __device__ __forceinline__ void cp16p(uint32_t dst, const void* src, uint32_t v) {
  asm volatile("{\n.reg .pred q;\nsetp.ne.u32 q, %2, 0;\n@q cp.async.cg.shared.global [%0], [%1], 16;\n}" :: "r"(dst), "l"(src), "r"(v) : "memory"); }
static __device__ __forceinline__ void red_bf2(void* p, uint32_t v) {
  asm volatile("red.relaxed.gpu.global.add.noftz.bf16x2 [%0], %1;" :: "l"(p), "r"(v) : "memory"); }
static __device__ __forceinline__ void red_bf2p4(void* p, uint32_t v, uint32_t e) {
  asm volatile("{\n.reg .pred q;\nsetp.lt.u32 q, %2, 4;\n@q red.relaxed.gpu.global.add.noftz.bf16x2 [%0], %1;\n}" :: "l"(p), "r"(v), "r"(e) : "memory"); }
static __device__ __forceinline__ void eta2(void* p, uint32_t t, uint32_t first, uint32_t l16) {
  asm volatile("{\n.reg .pred q;\nsetp.lt.u32 q, %3, 32;\n@q red.relaxed.gpu.global.max.u32 [%0+4], %1;\n@q red.relaxed.gpu.global.add.u32 [%0], %2;\n}" :: "l"(p), "r"(t), "r"(first), "r"(l16) : "memory"); }
static __device__ __forceinline__ uint32_t cnt_word(uint32_t L) { return (L & 17u) | ((L & 6u) << 1) | ((L & 8u) >> 2); }
static __device__ __forceinline__ uint32_t cnt_line(uint32_t l) { return (l & 17u) | ((l & 12u) >> 1) | ((l & 2u) << 2); }
static __device__ __forceinline__ int m3_check(uint32_t sb, const unsigned char* p3, const unsigned char* pd, int dq, uint32_t l16, uint32_t mc, int hf, int s) {
  const uint32_t md = l16 + (sb + SM_MEM + hf * 8192), dd = l16 + (sb + SM_RD + hf * 256), dc = (l16 >> 2) + (sb + SM_RD + hf * 256);
  int n = 0;
  uint32_t c0 = 0, c1 = 0, d0 = 0, d1 = 0, todo = 1;
#pragma unroll 1
  do {
    if (n) {
      const int src = cnt_word(l16 >> 4);
      const uint32_t m0 = __ballot_sync(~0u, (__shfl_sync(~0u, c0, src) >> 16) != 0x4200u) >> (l16 >> 7), m1 = __ballot_sync(~0u, (__shfl_sync(~0u, c1, src) >> 16) != 0x4200u) >> (l16 >> 7);
      const uint32_t m2 = __ballot_sync(~0u, (d0 >> 16) != 0x4200u), m3 = __ballot_sync(~0u, (d1 >> 16) != 0x4200u);
#pragma unroll
      for (int i = 0; i < 8; i++) { cp16p(md + i * 512, p3 + i * 1024, m0 & (1u << (4 * i))); cp16p(md + 4096 + i * 512, p3 + dq + i * 1024, m1 & (1u << (4 * i))); }
      cp16p(dd, pd, l16 < 256u ? (((l16 & 128u) ? m3 : m2) >> ((l16 >> 2) & 28u)) & 15u : 0u);
      sts32(sb + SM_Z + 40, s);
    }
    n++;
    asm volatile("cp.async.commit_group;\ncp.async.wait_group 0;" ::: "memory");
    __syncwarp();
    asm volatile("{\n.reg .pred p, q;\n.reg .b32 a, b;\n.reg .b16 h, g;\nsetp.ne.u32 p, %4, 0;\n"
                 "@p ld.shared.u32 %2, [%6];\n@p ld.shared.u32 %3, [%6+128];\n@p ld.shared.u32 %0, [%5];\n@p ld.shared.u32 %1, [%5+4096];\n"
                 "lop3.b32 a, %2, %3, 0x42000000, 0x7e;\nlop3.b32 b, %0, %1, 0x42000000, 0x7e;\nor.b32 a, a, b;\nsetp.lt.and.u32 q, a, %8, p;\n"
                 "cvt.u16.u32 h, %2;\ncvt.u16.u32 g, %3;\n@q st.shared.u16 [%5+2], h;\n@q st.shared.u16 [%5+4098], g;\n@q mbarrier.arrive.shared::cta.b64 _, [%7];\n"
                 "@q mov.u32 %4, 0;\n}"
                 : "+r"(c0), "+r"(c1), "+r"(d0), "+r"(d1), "+r"(todo) : "r"(mc), "r"(dc), "r"(sb + SM_BAR + MB_MEM + hf * 8), "r"(n < SPIN_LIMIT ? 0x10000u : ~0u) : "memory");
  } while (__any_sync(~0u, todo));
  return n - 1;
}

__global__ void __cluster_dims__(2, 1, 1) __launch_bounds__(384, 1)
rec_kernel(const __grid_constant__ CUtensorMap tmx, const __grid_constant__ CUtensorMap tmw, const __grid_constant__ WMaps W, RecParams P, const __grid_constant__ SideParams SP) {
  extern __shared__ __align__(1024) unsigned char smem[];
  asm volatile("griddepcontrol.launch_dependents;");
  const uint32_t sb = smem_u32(smem);
  const int tid = threadIdx.x, lane = tid & 31, t128 = tid & 127;
  const int wg = __shfl_sync(~0u, tid >> 7, 0), wq = __shfl_sync(~0u, (tid >> 5) & 3, 0);
  const int r = blockIdx.x & 1, pp = blockIdx.x >> 1;
  const int mi = lane >> 3, r8 = lane & 7;
  const uint32_t xb16 = __shfl_sync(~0u, (((sb + SM_X + (tid >> 7) * 32768 + r * 16384) & 0x3FFFF) >> 4) | (1u << 16), 0);
  const uint32_t va16 = __shfl_sync(~0u, (((sb + SM_WVS + (tid >> 7) * 16384) & 0x3FFFF) >> 4) | (64u << 16), 0);
#if defined(PER) || defined(PRO)
  const uint32_t tstart = gt32();
#endif

  if (tid == 0) {
    mbar_init(sb + SM_BAR + MB_F, 1); mbar_init(sb + SM_BAR + MB_F + 8, 1); mbar_init(sb + SM_BAR + MB_XE0, 2); mbar_init(sb + SM_BAR + MB_XE1, 2); mbar_init(sb + SM_BAR + MB_INIT, 2);
    mbar_init(sb + SM_BAR + MB_MEM, 32); mbar_init(sb + SM_BAR + MB_MEM + 8, 32); for (int i = 0; i < 8; i++) mbar_init(sb + SM_BAR + MB_W + i * 8, 1);
    mbar_init(sb + SM_BAR + MB_XF, 8); mbar_init(sb + SM_BAR + MB_X0, 1); mbar_init(sb + SM_BAR + MB_WO, 1); mbar_init(sb + SM_BAR + MB_VR, 5);
    sts32(sb + SM_Z + 40, ~0u);
    asm volatile("fence.mbarrier_init.release.cluster;" ::: "memory");
  }
  if (tid == 32) {
    asm volatile("prefetch.tensormap [%0];" :: "l"(&W.q) : "memory"); asm volatile("prefetch.tensormap [%0];" :: "l"(&W.k) : "memory");
    asm volatile("prefetch.tensormap [%0];" :: "l"(&W.v) : "memory"); asm volatile("prefetch.tensormap [%0];" :: "l"(&tmx) : "memory");
  }
  if (tid >= 256 && tid < 320) {
    unsigned char* pl = P.win + r * W_2 + (W_UP | (1u << 19) | ((pp >> 5) << 14)) + (pp & 31) * 128 + wq * 4096;
    stg_r1(pl + lane * 4, 0u);
    uint32_t best = 1u << 30;
    if (lane == 0) {
#pragma unroll 1
      for (int rep = 0; rep < NPROBE; rep++) {
        uint32_t dt;
        asm volatile("{\n.reg .u32 a, b, v;\nmov.u32 a, %%clock;\natom.relaxed.gpu.global.exch.b32 v, [%1], 0;\n"
                     "st.volatile.shared.u32 [%2], v;\nmov.u32 b, %%clock;\nsub.u32 %0, b, a;\n}" : "=r"(dt) : "l"(pl), "r"(sb + SM_SIDE + wq * 4) : "memory");
        best = min(best, dt);
      }
    }
    if (lane == 0) sts32(sb + SM_SIDE + wq * 4, best);
    bar_sync(B_P, 64);
    if (wq == 0) {
      const uint2 bt = lds64(sb + SM_SIDE);
      if (lane < 8 && (r == 0 || pp == 0)) stg_r1(&g_side[(r ? 66 : pp) * 32 + lane], 2u | (bt.x < bt.y ? 1u : 0u));
      spin(DLY_TB);
      uint32_t a, b, c; int n = 0;
#pragma unroll 1
      do {
        a = ldg_r1(&g_side[lane * 32]); b = ldg_r1(&g_side[(32 + lane) * 32]); c = ldg_r1(&g_side[(64 + min(lane, 2)) * 32]);
      } while (!__all_sync(~0u, a & b & c & 2u) && ++n < SPIN_LIMIT);
      a = __ballot_sync(~0u, a & 1u); b = __ballot_sync(~0u, b & 1u); c = __ballot_sync(~0u, c & 1u);
      const uint32_t pol2 = (a ^ (c >> 2)) & 1u;
      c &= 3u;
      const unsigned long long ab = ((unsigned long long)b << 32) | a;
      const int sd = pp < 64 ? (int)(ab >> pp) & 1 : (int)(c >> (pp - 64)) & 1;
      const int n1 = __popcll(ab) + __popc(c), n0 = 66 - n1;
      const int below1 = pp < 64 ? __popcll(ab & ((1ull << pp) - 1)) : __popcll(ab) + (pp == 65 ? (int)(c & 1u) : 0);
      const int rk = sd ? below1 : pp - below1;
      const int k0 = (n0 & 1) ? n0 - 1 : n0 >= n1 ? n0 - 2 : n0, k1 = 64 - k0;
      const int role = rk >= (sd ? k1 : k0) ? 64 + ((n0 & 1) ? sd : rk - (sd ? k1 : k0)) : sd ? k0 + rk : rk;
      __syncwarp();
      if (lane == 0) sts128(sb + SM_SIDE, 2 * k0, 0u, pol2, role * 2 + r);
#ifdef PER
      if (lane == 0) { atomicMax(&g_end[6], gt32()); atomicMin(&g_end[7], max(bt.x, bt.y) - min(bt.x, bt.y)); }
#endif
    }
  }
  __syncthreads();
  const int cta = __shfl_sync(~0u, (int)lds32(sb + SM_SIDE + 12), 0), h = cta >> 2, j = cta & 3, p = j >> 1;
  const int sw = (cta >= __shfl_sync(~0u, (int)lds32(sb + SM_SIDE), 0) ? 1 : 0) ^ r;
  if (cta >= NCTA) {
    spin(DLY_SIDE);
#ifndef NOSIDE
    side_work(SP, smem, cta - NCTA);
#endif
#ifdef PER
    if (threadIdx.x == 0) atomicMax(&g_end[1], gt32());
#endif
    return;
  }
#ifdef PER
  if (threadIdx.x == 0) g_per[cta][63] = tstart;
#endif
#ifdef PRO
  if (tid == 0) { g_pro[cta][0] = tstart; g_pro[cta][1] = gt32(); }
#endif
  asm volatile("barrier.cluster.arrive.relaxed.aligned;" ::: "memory");
#define WLOAD(i0, i1) _Pragma("unroll 1") for (int u = i0; u < i1; u++) {        \
    const int g2 = u >> 2, i = u & 3, k = g2 * 512 + ((i * 128 + r * 256) & 511); \
    const uint32_t mb = sb + SM_BAR + MB_W + u * 8; \
    mbar_expect_tx(mb, i < 2 ? 32768 : 16384); \
    tma_load_2d(sb + g2 * 65536 + i * 8192, &W.q, h * DH + j * 32, k, mb); \
    tma_load_2d(sb + g2 * 65536 + 32768 + i * 8192, &W.k, h * DH + j * 32, k, mb); \
    if (i < 2) tma_load_2d(sb + (i ? SM_WVS : SM_VST) + g2 * 16384, &W.v, h * DH + p * 64, k, mb); }
  if (tid == 288) {
    mbar_expect_tx(sb + SM_BAR + MB_X0, 32768);
#pragma unroll 1
    for (int i = 0; i < 2; i++)
      asm volatile("cp.async.bulk.tensor.3d.shared::cluster.global.mbarrier::complete_tx::bytes [%0], [%1, {%3, %3, %4}], [%2];"
                   :: "r"(sb + SM_MEM + i * 16384), "l"(&tmx), "r"(sb + SM_BAR + MB_X0), "r"(0), "r"(i * 4) : "memory");
    WLOAD(0, 4 + WSPL);
  }
  __syncwarp();
  asm volatile("barrier.cluster.wait.acquire.aligned;" ::: "memory");
#define SIDES() const uint4 sm2 = lds128(sb + SM_SIDE); const int nlo = sm2.x; const uint32_t me = cta >= nlo

#define XLOAD(t, sg) tma_load_mc(sb + SM_X + ((t) * 8 + r * 4) * 4096, &tmx, (sg) * SEG, (t) * 8 + r * 4, sb + SM_BAR + MB_F + (t) * 8)
#define F0LOAD() do { mbar_wait(sb + SM_BAR + MB_XE0, s & 1); \
    if (l16 == 0) XLOAD(0, s + 2); \
    __syncwarp(); } while (0)
  if (wg < 2) {
    asm volatile("setmaxnreg.inc.sync.aligned.u32 " STR(RF_FAT) ";");
    uint32_t w[32][4], wv[8][4];
    uint32_t lm = ((mi >> 1) * 8 + r8) * 128 + (((wq * 2 + (mi & 1)) ^ r8) << 4), l16 = lane * 16;
    lm = __shfl_sync(~0u, lm, lane); l16 = __shfl_sync(~0u, l16, lane);
    {
      const uint32_t lq0 = sb + wg * 65536 + (wq >> 1) * 32768 + ((mi >> 1) * 8 + r8) * 64 + ((((wq & 1) * 2 + (mi & 1)) ^ (r8 >> 1)) << 4);
      const uint32_t f = wq < 2 ? 0x3D003D00u : 0x3F803F80u;
#pragma unroll
      for (int i = 0; i < 4; i++) {
        mbar_wait(sb + SM_BAR + MB_W + (wg * 4 + i) * 8, 0);
        if (i == 3) PT(2 + wg, t128 == 0);
#pragma unroll
        for (int kk = 8 * i; kk < 8 * i + 8; kk++) ldmatrix_x4_trans(w[kk], lq0 + kk * 1024);
        if (i == 0) {
#pragma unroll
          for (int kk = 0; kk < 8; kk++) ldmatrix_x4_trans(wv[kk], sb + SM_VST + wg * 16384 + kk * 2048 + lm);
        }
#pragma unroll
        for (int kk = 32 * i; kk < 32 * i + 32; kk++) w[kk >> 2][kk & 3] = mulb2v(w[kk >> 2][kk & 3], f);
      }
    }
    if (wg == 0) bar_sync(B_V, 160);
    else bar_arrive(B_P, 160);
    const int w8 = wg * 4 + wq;
    const int cw = sw ^ wg;
    const uint32_t xh16 = xb16 ^ 1024u;
    const uint32_t rsb = mapa(sb, r ^ 1);
#define MT (l16 + (sb + SM_MEM + wg * 8192))
#define WA (lm + (sb + SM_WVS + wg * 16384))
#define WOF(f) (lm + (sb + SM_WOS + wg * 32768 + ((f) & 1) * 16384 + ((f) >> 1) * 2048))
#define TH(base) (l16 + (sb + (base) + w8 * 512))
#define TQ(base) (l16 + (sb + (base) + wq * 512))
#define DUMP(base) _Pragma("unroll") for (int n = 0; n < 4; n++) sts128f(TQ((base) + n * 2048), d[4 * n], d[4 * n + 1], d[4 * n + 2], d[4 * n + 3])
#define INIT(base) _Pragma("unroll") for (int n = 0; n < 4; n++) { const float4 t = lds128f(TQ((base) + n * 2048)); d[4 * n] = t.x; d[4 * n + 1] = t.y; d[4 * n + 2] = t.z; d[4 * n + 3] = t.w; }
#define XQK(first, b0, b1) do { wg_fence(); XR<0, 16, 0, 32, first>::run(d, w, b0); XR<0, 16, 16, 32, 0>::run(d, w, b1); wg_commit(); wg_wait0(); } while (0)
#define XVS(first, b0) do { wg_fence(); XS<8, 8, 16, first>::run(d, va16, b0); XR<0, 8, 0, 8, 0>::run(d, wv, b0); wg_commit(); wg_wait0(); } while (0)
#define XREL(mb) do { if (wq == 0 && l16 == 0) { mbar_arrive_cluster_rlx(rsb + SM_BAR + (mb)); mbar_arrive(sb + SM_BAR + (mb)); } } while (0)
#define XFOUT() do { \
          _Pragma("unroll") for (int hf = 0; hf < 2; hf++) \
            stsm4t(l16 + (sb + SM_XF + (wq * 2 + hf) * 512), pack_bf16(d[8 * hf], d[8 * hf + 1]), pack_bf16(d[8 * hf + 2], d[8 * hf + 3]), \
                   pack_bf16(d[8 * hf + 4], d[8 * hf + 5]), pack_bf16(d[8 * hf + 6], d[8 * hf + 7])); \
          __syncwarp(); \
          if (l16 < 32) mbar_arrive(sb + SM_BAR + MB_XF); } while (0)
#define VDUMP(base) _Pragma("unroll") for (int n = 0; n < 2; n++) sts128(TQ((base) + n * 2048), pack_bf16(d[8 * n], d[8 * n + 1]), pack_bf16(d[8 * n + 2], d[8 * n + 3]), pack_bf16(d[8 * n + 4], d[8 * n + 5]), pack_bf16(d[8 * n + 6], d[8 * n + 7]))

    if (wg == 0) {
      float d[16];
      const uint32_t x0 = (((sb + SM_MEM + r * 16384) & 0x3FFFF) >> 4) | (1u << 16), x1 = (((sb + SM_MEM + (r ^ 1) * 16384) & 0x3FFFF) >> 4) | (1u << 16);
      mbar_wait(sb + SM_BAR + MB_X0, 0);
      XQK(1, x0, x1);
      DUMP(SM_CQ);
      XVS(1, x0);
      bar_arrive(B_X2, 256);
      VDUMP(SM_CV);
      bar_sync(B_CQ, 256);
    } else {
      float d[16];
      bar_sync(B_CQ, 256);
      INIT(SM_CQ);
      mbar_wait(sb + SM_BAR + MB_F + 8, 0);
      PT(4, t128 == 0);
      XQK(0, xb16, xh16);
      XFOUT();
      PT(5, t128 == 0);
    }
#define QA (l16 + (sb + SM_QA + (w8 >> 1) * 512 + (w8 & 1) * 8))
    {
      const uint32_t qa = (((l16 & 0x30u) << 3) | ((l16 & 0x10u) << 2) | ((l16 >> 3) & 0x30u) | ((l16 >> 4) & 4u)) + w8 * 512;
      sts32(QA, qa + (sb + SM_QKP)); sts32(QA + 4, (qa ^ 64u) + (sb + SM_QKP));
    }
    if (wg == 0) mbar_wait(sb + SM_BAR + MB_F, 0);
    for (int s = -1;; s++) {
      if (s >= 0) {
        OPAQUE_R(lm); OPAQUE_R(l16);
        {
          uint32_t sa[4][4];
#pragma unroll
          for (int i = 0; i < 2; i++) ldmatrix_x4_trans(sa[i], WA + i * 2048);
          float a[2][4], v[2][4]; uint4 c[4]; uint2 qa;
          FENCE();
          mbar_wait(sb + SM_BAR + MB_MEM + wg * 8, s & 1);
#define QP(i) ((i) >= 12 ? (i) - 8 : (i) % 3 == 1 ? (i) / 3 : 8 + (i) - ((i) + 2) / 3)
#pragma unroll
          for (int i = 0; i < 3; i++) c[i] = ldsm4t(MT + QP(i) * 512);
#pragma unroll
          for (int i = 0; i < 16; i++) {
            if (i + 3 < 16) c[(i + 3) & 3] = ldsm4t(MT + QP(i + 3) * 512);
            if (i == 13) qa = lds64(QA);
            if (i == 0) {
              mma4z(a[0], w[2 * QP(i)][0], w[2 * QP(i)][1], w[2 * QP(i)][2], w[2 * QP(i)][3], c[i & 3].x, c[i & 3].y);
              mma4z(a[1], w[2 * QP(i) + 1][0], w[2 * QP(i) + 1][1], w[2 * QP(i) + 1][2], w[2 * QP(i) + 1][3], c[i & 3].z, c[i & 3].w);
            } else {
              mma_16816(a[0], w[2 * QP(i)], c[i & 3].x, c[i & 3].y);
              mma_16816(a[1], w[2 * QP(i) + 1], c[i & 3].z, c[i & 3].w);
            }
            if (QP(i) == 0) {
              mma4z(v[0], wv[0][0], wv[0][1], wv[0][2], wv[0][3], c[i & 3].x, c[i & 3].y);
              mma4z(v[1], wv[1][0], wv[1][1], wv[1][2], wv[1][3], c[i & 3].z, c[i & 3].w);
            } else if (QP(i) < 4) {
              mma_16816(v[0], wv[2 * (QP(i) & 3)], c[i & 3].x, c[i & 3].y);
              mma_16816(v[1], wv[2 * (QP(i) & 3) + 1], c[i & 3].z, c[i & 3].w);
            }
            if (i == 12) {
              mma_16816(v[0], sa[0], c[0].x, c[0].y); mma_16816(v[1], sa[1], c[0].z, c[0].w);
            }
            if (i == 13) { ldmatrix_x4_trans(sa[0], WA + 2 * 2048); ldmatrix_x4_trans(sa[1], WA + 3 * 2048); ldmatrix_x4_trans(sa[2], WA + 4 * 2048); }
            FENCE();
          }
#pragma unroll
          for (int i = 0; i < 4; i++) sts32(((i & 1) ? qa.y : qa.x) + (i >> 1) * 8, f2u(a[0][i] + a[1][i]));
          bar_arrive(B_QK, 288);
          bar_arrive(B_QK1, 288);
          FENCE();
          uint32_t sc2[4];
          ldmatrix_x4_trans(sa[3], WA + 5 * 2048); ldmatrix_x4_trans(sc2, WA + 6 * 2048);
          mma_16816(v[0], sa[0], c[1].x, c[1].y); mma_16816(v[1], sa[1], c[1].z, c[1].w);
          FENCE();
          ldmatrix_x4_trans(sa[0], WA + 7 * 2048);
          FENCE();
          mma_16816(v[0], sa[2], c[2].x, c[2].y); mma_16816(v[1], sa[3], c[2].z, c[2].w);
          mma_16816(v[0], sc2, c[3].x, c[3].y); mma_16816(v[1], sa[0], c[3].z, c[3].w);
          FENCE();
          sts128f(TH(SM_VP), v[0][0] + v[1][0], v[0][1] + v[1][1], v[0][2] + v[1][2], v[0][3] + v[1][3]);
          bar_arrive(B_V, 320);
        }
        if (s == NSEG - 1) break;
        OPAQUE_R(lm); OPAQUE_R(l16);
        uint32_t wo[WPF][4];
        {
          float d[16];
#define XOUT(g) _Pragma("unroll") for (int n = 0; n < 2; n++) sts128f(TQ(SM_CQ + ((g) * 2 + n) * 2048), d[8 - 8 * (g) + 4 * n], d[9 - 8 * (g) + 4 * n], d[10 - 8 * (g) + 4 * n], d[11 - 8 * (g) + 4 * n])
#define XIN(g) do { \
            const float4 t0 = lds128f(TQ(SM_CQ + (2 - 2 * (g)) * 2048)), t1 = lds128f(TQ(SM_CQ + (3 - 2 * (g)) * 2048)); \
            stsm4t(l16 + (sb + SM_XF + (wq * 2 + (g)) * 512), pack_bf16(d[8 * (g)] + t0.x, d[8 * (g) + 1] + t0.y), pack_bf16(d[8 * (g) + 2] + t0.z, d[8 * (g) + 3] + t0.w), \
                   pack_bf16(d[8 * (g) + 4] + t1.x, d[8 * (g) + 5] + t1.y), pack_bf16(d[8 * (g) + 6] + t1.z, d[8 * (g) + 7] + t1.w)); } while (0)
          if (wg == 0) {
            INIT(SM_CW);
            bar_sync(B_PUB, 320);
            wg_fence();
            XR<KB, 16, 0, 32, 0>::run(d, w, xb16); XR<0, 16, 16, 32, 0>::run(d, w, xh16);
            wg_commit(); wg_wait0();
            TSF(13, 1);
            OPAQUE_R(l16);
            XOUT(0);
            bar_arrive(B_G1, 256);
            XREL(MB_XE0);
            bar_sync(B_CQ, 256);
            XIN(0);
#pragma unroll
            for (int f = 0; f < WPA; f++) ldmatrix_x4_trans(wo[f], WOF(f));
          } else {
            const uint32_t ok = mbar_test(sb + SM_BAR + MB_F + 8, (s + 1) & 1);
            bar_sync(B_PUB, 320);
            if (!ok) mbar_wait(sb + SM_BAR + MB_F + 8, (s + 1) & 1);
            wg_fence();
            XR<0, 16, 0, 32, 1>::run(d, w, xb16); XR<0, 16 - WPP, 16, 32, 0>::run(d, w, xh16);
            wg_commit();
            XR<16 - WPP, 16, 16, 32, 0>::run(d, w, xh16);
            wg_commit();
            asm volatile("wgmma.wait_group.sync.aligned 1;" ::: "memory");
#pragma unroll
            for (int f = 0; f < WPA; f++) ldmatrix_x4_trans(wo[f], WOF(f));
            wg_wait0();
            TSF(31, 5);
            OPAQUE_R(l16);
            XOUT(1);
            bar_arrive(B_CQ, 256);
            bar_sync(B_G1, 256);
            XIN(1);
          }
          __syncwarp();
          if (l16 == 0) mbar_arrive(sb + SM_BAR + MB_XF);
          TSF(3, 5);
        }
        if (s == 0) {
          mbar_wait(sb + SM_BAR + MB_WO, 0);
#pragma unroll
          for (int f = 0; f < WPA; f++) ldmatrix_x4_trans(wo[f], WOF(f));
        }
#pragma unroll
        for (int f = WPA; f < WPF; f++) ldmatrix_x4_trans(wo[f], WOF(f));
        unsigned char* pa = P.win + (w_ar(s) + (j * 32 + cw * 16 + wq * 2) * 256 + (l16 >> 2));
        uint32_t ce = (l16 >> 4) - 4 * (cw * 4 + wq);
        OPAQUE_L(pa); OPAQUE_R(ce);
        FENCE();
        bar_sync(wg ? B_O : B_O2, wg ? 192 : 224);
        uint4 ob[2];
        ob[0] = ldsm4(l16 + (sb + SM_OF)); ob[1] = ldsm4(l16 + (sb + SM_OF + 512));
        float acc[2][4]; uint32_t f0ok;
#pragma unroll
        for (int f = 0; f < 16; f++) {
          const int ks = f >> 1;
          const uint32_t b0 = (ks & 1) ? ob[(ks >> 1) & 1].z : ob[(ks >> 1) & 1].x, b1 = (ks & 1) ? ob[(ks >> 1) & 1].w : ob[(ks >> 1) & 1].y;
          if (f < 2) mma4z(acc[f], wo[f][0], wo[f][1], wo[f][2], wo[f][3], b0, b1);
          else mma_16816(acc[f % 2], wo[f < WPF ? f : 2 + (f - WPF) % (WPF - 2)], b0, b1);
          if (f - 1 >= 2 && f - 1 + (WPF - 2) < 16) {
            const int nf = f - 1 + (WPF - 2);
            ldmatrix_x4_trans(wo[2 + (nf - WPF) % (WPF - 2)], WOF(nf));
          }
          if (f == 4 || f == 8) ob[((f >> 2) - 1) & 1] = ldsm4(l16 + (sb + SM_OF + (1 + (f >> 2)) * 512));
          if (f == 12) f0ok = mbar_test(sb + SM_BAR + MB_F, (s + 1) & 1);
          if (f < 15) FENCE();
        }
        if (!wg) bar_arrive(B_CV, 256);
        red_bf2(pa, pack_bf16(acc[0][0], ce == 0 ? 1.f : acc[0][1])); red_bf2(pa + 256, pack_bf16(acc[0][2], ce == 1 ? 1.f : acc[0][3]));
        red_bf2(pa + 2048, pack_bf16(acc[1][0], ce == 2 ? 1.f : acc[1][1])); red_bf2(pa + 2304, pack_bf16(acc[1][2], ce == 3 ? 1.f : acc[1][3]));
        red_bf2p4(pa + (W_DS + (wq & 1) * 256), pack_bf16(ce == 0 ? acc[0][1] : ce == 1 ? acc[0][3] : ce == 2 ? acc[1][1] : acc[1][3], 1.f), ce);
        TSF(4, 1); TSF(2, 6);
        if (wg) bar_sync(B_CV, 256);
        else if (!f0ok) mbar_wait(sb + SM_BAR + MB_F, (s + 1) & 1);
      }
      OPAQUE_R(lm); OPAQUE_R(l16);
      {
        float d[16];
        const uint32_t cv = TQ(SM_CV + ((s ^ wg) & 1) * 4096);
        TSF(9, 1);
        wg_fence();
        XV<0, 0, 0>::run(d, wv, va16, xb16);
        wg_commit(); wg_wait0();
        uint32_t q[8];
#pragma unroll
        for (int i = 0; i < 8; i++) q[i] = pack_bf16(d[2 * i], d[2 * i + 1]);
        if (wg == 0) {
          sts128(cv, q[0], q[1], q[2], q[3]); sts128(cv + 2048, q[4], q[5], q[6], q[7]);
          wg_fence(); XR<0, KB, 0, 32, 1>::run(d, w, xb16); wg_commit(); wg_wait0();
          OPAQUE_R(l16);
          DUMP(SM_CW);
          TSF(5, 1);
        } else {
          const uint4 o = lds128(cv + (r ^ 1) * 2048), k = lds128(cv + r * 2048);
          XREL(MB_XE1);
          st_async4(l16 + (rsb + SM_VR + wq * 512), u2f(addb2(r ? q[0] : q[4], o.x)), u2f(addb2(r ? q[1] : q[5], o.y)), u2f(addb2(r ? q[2] : q[6], o.z)), u2f(addb2(r ? q[3] : q[7], o.w)),
                    rsb + SM_BAR + MB_VR);
          sts128(TQ(SM_VL), addb2(r ? q[4] : q[0], k.x), addb2(r ? q[5] : q[1], k.y), addb2(r ? q[6] : q[2], k.z), addb2(r ? q[7] : q[3], k.w));
          __syncwarp();
          if (l16 == 0) mbar_arrive(sb + SM_BAR + MB_VR);
          TSF(28, 5);
        }
      }
    }
  } else {
    asm volatile("setmaxnreg.dec.sync.aligned.u32 " STR(RF_CTL) ";");
    const int g = lane >> 2, tq = lane & 3;
    if (wq == 0) {
      if (lane < 12) asm volatile("prefetch.global.L2 [%0];" :: "l"(SP.x + (size_t)(cta * 12 + lane) * 64));
      __syncwarp();
      {
        SIDES();
        const uint32_t o[6] = {w_blk(w_h1(cta), me), w_blk(w_h1(cta) ^ H1_V, me), w_blk(w_mvx(cta, 0), me ^ sm2.z), w_blk(w_mvx(cta, 1), me ^ sm2.z),
                               w_blk(w_mxa(cta, 0), me ^ sm2.z), w_blk(w_mxa(cta, 1), me ^ sm2.z)};
#pragma unroll
        for (int i = 0; i < 24; i++) stg_r4(P.win + (o[i >> 2] + (i & 3) * 512 + lane * 16), 0u, 0u, 0u, 0u);
#pragma unroll
        for (int i = 0; i < 6; i++) stg_r1(P.win + (w_ar(i >> 1) + cta * 256 + (i & 1) * W_DS + lane * 4), 0u);
        __threadfence();
        __syncwarp();
      }
      {
        const uint32_t wv = movm(*reinterpret_cast<const uint32_t*>(P.mem0 + g * DM + cta * 8 + tq * 2));
        const bool sp = lane == cnt_word(cta & 31);
        stg_r1(P.win + (w_ar(-1) + cta * 256 + lane * 4), sp ? (wv & 0xffffu) | 0x42000000u : wv);
        if (sp) stg_r1(P.win + (w_ar(-1) + ((cta & ~9) + ((cta >> 1) & 1)) * 256 + W_DS + lane * 4), (wv >> 16) | 0x42000000u);
      }
      bar_sync(B_V, 160);
      if (lane == 0) {
        fence_async_smem(); mbar_arrive_cluster_rlx(mapa(sb + SM_BAR + MB_INIT, 0)); mbar_arrive_cluster_rlx(mapa(sb + SM_BAR + MB_INIT, 1));
        mbar_wait(sb + SM_BAR + MB_INIT, 0);
        mbar_expect_tx(sb + SM_BAR + MB_F, 32768);
        mbar_expect_tx(sb + SM_BAR + MB_F + 8, 32768);
        XLOAD(1, 0); XLOAD(0, 1);
        WLOAD(4 + WSPL, 8);
      }
      __syncwarp();
#ifdef PER
      if (lane == 0) atomicMax(&g_end[5], gt32());
#endif
    }
    bar_sync(B_X2, 256);
    SIDES();
    uint32_t l16 = __shfl_sync(~0u, lane * 16, lane);
    const uint32_t me2 = me ^ sm2.z;
    const float sc = 32.f * 0.08838834764831845f * 1.4426950408889634f;
    uint32_t ls = l16 + sb;
#define PVM(o, zs, p0, p2) do { \
        FENCE(); \
        mma4z(zs, 0x3F803F80u, 0x3F803F80u, 0x3F803F80u, 0x3F803F80u, p0.x, p0.y); \
        FENCE(); \
        _Pragma("unroll") for (int t = 0; t < 4; t++) mma4z(o[t], va[2 * t].x, va[2 * t].y, va[2 * t].z, va[2 * t].w, p0.x, p0.y); \
        FENCE(); \
        mma4(zs, 0x3F803F80u, 0x3F803F80u, 0x3F803F80u, 0x3F803F80u, p0.z, p0.w); \
        _Pragma("unroll") for (int t = 0; t < 2; t++) mma4(o[t], va[2 * t + 1].x, va[2 * t + 1].y, va[2 * t + 1].z, va[2 * t + 1].w, p0.z, p0.w); \
        FENCE(); \
        mma_1688(zs, 0x3F803F80u, 0x3F803F80u, p2); \
        _Pragma("unroll") for (int t = 2; t < 4; t++) mma4(o[t], va[2 * t + 1].x, va[2 * t + 1].y, va[2 * t + 1].z, va[2 * t + 1].w, p0.z, p0.w); \
        mma_1688(o[0], vm[0].x, vm[0].y, p2); mma_1688(o[1], vm[0].z, vm[0].w, p2); mma_1688(o[2], vm[1].x, vm[1].y, p2); mma_1688(o[3], vm[1].z, vm[1].w, p2); } while (0)
#define PVE(o, z, dst) do { \
        const float i0 = rcpf(z[0]), i1 = rcpf(z[1]); \
        _Pragma("unroll") for (int u = 0; u < 2; u++) \
          stsm4t((dst) + u * 1024, pack_bf16(o[2 * u][0] * i0, o[2 * u][1] * i1), pack_bf16(o[2 * u][2] * i0, o[2 * u][3] * i1), \
                 pack_bf16(o[2 * u + 1][0] * i0, o[2 * u + 1][1] * i1), pack_bf16(o[2 * u + 1][2] * i0, o[2 * u + 1][3] * i1)); } while (0)
    const uint32_t lq = (l16 ^ ((l16 >> 1) & 64u)) + sb, l12 = (l16 >> 2) * 3;
#define M3PTR(sl) \
            const uint32_t tf = me ^ 1 ^ r, m3i = w_ar(sl) + (wq & 1) * 16384 + (l16 & 0x70u) + ((l16 & 0x180u) << 1); \
            const unsigned char* p0f = P.win + (m3i + r * 8192 + tf * 4096); const unsigned char* p0n = P.win + (m3i + r * 8192 + (tf ^ 1) * 4096); \
            const unsigned char* p1f = P.win + (m3i + (r ^ 1) * 8192 + (tf ^ 1) * 4096); const unsigned char* p1n = P.win + (m3i + (r ^ 1) * 8192 + tf * 4096); \
            const unsigned char* pd = P.win + (w_ar(sl) + (wq & 1) * 16384 + (((l16 >> 7) ^ r) & 1u) * 8192 + ((l16 & 64u) * 4 + (l16 & 48u) * 2 + (l16 & 16u)) * 16 + W_DS + (l16 & 0x70u)); \
            uint32_t mf = ls + SM_MEM + (wq & 1) * 8192 + tf * 2048, mn = ls + SM_MEM + (wq & 1) * 8192 + (tf ^ 1) * 2048, nr = l16 < 256u ? 1u + (((l16 >> 6) ^ (l16 >> 7) ^ tf) & 1u) : 0u; \
            OPAQUE_L(p0f); OPAQUE_L(p0n); OPAQUE_L(p1f); OPAQUE_L(p1n); OPAQUE_L(pd); OPAQUE_R(mf); OPAQUE_R(mn); OPAQUE_R(nr); FENCE()
#define M3REQ() \
            _Pragma("unroll") for (int i = 0; i < 4; i++) { cp16(mn + 4096 + i * 512, p1f + i * 1024); cp16(mf + i * 512, p0f + i * 1024); } \
            cp16p(ls + SM_RD + (wq & 1) * 256, pd, nr & 1u); \
            _Pragma("unroll") for (int i = 0; i < 4; i++) { cp16(mf + 4096 + i * 512, p1n + i * 1024); cp16(mn + i * 512, p0n + i * 1024); } \
            cp16p(ls + SM_RD + (wq & 1) * 256, pd, nr & 2u)
    if (wq >= 2) { M3PTR(-1); M3REQ(); }
    if (wq == 0) {
      bar_sync(B_P, 160);
      if (l16 == 0) {
        fence_async_smem();
        mbar_expect_tx(sb + SM_BAR + MB_WO, 65536);
        for (int i = 0; i < 8; i++) tma_load_2d(sb + SM_WOS + i * 8192, &tmw, j * 256 + ((i >> 1) ^ (2 * sw)) * 64, h * DH + (i & 1) * 64, sb + SM_BAR + MB_WO);
      }
      __syncwarp();
    }
#define ETA(k, first) ETAT(gt32() + (k), first)
#define ETAT(tm, first) do { unsigned char* pt = P.win + (w_ar(s) + (W_DS + 256) + (cta >> 5) * 8192 + ((cta >> 4) & 1) * 2048 + (l16 & 16u) * 256); \
          asm volatile("{\n.reg .pred q;\nsetp.lt.u32 q, %2, 32;\n@q red.relaxed.gpu.global.max.u32 [%0+4], %1;\n}" :: "l"(pt), "r"(tm), "r"(l16) : "memory"); \
          if (first) asm volatile("{\n.reg .pred q;\nsetp.lt.u32 q, %1, 32;\n@q red.relaxed.gpu.global.add.u32 [%0], 1;\n}" :: "l"(pt), "r"(l16) : "memory"); } while (0)
    if (wq == 1) {
      const uint32_t xin = w_blk(w_mxa(cta, 0), me2) + l16;
      const uint32_t lsq = sb + ((l16 & 0x70u) | ((l16 & 0x80u) << 1) | ((l16 & 0x100u) >> 1));
      mbar_wait(sb + SM_BAR + MB_MEM, 0); mbar_wait(sb + SM_BAR + MB_MEM + 8, 0);
      for (int s = 0; s < NSEG; s++) {
        const uint32_t t2 = ((s >> 1) & 1) ^ 1;
        mbar_wait(sb + SM_BAR + MB_XF, s & 1);
        {
        uint4 kx[4], qx[4];
#pragma unroll
        for (int i = 0; i < 4; i++) { kx[i] = ldsm4(ls + (SM_XF + (4 + i) * 512)); qx[i] = ldsm4(lsq + (SM_XF + i * 512)); }
        const uint32_t db = w_blk(w_mxa(h * 4, s), me2) + l16 - 512;
        {
          float S[2][4][4];
          FENCE();
#pragma unroll
          for (int mt = 0; mt < 2; mt++) {
            const uint4 q0 = qx[mt];
            mma4z(S[mt][0], q0.x, q0.y, q0.z, q0.w, kx[0].x, kx[0].y); mma4z(S[mt][1], q0.x, q0.y, q0.z, q0.w, kx[0].z, kx[0].w);
            if (mt) { mma4z(S[mt][2], q0.x, q0.y, q0.z, q0.w, kx[1].x, kx[1].y); mma4z(S[mt][3], q0.x, q0.y, q0.z, q0.w, kx[1].z, kx[1].w); }
          }
#pragma unroll
          for (int mt = 0; mt < 2; mt++) {
            const uint4 q1 = qx[2 + mt];
            mma4(S[mt][0], q1.x, q1.y, q1.z, q1.w, kx[2].x, kx[2].y); mma4(S[mt][1], q1.x, q1.y, q1.z, q1.w, kx[2].z, kx[2].w);
            if (mt) { mma4(S[mt][2], q1.x, q1.y, q1.z, q1.w, kx[3].x, kx[3].y); mma4(S[mt][3], q1.x, q1.y, q1.z, q1.w, kx[3].z, kx[3].w); }
          }
          FENCE();
          if (s > 0) bar_arrive(B_O2, 224);
          FENCE();
#pragma unroll
          for (int u = 0; u < 4; u++) {
            const int mt = u >> 1, c = 2 * (u & 1);
            const uint32_t m0 = tagw(pack_f16(S[mt][0][c], S[mt][0][c + 1]), t2), m1 = pack_f16(S[mt][1][c], S[mt][1][c + 1]),
                           m2 = mt ? pack_f16(S[mt][2][c], S[mt][2][c + 1]) : 0u, m3 = mt ? pack_f16(S[mt][3][c], S[mt][3][c + 1]) : 0u;
            const int e = u ^ j;
            if (e) stg_r4(P.win + (db + mt * 16384 + (u & 1) * 2048 + e * 512), m0, m1, m2, m3);
            else sts128(ls + SM_XS, m0, m1, m2, m3);
          }
        }
        TS(15);
        float sx[10];
        const unsigned char* pa = P.win + (xin + ((s & 1) << 20));
        uint4 xv[3];
        if (s > 0) spin(DLY_XD);
#pragma unroll
        for (int i = 0; i < 3; i++) xv[i] = ldg_r4(pa + i * 512);
        FENCE();
        int n = 0; float mx;
        auto xsum = [&]() {
#pragma unroll 1
        while (__any_sync(~0u, (x3(xv[0].x, xv[1].x, t2) | (xv[2].x ^ t2)) & 1u) && ++n < SPIN_LIMIT) {
#pragma unroll
          for (int i = 0; i < 3; i++) xv[i] = ldg_r4(pa + i * 512);
        }
        {
          const uint4 v3 = lds128(ls + SM_XS);
          sum_h4(sx[2], sx[3], xv[0].x, xv[1].x, xv[2].x, v3.x); sum_h4(sx[4], sx[5], xv[0].y, xv[1].y, xv[2].y, v3.y);
          sum_h4(sx[6], sx[7], xv[0].z, xv[1].z, xv[2].z, v3.z); sum_h4(sx[8], sx[9], xv[0].w, xv[1].w, xv[2].w, v3.w);
          const int row = 8 * j + g - 2 * tq;
#pragma unroll
          for (int i = 0; i < 8; i++) if ((i >> 1) * 8 + (i & 1) > row) sx[2 + i] = -INFINITY;
        }
        mx = fmaxf(fmaxf(fmaxf(sx[2], sx[3]), fmaxf(sx[4], sx[5])), fmaxf(fmaxf(sx[6], sx[7]), fmaxf(sx[8], sx[9])));
        };
        if (s > 0) xsum();
        else {
#pragma unroll
          for (int i = 2; i < 10; i++) sx[i] = 0.f;
          mx = 0.f;
        }
        sts32(ls - l12 + SM_XS + 512, f2u(mx));
        {
          if (l16 == 0) mbar_expect_tx(sb + SM_BAR + MB_VR, 2048);
          unsigned char* d = P.win + (w_blk(w_mvx(cta, s), me2) + l16);
          OPAQUE_L(d); FENCE();
          mbar_wait(sb + SM_BAR + MB_VR, s & 1);
#pragma unroll
          for (int t = 0; t < 4; t++) {
            const uint4 a0 = lds128(ls + (SM_VL + t * 512)), a1 = lds128(ls + (SM_VR + t * 512));
            stg_r4(d + t * 512, tagw(addb2(a0.x, a1.x), t2), addb2(a0.y, a1.y), addb2(a0.z, a1.z), addb2(a0.w, a1.w));
          }
          TS(23);
        }
        unsigned char* pm = P.win + (db + 2048 + j * 128 - l12);
        const unsigned char* py = pa + 1536 - l12;
        OPAQUE_L(pm); OPAQUE_L(py);
        if (s > 0) bar_sync(B_PXF, 96);
        FENCE();
        bar_sync(B_QK1, 288);
        uint32_t kb[2][2];
#pragma unroll
        for (int t = 0; t < 2; t++) {
          const float4 u = lds128f(lq + (SM_QKP + (2 + t) * 512)), v4 = lds128f(lq + (SM_QKP + 2048 + (2 + t) * 512));
          kb[t][0] = pack_bf16(u.x + v4.x, u.y + v4.y); kb[t][1] = pack_bf16(u.z + v4.z, u.w + v4.w);
        }
        float S[2][4];
#pragma unroll
        for (int mt = 0; mt < 2; mt++) mma4z(S[mt], qx[mt].x, qx[mt].y, qx[mt].z, qx[mt].w, kb[0][0], kb[0][1]);
#pragma unroll
        for (int mt = 0; mt < 2; mt++) mma4(S[mt], qx[2 + mt].x, qx[2 + mt].y, qx[2 + mt].z, qx[2 + mt].w, kb[1][0], kb[1][1]);
        PT(14, s == 0 && l16 == 0);
        PT(15, s == 0 && l16 == 0);
        if (s < NSEG - 1) bar_arrive(B_PUB, 320);
        FENCE();
#pragma unroll
        for (int u = 0; u < 4; u++) stg_r1(pm + (u >> 1) * 16384 + (u & 1) * 2048, tagw(pack_f16(S[u >> 1][2 * (u & 1)], S[u >> 1][2 * (u & 1) + 1]), t2));
        TS(30);
        FENCE();
        if (s == 0) xsum();
        spin(DLY_XL);
        uint32_t xy[4];
#pragma unroll
        for (int i = 0; i < 4; i++) xy[i] = ldg_r1(py + i * 128);
        FENCE();

        n = 0;
#pragma unroll 1
        while (__any_sync(~0u, (x3(xy[0], xy[1], t2) | x3(xy[2], xy[3], t2)) & 1u) && ++n < SPIN_LIMIT) {
#pragma unroll
          for (int i = 0; i < 4; i++) xy[i] = ldg_r1(py + i * 128);
        }
        sum_h4(sx[0], sx[1], xy[0], xy[1], xy[2], xy[3]);
        mx = fmaxf(mx, fmaxf(sx[0], sx[1]));
        mx = fmaxf(fmaxf(mx, __shfl_xor_sync(~0u, mx, 1)), fmaxf(__shfl_xor_sync(~0u, mx, 2), __shfl_xor_sync(~0u, mx, 3)));
#pragma unroll
        for (int i = 0; i < 10; i++) sx[i] = ex2(fmaf(sx[i], sc, -sc * mx));
        sts128(ls + SM_PX, pack_bf16(sx[2], sx[3]), pack_bf16(sx[4], sx[5]), pack_bf16(sx[6], sx[7]), pack_bf16(sx[8], sx[9]));
        sts32(ls - l12 + SM_PX + 512, pack_bf16(sx[0], sx[1]));
        bar_arrive(B_PX, 96);
        TS(1);
        }
      }
    } else {
      const uint32_t ho = (wq & 1) * 512 + l16, hv = wq == 0 ? 0u : H1_V;
      uint32_t ow = w_blk(w_h1(cta) ^ hv, me) + ho, or0 = w_blk(w_h1(cta ^ 1) ^ hv, me) + ho, or1 = w_blk(w_h1((cta ^ 2) & ~1) ^ hv, me) + ho;
#define PTRS() OPAQUE_R(ow); OPAQUE_R(or0); OPAQUE_R(or1); \
      unsigned char* pw0 = P.win + ow; const unsigned char* pr0 = P.win + or0; const unsigned char* pr1 = P.win + or1; \
      OPAQUE_L(pw0); OPAQUE_L(pr0); OPAQUE_L(pr1); FENCE()
      if (wq == 0) {
        const uint32_t xcnt = me ? NCTA - nlo : nlo, xrank = (me ? cta - nlo : cta) + lane * xcnt;
        int kd = DLY_K;
        mbar_wait(sb + SM_BAR + MB_XE1, 0);
        if (l16 == 0) { mbar_expect_tx(sb + SM_BAR + MB_F + 8, 32768); XLOAD(1, 1); }
        __syncwarp();
        for (int s = 0; s < NSEG - 1; s++) {
          const uint32_t tg = (s & 1) ^ 1;
          mbar_wait(sb + SM_BAR + MB_XF, s & 1);
          uint4 xf[4];
#pragma unroll
          for (int i = 0; i < 4; i++) xf[i] = ldsm4(ls + (SM_XF + (4 + i) * 512));
          FENCE();
          if (s > 0) {
            mbar_wait(sb + SM_BAR + MB_XE1, s & 1);
            if (l16 == 0) mbar_expect_tx(sb + SM_BAR + MB_F + 8, 32768);
            mbar_wait(sb + SM_BAR + MB_MEM, s & 1); mbar_wait(sb + SM_BAR + MB_MEM + 8, s & 1);
            if (l16 == 0) XLOAD(1, s + 1);
            __syncwarp();
          }
          kd = lds32(sb + SM_Z + 40) == (uint32_t)s && s ? min(kd + KU, DLY_K + 256) : max(kd - KD, DLY_K);
          kd = __shfl_sync(~0u, kd, l16 >> 4);
#ifdef PER
          if (l16 == 0) { g_per[cta][max(s - 1, 0)] = gt32(); g_pclk[cta][max(s - 1, 0)] = clk32(); g_pk[cta][max(s - 1, 0)] = kd - DLY_K; }
#endif
          PTRS();
          unsigned char* pw1 = pw0 + 512 - l12; OPAQUE_L(pw1);
          bar_sync(B_QK, 288);
          float4 u[4], v4[4];
#pragma unroll
          for (int t = 0; t < 4; t++) { u[t] = lds128f(lq + (SM_QKP + t * 512)); v4[t] = lds128f(lq + (SM_QKP + 2048 + t * 512)); }
          FENCE();
          uint32_t f[4][2], m[5];
#pragma unroll
          for (int t = 0; t < 2; t++) { f[t][0] = pack_bf16(u[t].x + v4[t].x, u[t].y + v4[t].y); f[t][1] = pack_bf16(u[t].z + v4[t].z, u[t].w + v4[t].w); }
          float S[5][4], T[5][4];
          mma4z(S[1], f[0][0], f[1][0], f[0][1], f[1][1], xf[0].x, xf[0].y); mma4z(T[1], f[0][0], f[1][0], f[0][1], f[1][1], xf[2].x, xf[2].y);
          mma4z(S[2], f[0][0], f[1][0], f[0][1], f[1][1], xf[0].z, xf[0].w); mma4z(T[2], f[0][0], f[1][0], f[0][1], f[1][1], xf[2].z, xf[2].w);
          FENCE();
#pragma unroll
          for (int t = 2; t < 4; t++) { f[t][0] = packv(u[t].x, v4[t].x, u[t].y, v4[t].y); f[t][1] = packv(u[t].z, v4[t].z, u[t].w, v4[t].w); }
          mma4z(S[3], f[0][0], f[1][0], f[0][1], f[1][1], xf[1].x, xf[1].y); mma4z(T[3], f[0][0], f[1][0], f[0][1], f[1][1], xf[3].x, xf[3].y);
          mma4z(S[4], f[0][0], f[1][0], f[0][1], f[1][1], xf[1].z, xf[1].w); mma4z(T[4], f[0][0], f[1][0], f[0][1], f[1][1], xf[3].z, xf[3].w);
          FENCE();
          mma4z(S[0], f[0][0], f[1][0], f[0][1], f[1][1], f[2][0], f[2][1]); mma4z(T[0], f[0][0], f[1][0], f[0][1], f[1][1], f[3][0], f[3][1]);
          bar_arrive(B_PUB, 320);
          FENCE();
#pragma unroll
          for (int i = 1; i < 5; i++) m[i] = packh(S[i][0], T[i][2], S[i][1], T[i][3]);
          m[1] = tagw(m[1], tg);
          stg_r4(pw0, m[1], m[2], m[3], m[4]);
          FENCE();
          m[0] = tagw(packh(S[0][0], T[0][2], S[0][1], T[0][3]), tg);
          stg_r1(pw1, m[0]);
          TS(6); PT(11, s == 0 && l16 == 0);
          FENCE();
          const uint32_t ts = clk32();
          uint32_t te = gt32() + kd;
          const unsigned char* py0 = pr0 + 512 - l12; const unsigned char* py1 = pr1 + 512 - l12;
          OPAQUE_L(py0); OPAQUE_L(py1);
          unsigned char* pt = P.win + (w_ar(s) + (W_DS + 256) + (cta >> 5) * 8192 + ((cta >> 4) & 1) * 2048 + (l16 & 16u) * 256);
          OPAQUE_L(pt);
          if (l16 == 0) mbar_expect_tx(sb + SM_BAR + MB_F, s < NSEG - 2 ? 32768 : 0);
          FENCE();
          while (clk32() - ts < (uint32_t)DLY_S) {}
          {
            float sx[10]; uint32_t x, x1, x2, x3_; int n = 0; bool bad;
#pragma unroll 1
            do {
              uint4 v[3]; uint32_t y[3], t[5];
              v[0] = ldg_r4(pr0); v[1] = ldg_r4(pr1); v[2] = ldg_r4(pr1 + 2048);
              y[0] = ldg_r1(py0); y[1] = ldg_r1(py1); y[2] = ldg_r1(py1 + 2048);
              if (n) te = gt32() + DLY_KS;
              eta2(pt, te, n == 0, l16);
              n++;
              FENCE();
#define Q3(o, a, b, c) hadd2(hadd2(o, a), hadd2(b, c))
              t[1] = Q3(m[1], v[0].x, v[1].x, v[2].x); t[2] = Q3(m[2], v[0].y, v[1].y, v[2].y); t[3] = Q3(m[3], v[0].z, v[1].z, v[2].z); t[4] = Q3(m[4], v[0].w, v[1].w, v[2].w);
              t[0] = Q3(m[0], y[0], y[1], y[2]);
              bad = __any_sync(~0u, or3(x3(v[0].x, v[1].x, tg), x3(v[2].x, y[0], tg), x3(y[1], y[2], tg)) & (n < SPIN_LIMIT ? 1u : 0u));
              x = hmax2(hmax2(hmax2(t[1], t[2]), hmax2(t[3], t[4])), t[0]);
              const float2 xm = __half22float2(*reinterpret_cast<__half2*>(&x));
              x = f2u(fmaxf(xm.x, xm.y) * -sc);
              x1 = shfl_x(x, 1); x2 = shfl_x(x, 2); x3_ = shfl_x(x, 3);
              FENCE();
#pragma unroll
              for (int i = 1; i < 6; i++) {
                h2f(sx[2 * (i % 5)], sx[2 * (i % 5) + 1], t[i % 5]);
                sx[2 * (i % 5)] = ex2v(sx[2 * (i % 5)], sc, u2f(x)); sx[2 * (i % 5) + 1] = ex2v(sx[2 * (i % 5) + 1], sc, u2f(x));
              }
              FENCE();
            } while (bad);
            const float cr = ex2(fminf(fminf(u2f(x), u2f(x1)), fminf(u2f(x2), u2f(x3_))) - u2f(x));
#pragma unroll
            for (int i = 1; i < 6; i++) m[i % 5] = pack_bf16(sx[2 * (i % 5)] * cr, sx[2 * (i % 5) + 1] * cr);
            sts128(ls + SM_PF, m[1], m[2], m[3], m[4]);
            sts32(ls - l12 + SM_PF + 512, m[0]);
            TV(19, n - 1);
          }
          TS(12);
          bar_sync(B_P, 96);
          PT(12, s == 0 && l16 == 0);
          OPAQUE_R(l16);
          {
            const unsigned char* pe = P.win + w_blk(w_ar(s) + (W_DS + 256) + (l16 & 0x60u) * 256 + (l16 & 16u) * 128, me);
            const uint32_t tp = gt32() + DLY_M3;
            if (s < NSEG - 2) F0LOAD();
            ETAT(tp, 0);
            uint32_t tg0; int n = 0;
#pragma unroll 1
            for (;;) {
              const uint2 e = ldg_r2(pe);
              tg0 = __reduce_max_sync(~0u, e.y);
              if (tg0 - tp >= 4096u) tg0 = tp;
              if ((!__any_sync(~0u, e.x != 16u) && (int)(tg0 - gt32()) < DLY_RR) || ++n >= SPIN_LIMIT) break;
            }
            sts32(sb + SM_Z + 32, tg0);
            TV(16, tg0); TV(7, kd - DLY_K);
            bar_arrive(B_GO, 96);
          }
          if (XPF && s + XPF < NSEG) {
            for (uint32_t i = xrank; i < 512; i += 32 * xcnt)
              asm volatile("prefetch.global.L2 [%0];" :: "l"(SP.x + (size_t)(s + XPF) * (SEG * DM) + i * 64));
            __syncwarp();
          }
          stg_2(P.win + (w_ar(s + 2) + cta * 256 + (l16 >> 8) * W_DS + ((l16 >> 1) & 127u)), 0u, 0u);
        }
        bar_sync(B_QK, 288);
      } else {
        const int mt = wq - 2;
        const uint32_t lt = ls + mt * 1024;
        const uint32_t vi0 = w_blk(w_mvx(h * 4, 0), me2) + mt * 1024;
        const int m3d = r ? -8192 : 8192;
#ifdef PROF
        const uint32_t epoch = gt32(); TST(-1, 30 + mt, l16, epoch);
#endif
        float ox[4][4], zx[4];
#pragma unroll
        for (int i = 0; i < 16; i++) ox[i >> 2][i & 3] = zx[i & 3] = 1.f;
        for (int s = 0;; s++) {
          const uint32_t tg = (s & 1) ^ 1, t2 = ((s >> 1) & 1) ^ 1;
          {
            OPAQUE_R(l16);
            const uint32_t m3i = (mt * 2 + r) * 8192 + (l16 & 0x70u) + ((l16 & 0x180u) << 1);
            const uint32_t m3j = (mt * 2 + (r ^ (l16 >> 7 & 1))) * 8192 + ((l16 & 64u) * 4 + (l16 & 48u) * 2 + (l16 & 16u)) * 16 + W_DS + (l16 & 0x70u);
            uint32_t m3c = sb + SM_MEM + mt * 8192 + cnt_line(l16 >> 4) * 128 + (l16 >> 2);
            const unsigned char* p3 = P.win + (m3i + w_ar(s - 1)); const unsigned char* pd = P.win + (m3j + w_ar(s - 1));
            OPAQUE_L(pd); OPAQUE_R(m3c);
#define XEPI() do { \
              const float i0 = rcpf(zx[0]), i1 = rcpf(zx[1]); \
              unsigned char* o = reinterpret_cast<unsigned char*>(g_ox + (size_t)((s - 1) * SEG + 8 * j) * (NH * DH) + h * DH + mt * 64) + ((l16 & 48u) * (NH * DH / 4) + ((l16 >> 2) & 0x70u)); \
              stg_4(o, make_uint4(pack_bf16(ox[0][0] * i0, ox[0][2] * i0), pack_bf16(ox[1][0] * i0, ox[1][2] * i0), pack_bf16(ox[2][0] * i0, ox[2][2] * i0), pack_bf16(ox[3][0] * i0, ox[3][2] * i0))); \
              stg_4(o + NH * DH * 2, make_uint4(pack_bf16(ox[0][1] * i1, ox[0][3] * i1), pack_bf16(ox[1][1] * i1, ox[1][3] * i1), pack_bf16(ox[2][1] * i1, ox[2][3] * i1), pack_bf16(ox[3][1] * i1, ox[3][3] * i1))); \
              TST(s - 1, 18, l16 | mt, TCLK()); } while (0)
            if (s > 0) XEPI();
            if (s == NSEG) break;
            if (s > 0) {
              M3PTR(s - 1);
              bar_sync(B_GO, 96);
              const uint32_t tg0 = lds32(sb + SM_Z + 32);
              while (tg0 - gt32() - 1u < 8192u) {}
              M3REQ();
            }
            FENCE();
            const int n = m3_check(sb, p3, pd, m3d, l16, m3c, mt, s);
            FENCE();
            TST(s, mt ? 21 : 0, l16, TCLK());
            TST(s, mt ? 22 : 17, l16, n);
            PT(6 + s, s < 5 && (l16 | mt) == 0);
          }
          uint4 va[8], vm[2], p0, q0; uint32_t p2, q2;
          const unsigned char* a0 = P.win + (vi0 + ((s & 1) << 20) + l16);
#define VALD() _Pragma("unroll") for (int i = 0; i < 4; i++) { va[i] = ldg_r4(a0 + (i >> 1) * 512 + (i & 1) * 2048); va[4 + i] = ldg_r4(a0 + 16384 + (i >> 1) * 512 + (i & 1) * 2048); }
          spin(DLY_WO);
          VALD();
          {
          PTRS();
          bar_sync(B_V, 320);
            const float4 u0 = lds128f(lt + SM_VP), w0 = lds128f(lt + SM_VP + 2048), u1 = lds128f(lt + SM_VP + 512), w1 = lds128f(lt + SM_VP + 2560);
            const uint32_t m0 = tagw(pack_bf16(u0.x + w0.x, u0.y + w0.y), tg), m1 = pack_bf16(u0.z + w0.z, u0.w + w0.w),
                           m2 = pack_bf16(u1.x + w1.x, u1.y + w1.y), m3 = pack_bf16(u1.z + w1.z, u1.w + w1.w);
            stg_r4(pw0, m0, m1, m2, m3);
            if (wq == 2) TS(10);
            FENCE();
            const uint32_t tv = clk32();
            while (clk32() - tv < (uint32_t)DLY_V) {}
            uint4 v[3]; int n = 0; uint32_t bada = 0;
#pragma unroll 1
            do {
              v[0] = ldg_r4(pr0); v[1] = ldg_r4(pr1); v[2] = ldg_r4(pr1 + 2048);
              if (n) {
                TST(s, __any_sync(~0u, bada & 1u) ? 26 : 24, l16, epoch);
                if (__any_sync(~0u, bada & 1u)) { VALD(); }
                if (s < NSEG - 1) ETA(DLY_KS - 192, 0);
              }
              n++;
              FENCE();
              bada = or3(x3(va[0].x, va[1].x, t2), x3(va[2].x, va[3].x, t2), x3(va[4].x, va[5].x, t2)) | x3(va[6].x, va[7].x, t2);
            } while (__any_sync(~0u, or3(bada, x3(v[0].x, v[1].x, tg), v[2].x ^ tg) & 1u) && n < SPIN_LIMIT);
            const uint4 A = make_uint4(addb2(m0, v[0].x), addb2(m1, v[0].y), addb2(m2, v[0].z), addb2(m3, v[0].w));
            const uint4 B = make_uint4(addb2(v[1].x, v[2].x), addb2(v[1].y, v[2].y), addb2(v[1].z, v[2].z), addb2(v[1].w, v[2].w));
            vm[0] = p ? B : A; vm[1] = p ? A : B;
            TST(s, 11, l16 | mt, TCLK()); TST(s, 29, l16 | (mt ^ 1), TCLK());
          }
          FENCE();
          if (s < NSEG - 1) {
          bar_sync(B_P, 96);
          p0 = lds128(ls + SM_PF); p2 = lds32(ls - l12 + SM_PF + 512);
          float o[4][4], z[4];
          PVM(o, z, p0, p2);
          PVE(o, z, ls + (SM_OF + mt * 512));
          bar_arrive(B_O, 192);
          }
          FENCE();
          TST(s, 8, l16 | mt, TCLK());
          bar_sync(B_PX, 96);
          q0 = lds128(ls + SM_PX); q2 = lds32(ls - l12 + SM_PX + 512);
          PVM(ox, zx, q0, q2);
          if (s < NSEG - 1) bar_arrive(B_O2, 224);
          FENCE();
          FENCE();
          if (s < NSEG - 1) bar_arrive(B_PXF, 96);
        }
      }
    }
  }
  asm volatile("barrier.cluster.arrive.relaxed.aligned;\nbarrier.cluster.wait.aligned;" ::: "memory");
#ifdef PER
  if (threadIdx.x == 0) atomicMax(&g_end[0], gt32());
#endif
}
#ifndef PW
#define PW 2
#endif
#ifndef G2_PD
#define G2_PD 300
#endif
#ifndef G2_HD
#define G2_HD 8000
#endif
#ifndef G2_B
#define G2_B 4
#endif
#ifndef G2_ST
#define G2_ST 6
#endif
#define G2_TB (G2_ST * 32768 + 1024)
#define G2_SMEM (G2_TB + 32768)
template <int AOFF, int BOFF>
static __device__ __forceinline__ void wgmma_n128_ta(float (&d)[64], uint32_t a16, uint32_t b16) {
  asm volatile(
      "{\n.reg .b32 t, u;\n.reg .b64 da, db;\nadd.u32 t, %64, %66;\nmov.b64 da, {t, %68};\nadd.u32 u, %65, %67;\nmov.b64 db, {u, %68};\n"
      "wgmma.mma_async.sync.aligned.m64n128k16.f32.bf16.bf16 "
      "{%0,%1,%2,%3,%4,%5,%6,%7,%8,%9,%10,%11,%12,%13,%14,%15,%16,%17,%18,%19,%20,%21,%22,%23,%24,%25,%26,%27,%28,%29,%30,%31,"
      "%32,%33,%34,%35,%36,%37,%38,%39,%40,%41,%42,%43,%44,%45,%46,%47,%48,%49,%50,%51,%52,%53,%54,%55,%56,%57,%58,%59,%60,%61,%62,%63}, "
      "da, db, 1, 1, 1, 1, 0;\n}"
      : "+f"(d[0]), "+f"(d[1]), "+f"(d[2]), "+f"(d[3]), "+f"(d[4]), "+f"(d[5]), "+f"(d[6]), "+f"(d[7]), "+f"(d[8]), "+f"(d[9]), "+f"(d[10]), "+f"(d[11]),
        "+f"(d[12]), "+f"(d[13]), "+f"(d[14]), "+f"(d[15]), "+f"(d[16]), "+f"(d[17]), "+f"(d[18]), "+f"(d[19]), "+f"(d[20]), "+f"(d[21]), "+f"(d[22]), "+f"(d[23]),
        "+f"(d[24]), "+f"(d[25]), "+f"(d[26]), "+f"(d[27]), "+f"(d[28]), "+f"(d[29]), "+f"(d[30]), "+f"(d[31]), "+f"(d[32]), "+f"(d[33]), "+f"(d[34]), "+f"(d[35]),
        "+f"(d[36]), "+f"(d[37]), "+f"(d[38]), "+f"(d[39]), "+f"(d[40]), "+f"(d[41]), "+f"(d[42]), "+f"(d[43]), "+f"(d[44]), "+f"(d[45]), "+f"(d[46]), "+f"(d[47]),
        "+f"(d[48]), "+f"(d[49]), "+f"(d[50]), "+f"(d[51]), "+f"(d[52]), "+f"(d[53]), "+f"(d[54]), "+f"(d[55]), "+f"(d[56]), "+f"(d[57]), "+f"(d[58]), "+f"(d[59]),
        "+f"(d[60]), "+f"(d[61]), "+f"(d[62]), "+f"(d[63])
      : "r"(a16), "r"(b16), "n"(AOFF >> 4), "n"(BOFF >> 4), "n"(DESC_HI(1024)));
}
__global__ void __cluster_dims__(2, 1, 1) __launch_bounds__(384, 1)
gemm2_kernel(const __grid_constant__ CUtensorMap tmo, const __grid_constant__ CUtensorMap tmw, const bf16* __restrict__ x, bf16* __restrict__ out, unsigned char* win) {
  extern __shared__ __align__(1024) unsigned char smem[];
  const uint32_t sb = smem_u32(smem), bars = sb + G2_ST * 32768;
  const int tid = threadIdx.x, lane = tid & 31, warp = __shfl_sync(~0u, tid >> 5, 0);
  const int r = blockIdx.x & 1, pp = blockIdx.x >> 1;
  const int n0 = (((pp >> G2_B) & 3) * 2 + r) * 128, m0 = ((pp & ((1 << G2_B) - 1)) | ((pp >> (G2_B + 2)) << G2_B)) * 128;
  if (tid == 0) {
    for (int i = 0; i < G2_ST; i++) { mbar_init(bars + i * 8, 1); mbar_init(bars + 64 + i * 8, 4); }
    asm volatile("fence.mbarrier_init.release.cluster;" ::: "memory");
  }
  if (tid == 32) { asm volatile("prefetch.tensormap [%0];" :: "l"(&tmw) : "memory"); asm volatile("prefetch.tensormap [%0];" :: "l"(&tmo) : "memory"); }
  __syncthreads();
  asm volatile("barrier.cluster.arrive.relaxed.aligned;" ::: "memory");
#define LW(kt, st) asm volatile("cp.async.bulk.tensor.5d.shared::cluster.global.mbarrier::complete_tx::bytes [%0], [%1, {%3, %4, %3, %3, %5}], [%2];" \
                     :: "r"(sb + (st) * 32768), "l"(&tmw), "r"(bars + (st) * 8), "r"(0), "r"(((kt) >> 1) * 16 + ((kt) & 1) * 4), "r"(n0 >> 6) : "memory")
#define LO(kt, st) asm volatile("cp.async.bulk.tensor.2d.shared::cluster.global.mbarrier::complete_tx::bytes.multicast::cluster [%0], [%1, {%3, %4}], [%2], %5;" \
                     :: "r"(sb + (st) * 32768 + 16384 + r * 8192), "l"(&tmo), "r"(bars + (st) * 8), "r"((kt) * 64), "r"(m0 + r * 64), "h"((uint16_t)3) : "memory")
  if (tid == 256) for (int kt = 0; kt < G2_ST; kt++) { mbar_expect_tx(bars + kt * 8, 32768); if (kt < PW) LW(kt, kt); }
  __syncwarp();
  asm volatile("barrier.cluster.wait.acquire.aligned;" ::: "memory");
  if (warp == 8) {
    if (lane == 0) {
      asm volatile("griddepcontrol.wait;" ::: "memory");
      for (int kt = 0; kt < G2_ST; kt++) { LO(kt, kt); if (kt >= PW) LW(kt, kt); spin(G2_PD); }
#pragma unroll 1
      for (int kt = G2_ST, st = 0, ph = 0; kt < 64; kt++) {
        mbar_wait(bars + 64 + st * 8, ph);
        mbar_expect_tx(bars + st * 8, 32768);
        LO(kt, st); LW(kt, st);
        if (++st == G2_ST) { st = 0; ph ^= 1; }
      }
    }
  } else if (warp > 8) {
    const int t = tid - 288, ch = t & 15;
    asm volatile("griddepcontrol.wait;" ::: "memory");
#ifdef PER
    if (t == 0) atomicMax(&g_end[3], gt32());
#endif
    spin(G2_HD);
    int idx[8];
#pragma unroll
    for (int c = 0; c < 8; c++) idx[c] = g_idx[c];
    const int gi = blockIdx.x * 96 + t;
    if (gi < 67) g_side[gi * 32] = 0u;
    if (gi == 0) g_sbar = 0u;
#pragma unroll 4
    for (int row = t >> 4; row < 128; row += 6) {
      const int tok = m0 + row;
      const uint4 xv = *reinterpret_cast<const uint4*>(x + (size_t)tok * DM + n0 + ch * 8);
      const float g = g_gate[tok], omg = rbf(1.f - g);
      int sel = -1;
#pragma unroll
      for (int c = 0; c < 8; c++) if (idx[c] == tok) sel = c;
      uint4 uv = make_uint4(0u, 0u, 0u, 0u);
      if (sel >= 0) uv = *reinterpret_cast<const uint4*>(g_upd + sel * DM + n0 + ch * 8);
      const uint32_t x4[4] = {xv.x, xv.y, xv.z, xv.w}, u4[4] = {uv.x, uv.y, uv.z, uv.w};
      uint32_t o4[4];
#pragma unroll
      for (int e = 0; e < 4; e++) {
        const float b0 = rbf(u2f(x4[e] << 16) + u2f(u4[e] << 16)), b1 = rbf(u2f(x4[e] & 0xffff0000u) + u2f(u4[e] & 0xffff0000u));
        o4[e] = pack_bf16(omg * b0, omg * b1);
      }
      sts128(sb + G2_TB + row * 256 + ch * 16, o4[0], o4[1], o4[2], o4[3]);
      if (ch == 0) sts32(bars + 512 + row * 4, pack_bf16(g, g));
    }
    bar_arrive(2, 352);
  } else {
    const int wg = warp >> 2;
    float d[64];
#pragma unroll
    for (int i = 0; i < 64; i++) d[i] = 0.f;
    const uint32_t e0 = mapa(bars + 64, 0), e1 = mapa(bars + 64, 1);
#ifdef PER
    if (threadIdx.x == 0) { mbar_wait(bars, 0); atomicMax(&g_end[4], gt32()); }
    __syncwarp();
#endif
    const uint32_t a16 = (((sb + wg * 8192) & 0x3FFFF) >> 4) | (64u << 16), b16 = (((sb + 16384) & 0x3FFFF) >> 4) | (1u << 16);
#pragma unroll 1
    for (int kt = 0, st = 0, ph = 0, ps = -1; kt < 64; kt++) {
      mbar_wait(bars + st * 8, ph);
      wg_fence();
      wgmma_n128_ta<0, 0>(d, a16 + st * 2048, b16 + st * 2048); wgmma_n128_ta<2048, 32>(d, a16 + st * 2048, b16 + st * 2048);
      wgmma_n128_ta<4096, 64>(d, a16 + st * 2048, b16 + st * 2048); wgmma_n128_ta<6144, 96>(d, a16 + st * 2048, b16 + st * 2048);
      wg_commit();
      asm volatile("wgmma.wait_group.sync.aligned 1;" ::: "memory");
      if (ps >= 0 && (tid & 127) == 0) {
        mbar_arrive_cluster_rlx(e0 + ps * 8); mbar_arrive_cluster_rlx(e1 + ps * 8);
      }
      ps = st;
      if (++st == G2_ST) { st = 0; ph ^= 1; }
    }
    wg_wait0();
#ifdef PER
    if (threadIdx.x == 0) atomicMax(&g_end[5], gt32());
#endif
    bar_sync(1, 256);
#pragma unroll
    for (int jj = 0; jj < 8; jj++) {
      const uint32_t q0 = pack_bf16(d[8 * jj], d[8 * jj + 1]), q1 = pack_bf16(d[8 * jj + 2], d[8 * jj + 3]);
      const uint32_t q2 = pack_bf16(d[8 * jj + 4], d[8 * jj + 5]), q3 = pack_bf16(d[8 * jj + 6], d[8 * jj + 7]);
      stsm4t(sb + (jj * 16 + (lane >> 4) * 8 + (lane & 7)) * 272 + (warp * 16 + ((lane >> 3) & 1) * 8) * 2, q0, q1, q2, q3);
    }
    bar_sync(2, 352);
#pragma unroll
    for (int it = 0; it < 8; it++) {
      const int row = it * 16 + (tid >> 4), ch = tid & 15, tok = m0 + row;
      const uint4 av = lds128(sb + row * 272 + ch * 16), tv = lds128(sb + G2_TB + row * 256 + ch * 16);
      const uint32_t g = lds32(bars + 512 + row * 4);
      *reinterpret_cast<uint4*>(out + (size_t)tok * DM + n0 + ch * 8) =
          make_uint4(addb2(mulb2(g, av.x), tv.x), addb2(mulb2(g, av.y), tv.y), addb2(mulb2(g, av.z), tv.z), addb2(mulb2(g, av.w), tv.w));
    }
  }
  asm volatile("barrier.cluster.arrive.relaxed.aligned;\nbarrier.cluster.wait.aligned;" ::: "memory");
#ifdef PER
  if (threadIdx.x == 0) atomicMax(&g_end[2], gt32());
#endif
}
#ifndef WPROM
#define WPROM CU_TENSOR_MAP_L2_PROMOTION_L2_128B
#endif
#ifndef PDL
#define PDL 1
#endif
typedef CUresult (*PFN_encodeTiled)(CUtensorMap*, CUtensorMapDataType, cuuint32_t, void*, const cuuint64_t*, const cuuint64_t*,
                                    const cuuint32_t*, const cuuint32_t*, CUtensorMapInterleave, CUtensorMapSwizzle,
                                    CUtensorMapL2promotion, CUtensorMapFloatOOBfill);

extern "C" void kernel_launch(void* const* d_in, const int* in_sizes, int n_in, void* d_out, int out_size) {
  const bf16* x = (const bf16*)d_in[0];
  const bf16* mem0 = (const bf16*)d_in[1];
  const bf16* Wq = (const bf16*)d_in[2];
  const bf16* Wk = (const bf16*)d_in[3];
  const bf16* Wv = (const bf16*)d_in[4];
  const bf16* Wo = (const bf16*)d_in[5];
  const bf16* w_r = (const bf16*)d_in[8];
  const bf16* w_gate = (const bf16*)d_in[9];
  const bf16* w_up = (const bf16*)d_in[10];
  const bf16* w_down = (const bf16*)d_in[11];
  const bf16* gate_w = (const bf16*)d_in[12];
  bf16* out = (bf16*)d_out;

  static PFN_encodeTiled encode = nullptr;
  if (!encode) {
    void* fn = nullptr; cudaDriverEntryPointQueryResult st;
    cudaGetDriverEntryPoint("cuTensorMapEncodeTiled", &fn, cudaEnableDefault, &st);
    encode = (PFN_encodeTiled)fn;
    cudaFuncSetAttribute(rec_kernel, cudaFuncAttributeMaxDynamicSharedMemorySize, SM_TOTAL);
    cudaFuncSetAttribute(gemm2_kernel, cudaFuncAttributeMaxDynamicSharedMemorySize, G2_SMEM);
  }
  CUtensorMap tmx;
  {
    cuuint64_t gd[3] = {64, S_TOK, DM / 64};
    cuuint64_t gs[2] = {DM * 2, 128};
    cuuint32_t bx[3] = {64, SEG, 4};
    cuuint32_t es[3] = {1, 1, 1};
    encode(&tmx, CU_TENSOR_MAP_DATA_TYPE_BFLOAT16, 3, (void*)x, gd, gs, bx, es, CU_TENSOR_MAP_INTERLEAVE_NONE,
           CU_TENSOR_MAP_SWIZZLE_128B, CU_TENSOR_MAP_L2_PROMOTION_L2_128B, CU_TENSOR_MAP_FLOAT_OOB_FILL_NONE);
  }
  bf16* ox;
  cudaGetSymbolAddress((void**)&ox, g_ox);
  CUtensorMap tmo, tmw, tmw3;
  {
    cuuint64_t gd[2] = {NH * DH, S_TOK}; cuuint64_t gs[1] = {NH * DH * 2}; cuuint32_t bx[2] = {64, 64}; cuuint32_t es[3] = {1, 1, 1};
    encode(&tmo, CU_TENSOR_MAP_DATA_TYPE_BFLOAT16, 2, (void*)ox, gd, gs, bx, es, CU_TENSOR_MAP_INTERLEAVE_NONE,
           CU_TENSOR_MAP_SWIZZLE_128B, CU_TENSOR_MAP_L2_PROMOTION_L2_128B, CU_TENSOR_MAP_FLOAT_OOB_FILL_NONE);
    cuuint64_t gd2[2] = {DM, NH * DH}; cuuint64_t gs2[1] = {DM * 2}; cuuint32_t bx2[2] = {64, 64};
    encode(&tmw, CU_TENSOR_MAP_DATA_TYPE_BFLOAT16, 2, (void*)Wo, gd2, gs2, bx2, es, CU_TENSOR_MAP_INTERLEAVE_NONE,
           CU_TENSOR_MAP_SWIZZLE_128B, CU_TENSOR_MAP_L2_PROMOTION_L2_128B, CU_TENSOR_MAP_FLOAT_OOB_FILL_NONE);
  }
  {
    cuuint64_t gd[5] = {64, NH * DH / 8, 2, 8, DM / 64}; cuuint64_t gs[4] = {8 * DM * 2, 64 * DM * 2, DM * 2, 128}; cuuint32_t bx[5] = {64, 4, 2, 8, 2}; cuuint32_t es[5] = {1, 1, 1, 1, 1};
    encode(&tmw3, CU_TENSOR_MAP_DATA_TYPE_BFLOAT16, 5, (void*)Wo, gd, gs, bx, es, CU_TENSOR_MAP_INTERLEAVE_NONE,
           CU_TENSOR_MAP_SWIZZLE_128B, CU_TENSOR_MAP_L2_PROMOTION_L2_128B, CU_TENSOR_MAP_FLOAT_OOB_FILL_NONE);
  }
  unsigned char* win;
  cudaGetSymbolAddress((void**)&win, g_win);
  win = (unsigned char*)(((uintptr_t)win + (2u << 20) - 1) & ~(uintptr_t)((2u << 20) - 1));
  WMaps W;
  {
    cuuint64_t gd[2] = {NH * DH, DM}; cuuint64_t gs[1] = {NH * DH * 2}; cuuint32_t b32[2] = {32, 128}, b64[2] = {64, 128}; cuuint32_t es[2] = {1, 1};
    encode(&W.q, CU_TENSOR_MAP_DATA_TYPE_BFLOAT16, 2, (void*)Wq, gd, gs, b32, es, CU_TENSOR_MAP_INTERLEAVE_NONE,
           CU_TENSOR_MAP_SWIZZLE_64B, WPROM, CU_TENSOR_MAP_FLOAT_OOB_FILL_NONE);
    encode(&W.k, CU_TENSOR_MAP_DATA_TYPE_BFLOAT16, 2, (void*)Wk, gd, gs, b32, es, CU_TENSOR_MAP_INTERLEAVE_NONE,
           CU_TENSOR_MAP_SWIZZLE_64B, WPROM, CU_TENSOR_MAP_FLOAT_OOB_FILL_NONE);
    encode(&W.v, CU_TENSOR_MAP_DATA_TYPE_BFLOAT16, 2, (void*)Wv, gd, gs, b64, es, CU_TENSOR_MAP_INTERLEAVE_NONE,
           CU_TENSOR_MAP_SWIZZLE_128B, WPROM, CU_TENSOR_MAP_FLOAT_OOB_FILL_NONE);
  }
  RecParams P{mem0, win};
  SideParams SP{x, w_r, w_gate, w_up, w_down, gate_w, Wo};
  rec_kernel<<<NCTA + 4, 384, SM_TOTAL, cudaStreamPerThread>>>(tmx, tmw, W, P, SP);
  {
    cudaLaunchConfig_t cfg = {};
    cfg.gridDim = dim3(NCTA); cfg.blockDim = dim3(384); cfg.dynamicSmemBytes = G2_SMEM; cfg.stream = cudaStreamPerThread;
    cudaLaunchAttribute at[1];
    at[0].id = cudaLaunchAttributeProgrammaticStreamSerialization; at[0].val.programmaticStreamSerializationAllowed = 1;
    cfg.attrs = at; cfg.numAttrs = PDL;
    cudaLaunchKernelEx(&cfg, gemm2_kernel, tmo, tmw3, x, out, win);
  }
}
```
